```python
import torch

def _softmax(x, axis=-1):
    return torch.softmax(x, dim=axis)
def _gelu(x):
    return torch.nn.functional.gelu(x, approximate="tanh")
def _silu(x):
    return torch.nn.functional.silu(x)
def _sigmoid(x):
    return torch.sigmoid(x)
def _layernorm(x, axis=-1, eps=1e-5):
    m = x.mean(dim=axis, keepdim=True)
    v = x.var(dim=axis, keepdim=True, unbiased=False)
    return (x - m) / torch.sqrt(v + eps)
def _scatter_add(tgt, idx, src, axis=0):
    return tgt.clone().index_add_(axis, idx, src)
def _segment_sum(src, seg, n):
    out = torch.zeros((n,) + src.shape[1:], dtype=src.dtype)
    return out.index_add_(0, seg, src)
def _pad(x, pw):
    flat = tuple(v for pair in reversed(pw) for v in pair)
    return torch.nn.functional.pad(x, flat)

kernel_name = 'sequential_preLN__ssm_conv_h3__moe_arch_mod__prompt'

def setup_inputs():

    _w = (lambda a: (lambda t: t.to(torch.bfloat16) if t.is_floating_point() else t)(torch.as_tensor(a)))
    def _A_setup():
        B, S, D = 1, 2048, 640
        ks = 4
        return {
            "q": _w((lambda *s: torch.randn(*s, dtype=torch.bfloat16) * 0.05)(B, S, D)),
            "k": _w((lambda *s: torch.randn(*s, dtype=torch.bfloat16) * 0.2)(B, S, D)),
            "v": _w((lambda *s: torch.randn(*s, dtype=torch.bfloat16) * 0.2)(B, S, D)),
            "shift_k": _w((lambda *s: torch.randn(*s, dtype=torch.bfloat16) * 0.2)(D, ks) * 0.5),
            "ssm_k": _w((lambda *s: torch.randn(*s, dtype=torch.bfloat16) * 0.8)(D, S) * (1.0 / S ** 0.5)),
            "ssm_D": _w((lambda *s: torch.randn(*s, dtype=torch.bfloat16) * 0.2)(D)),
        }
    _A_in = _A_setup()

    def _B_setup():
        B, S, D, F, C = 1, 2048, 640, 1536, 1
        return {
            "x": _w((lambda *s: torch.randn(*s, dtype=torch.bfloat16) * 0.05)(B, S, D)),
            "w_r": _w((lambda *s: torch.randn(*s, dtype=torch.bfloat16) * 0.05)(D)),
            "w_gate": _w((lambda *s: torch.randn(*s, dtype=torch.bfloat16) * 0.05)(D, F)),
            "w_up": _w((lambda *s: torch.randn(*s, dtype=torch.bfloat16) * 0.05)(D, F)),
            "w_down": _w((lambda *s: torch.randn(*s, dtype=torch.bfloat16) * 0.05)(F, D)),
        }
    _B_in = _B_setup()

    return {
        "A_q": _A_in["q"],
        "A_k": _A_in["k"],
        "A_v": _A_in["v"],
        "A_shift_k": _A_in["shift_k"],
        "A_ssm_k": _A_in["ssm_k"],
        "A_ssm_D": _A_in["ssm_D"],
        "B_x": _B_in["x"],
        "B_w_r": _B_in["w_r"],
        "B_w_gate": _B_in["w_gate"],
        "B_w_up": _B_in["w_up"],
        "B_w_down": _B_in["w_down"],
    }

def reference(A_q, A_k, A_v, A_shift_k, A_ssm_k, A_ssm_D, B_x, B_w_r, B_w_gate, B_w_up, B_w_down):
    def _A_ref(q, k, v, shift_k, ssm_k, ssm_D):
        B, S, D = q.shape
        ks = shift_k.shape[-1]
        k_pad = _pad(k, ((0, 0), (ks - 1, 0), (0, 0)))
        k_shift = torch.zeros_like(k)
        for t in range(ks):
            k_shift = k_shift + k_pad[:, t:t + S, :] * shift_k[:, ks - 1 - t][None, None, :]
        kv = k_shift * v
        L = 2 * S
        kv_pad = _pad(kv, ((0, 0), (0, S), (0, 0)))
        kf_pad = _pad(ssm_k, ((0, 0), (0, S)))
        kv_f = (lambda x, axes=(-2,-1): torch.fft.rfft2(x.float(), dim=axes))(kv_pad[:, None, :, :], axes=(1, 2))
        kf_f = (lambda x, axes=(-2,-1): torch.fft.rfft2(x.float(), dim=axes))(kf_pad[:, None, :], axes=(1, 2))
        kf_f = (lambda x, *d: x.permute(*d))(kf_f, 1, 2, 0)
        y_f = kv_f * kf_f[None, :, :, :]
        y = (lambda x, s, axes=(-2,-1): torch.fft.irfft2(x, s=s, dim=axes).to(torch.bfloat16))(y_f, (1, L), axes=(1, 2))[:, 0, :S, :]
        y = y + kv * ssm_D[None, None, :]
        return q * y

    def _B_ref(x, w_r, w_gate, w_up, w_down):
        B, S, D = x.shape
        C = 1
        r = x @ w_r
        idx = torch.argsort(-r, axis=-1)[:, :C]
        idx_e = (lambda x, n, axis: torch.repeat_interleave(x, n, dim=axis))(idx.reshape(B, C, 1), D, axis=2)
        x_sel = (lambda x, i, axis: torch.take_along_dim(x, i, dim=axis))(x, idx_e, axis=1)
        g = _silu(x_sel @ w_gate)
        u = x_sel @ w_up
        y = (g * u) @ w_down
        r_sel = _sigmoid((lambda x, i, axis: torch.take_along_dim(x, i, dim=axis))(r, idx, axis=1))
        y = y * r_sel.reshape(B, C, 1)
        b_off = (torch.arange(B) * S).reshape(B, 1)
        flat_idx = (idx + b_off).reshape(B * C)
        zero = (x * 0.0).reshape(B * S, D)
        upd = _scatter_add(zero, flat_idx, y.reshape(B * C, D), axis=0)
        return x + upd.reshape(B, S, D)

    x = A_q
    h = x + _A_ref(_layernorm(x, axis=-1), A_k, A_v, A_shift_k, A_ssm_k, A_ssm_D)
    h2 = h + _B_ref(_layernorm(h, axis=-1), B_w_r, B_w_gate, B_w_up, B_w_down)
    return h2
```

```cpp
#include <cuda_runtime.h>
#include <cuda_bf16.h>
#include <stdint.h>

namespace {

typedef __nv_bfloat16 bf16;
typedef __nv_bfloat162 bf162;

constexpr int S_ = 2048, D_ = 640, F_ = 1536;
constexpr int NCTA = 128, CPC = 5, NTHR = 384;
constexpr int UPAD = 136, USTR = 2192;
constexpr int TABW = 1040;
constexpr int ZPB = 132;
constexpr int QSTR = 648;
constexpr int N1 = 64;
constexpr int N2 = 40;
constexpr int SPIN_LIMIT = 1 << 19;

struct __align__(128) Smem {
  bf16 u[CPC][USTR];
  uint32_t tab[CPC][2][TABW];
  float z[2][4][ZPB * 16];
  bf16 q[16][QSTR];
  uint4 w[3840];
  float qstat[16][2];
  float2 st[16][5];
  float rp[16][5];
  unsigned long long mbar;
  uint32_t target;
  uint32_t best;
  uint32_t win;
};

__device__ uint4 g_y2[D_ * S_ / 8];
__device__ uint32_t g_keys[NCTA];
__device__ uint4 g_cand[NCTA][2][80];
__device__ uint4 g_act[F_ / 8];
__device__ unsigned int g_ctr;
#define STAMP(i)

__device__ __forceinline__ uint32_t smem_u32(const void* p) { return (uint32_t)__cvta_generic_to_shared(p); }
__device__ __forceinline__ void wg_fence() { asm volatile("wgmma.fence.sync.aligned;" ::: "memory"); }
__device__ __forceinline__ void wg_commit() { asm volatile("wgmma.commit_group.sync.aligned;" ::: "memory"); }
template <int N> __device__ __forceinline__ void wg_wait() { asm volatile("wgmma.wait_group.sync.aligned %0;" ::"n"(N) : "memory"); }
__device__ __forceinline__ void bar_sync(int id, int n) { asm volatile("bar.sync %0, %1;" ::"r"(id), "r"(n) : "memory"); }
__device__ __forceinline__ void bar_arrive(int id, int n) { asm volatile("bar.arrive %0, %1;" ::"r"(id), "r"(n) : "memory"); }
__device__ __forceinline__ bf162 u2b(uint32_t u) { return *reinterpret_cast<bf162*>(&u); }
__device__ __forceinline__ uint32_t b2u(bf162 b) { return *reinterpret_cast<uint32_t*>(&b); }
__device__ __forceinline__ float lo_f(uint32_t u) { return __uint_as_float(u << 16); }
__device__ __forceinline__ float hi_f(uint32_t u) { return __uint_as_float(u & 0xFFFF0000u); }
__device__ __forceinline__ float rbf(float x) { return __bfloat162float(__float2bfloat16_rn(x)); }
__device__ __forceinline__ uint32_t pack2(float a, float b) { return b2u(__floats2bfloat162_rn(a, b)); }
__device__ __forceinline__ uint32_t enc(uint32_t w) {
  uint32_t e = ~w;
  if ((e & 0xFFFFu) == 0u) e |= 0x8000u;
  if ((e >> 16) == 0u) e |= 0x80000000u;
  return e;
}
__device__ __forceinline__ uint4 enc4(uint4 v) { return make_uint4(enc(v.x), enc(v.y), enc(v.z), enc(v.w)); }
__device__ __forceinline__ uint4 ld_poll4(const uint4* p) {
  uint4 v;
  asm volatile("ld.relaxed.gpu.global.v4.u32 {%0,%1,%2,%3}, [%4];" : "=r"(v.x), "=r"(v.y), "=r"(v.z), "=r"(v.w) : "l"(p) : "memory");
  return v;
}
__device__ __forceinline__ bool ready4(uint4 v) { return v.x != 0u && v.y != 0u && v.z != 0u && v.w != 0u; }
__device__ __forceinline__ uint4 poll4(const uint4* p) {
  uint4 v = ld_poll4(p);
  int it = 0;
  while (!ready4(v) && ++it < SPIN_LIMIT) v = ld_poll4(p);
  return make_uint4(~v.x, ~v.y, ~v.z, ~v.w);
}
__device__ __forceinline__ void st_pub4(uint4* p, uint4 v) {
  asm volatile("st.relaxed.gpu.global.v4.u32 [%0], {%1,%2,%3,%4};" ::"l"(p), "r"(v.x), "r"(v.y), "r"(v.z), "r"(v.w) : "memory");
}
__device__ __forceinline__ float fdivr(float a, float d, float r) {
  float q = a * r;
  float e = fmaf(-q, d, a);
  return fmaf(e, r, q);
}

template <bool FIRST> __device__ __forceinline__ void wgmma32(float (&d)[16], const uint32_t* a, uint64_t desc) {
  if (FIRST) {
    asm volatile("wgmma.mma_async.sync.aligned.m64n32k16.f32.bf16.bf16 {%0,%1,%2,%3,%4,%5,%6,%7,%8,%9,%10,%11,%12,%13,%14,%15}, {%16,%17,%18,%19}, %20, 0, 1, 1, 0;"
                 : "+f"(d[0]), "+f"(d[1]), "+f"(d[2]), "+f"(d[3]), "+f"(d[4]), "+f"(d[5]), "+f"(d[6]), "+f"(d[7]),
                   "+f"(d[8]), "+f"(d[9]), "+f"(d[10]), "+f"(d[11]), "+f"(d[12]), "+f"(d[13]), "+f"(d[14]), "+f"(d[15])
                 : "r"(a[0]), "r"(a[1]), "r"(a[2]), "r"(a[3]), "l"(desc));
  } else {
    asm volatile("wgmma.mma_async.sync.aligned.m64n32k16.f32.bf16.bf16 {%0,%1,%2,%3,%4,%5,%6,%7,%8,%9,%10,%11,%12,%13,%14,%15}, {%16,%17,%18,%19}, %20, 1, 1, 1, 0;"
                 : "+f"(d[0]), "+f"(d[1]), "+f"(d[2]), "+f"(d[3]), "+f"(d[4]), "+f"(d[5]), "+f"(d[6]), "+f"(d[7]),
                   "+f"(d[8]), "+f"(d[9]), "+f"(d[10]), "+f"(d[11]), "+f"(d[12]), "+f"(d[13]), "+f"(d[14]), "+f"(d[15])
                 : "r"(a[0]), "r"(a[1]), "r"(a[2]), "r"(a[3]), "l"(desc));
  }
}

template <int G> __device__ __forceinline__ void load_a(uint32_t (&a)[8], const uint32_t* tp) {
#pragma unroll
  for (int q = 0; q < 2; q++) {
    const int e = 2 * G + q;
    a[4 * q + 0] = tp[-64 * e];
    a[4 * q + 1] = tp[-64 * e - 32];
    a[4 * q + 2] = tp[-64 * e + 4];
    a[4 * q + 3] = tp[-64 * e - 28];
  }
}
__device__ __forceinline__ void load_a_all(uint32_t (&a)[8][8], const uint32_t* tp) {
  load_a<0>(a[0], tp); load_a<1>(a[1], tp); load_a<2>(a[2], tp); load_a<3>(a[3], tp);
  load_a<4>(a[4], tp); load_a<5>(a[5], tp); load_a<6>(a[6], tp); load_a<7>(a[7], tp);
}
template <int G> __device__ __forceinline__ void issue_g(float (&acc)[8][16], uint32_t (&a)[8], uint64_t desc0) {
  wg_fence();
#pragma unroll
  for (int q = 0; q < 2; q++) {
#pragma unroll
    for (int b = G; b < 8; b++) {
      const int delta = 2 * b - (2 * G + q);
      if (G == 0 && q == 0) wgmma32<true>(acc[b], &a[4 * q], desc0 + (uint64_t)(int64_t)(16 * delta));
      else wgmma32<false>(acc[b], &a[4 * q], desc0 + (uint64_t)(int64_t)(16 * delta));
    }
  }
  wg_commit();
}
template <int B> __device__ __forceinline__ void fence_blk(float (&acc)[8][16]) {
#pragma unroll
  for (int i = 0; i < 16; i++) asm volatile("" : "+f"(acc[B][i])::"memory");
}
__device__ __forceinline__ void fence_a(uint32_t (&a)[8]) {
#pragma unroll
  for (int i = 0; i < 8; i++) asm volatile("" : "+r"(a[i])::"memory");
}
template <int B> __device__ __forceinline__ void sts_blk(float (&acc)[8][16], float* zw, int off_even, int off_odd) {
#pragma unroll
  for (int jj = 0; jj < 4; jj++) {
    const int j = 4 * B + jj;
    float p0 = acc[B][4 * jj + 0], p1 = acc[B][4 * jj + 1];
    if (jj > 0) { p0 += acc[B][4 * (jj - 1) + 2]; p1 += acc[B][4 * (jj - 1) + 3]; }
    else if (B > 0) { p0 += acc[B > 0 ? B - 1 : 0][14]; p1 += acc[B > 0 ? B - 1 : 0][15]; }
    zw[64 * j + off_even] = p0;
    zw[64 * j + off_odd] = p1;
  }
}
__device__ __forceinline__ int tile_perm(int ch) { return ch ^ (((ch >> 3) & 3) << 1); }

__device__ __forceinline__ void wait_cleared(uint32_t target) {
  uint32_t v;
  int it = 0;
  do {
    asm volatile("ld.acquire.gpu.global.u32 %0, [%1];" : "=r"(v) : "l"(&g_ctr) : "memory");
  } while ((int)(v - target) < 0 && ++it < SPIN_LIMIT);
}

__global__ void __cluster_dims__(2, 1, 1) __launch_bounds__(NTHR, 1)
fused_kernel(const bf16* __restrict__ gq, const bf16* __restrict__ gk, const bf16* __restrict__ gv,
             const bf16* __restrict__ gsk, const bf16* __restrict__ gh, const bf16* __restrict__ gD,
             const bf16* __restrict__ gwr, const bf16* __restrict__ gwg, const bf16* __restrict__ gwu,
             const bf16* __restrict__ gwd, bf16* __restrict__ gout) {
  extern __shared__ __align__(128) unsigned char smraw[];
  Smem& sm = *reinterpret_cast<Smem*>(smraw);
  const int tid = threadIdx.x;
  const int cta = blockIdx.x;
  const int rank = cta & 1;
  const int c0 = cta * CPC;
  const int cc0 = (cta >> 1) * 10;
  const int lane = tid & 31;
  const int wid = tid >> 5;
  STAMP(0);
  asm volatile("barrier.cluster.arrive.relaxed.aligned;" ::: "memory");

  {
    uint4 hv[4];
    uint32_t hp[4];
#pragma unroll
    for (int i = 0; i < 4; i++) {
      const int t = tid + NTHR * i;
      hp[i] = 0;
      if (t < CPC * 256) {
        const bf16* p = gh + (size_t)c0 * S_ + t * 8;
        hv[i] = __ldg(reinterpret_cast<const uint4*>(p));
        if (t & 255) hp[i] = __ldg(reinterpret_cast<const unsigned short*>(p) - 1);
      }
    }
    uint32_t kk[19], vv[16];
    uint2 s0, s1;
    const int pr = tid % 5, grp = tid / 5;
    const int r0 = 1024 * rank + 16 * grp;
    if (tid < 320) {
      const uint32_t* kp = reinterpret_cast<const uint32_t*>(gk + (size_t)r0 * D_ + cc0 + 2 * pr);
      const uint32_t* vp = reinterpret_cast<const uint32_t*>(gv + (size_t)r0 * D_ + cc0 + 2 * pr);
#pragma unroll
      for (int i = 0; i < 19; i++) kk[i] = (i >= 3 || r0 > 0) ? __ldg(kp + (i - 3) * (D_ / 2)) : 0u;
#pragma unroll
      for (int i = 0; i < 16; i++) vv[i] = __ldg(vp + i * (D_ / 2));
      s0 = __ldg(reinterpret_cast<const uint2*>(gsk + (cc0 + 2 * pr) * 4));
      s1 = __ldg(reinterpret_cast<const uint2*>(gsk + (cc0 + 2 * pr + 1) * 4));
    }
    {
      const uint4 zz = make_uint4(0, 0, 0, 0);
      for (int t = tid; t < CPC * 256; t += NTHR) g_y2[c0 * 256 + t] = zz;
      if (tid < 160) (&g_cand[cta][0][0])[tid] = zz;
      else if (tid < 163) { if (cta < N1) g_act[cta * 3 + (tid - 160)] = zz; }
      else if (tid == 163) g_keys[cta] = 0u;
      if (tid < CPC * 17) *reinterpret_cast<uint4*>(&sm.u[tid / 17][(tid % 17) * 8]) = zz;
      else if (tid < CPC * 17 + 40) { const int t = tid - CPC * 17; *reinterpret_cast<uint4*>(&sm.tab[t >> 3][(t >> 2) & 1][1024 + 4 * (t & 3)]) = zz; }
      else if (tid < CPC * 17 + 40 + 128) { const int t = tid - CPC * 17 - 40; *reinterpret_cast<uint4*>(&sm.z[t >> 6][(t >> 4) & 3][(t & 15) * 4]) = zz; }
      if (tid == 0) {
        asm volatile("mbarrier.init.shared.b64 [%0], 1;" ::"r"(smem_u32(&sm.mbar)) : "memory");
      }
    }
#pragma unroll
    for (int i = 0; i < 4; i++) {
      const int t = tid + NTHR * i;
      if (t < CPC * 256) {
        const int c = t >> 8, ch = t & 255;
        uint4 h = hv[i], r1, rr;
        r1.x = __byte_perm(h.w, 0, 0x1032); r1.y = __byte_perm(h.z, 0, 0x1032);
        r1.z = __byte_perm(h.y, 0, 0x1032); r1.w = __byte_perm(h.x, 0, 0x1032);
        rr.x = __byte_perm(h.w, h.z, 0x7610); rr.y = __byte_perm(h.z, h.y, 0x7610);
        rr.z = __byte_perm(h.y, h.x, 0x7610); rr.w = __byte_perm(h.x, hp[i], 0x5410);
        *reinterpret_cast<uint4*>(&sm.tab[c][0][(255 - ch) * 4]) = rr;
        *reinterpret_cast<uint4*>(&sm.tab[c][1][(255 - ch) * 4]) = r1;
      }
    }
    __syncwarp();
    asm volatile("barrier.cluster.wait.aligned;" ::: "memory");
    if (tid < 320) {
      const bf162 w0 = u2b(__byte_perm(s0.x, s1.x, 0x5410)), w1 = u2b(__byte_perm(s0.x, s1.x, 0x7632));
      const bf162 w2 = u2b(__byte_perm(s0.y, s1.y, 0x5410)), w3 = u2b(__byte_perm(s0.y, s1.y, 0x7632));
      uint32_t kv[16];
#pragma unroll
      for (int i = 0; i < 16; i++) {
        bf162 a = __hmul2_rn(u2b(kk[i]), w3);
        a = __hadd2_rn(a, __hmul2_rn(u2b(kk[i + 1]), w2));
        a = __hadd2_rn(a, __hmul2_rn(u2b(kk[i + 2]), w1));
        a = __hadd2_rn(a, __hmul2_rn(u2b(kk[i + 3]), w0));
        kv[i] = b2u(__hmul2_rn(a, u2b(vv[i])));
      }
#pragma unroll
      for (int e = 0; e < 2; e++) {
        const int ch10 = 2 * pr + e;
        const int owner = ch10 >= 5 ? 1 : 0;
        const int cl = ch10 - 5 * owner;
        uint32_t la = smem_u32(&sm.u[cl][UPAD + r0]), ra;
        asm("mapa.shared::cluster.u32 %0, %1, %2;" : "=r"(ra) : "r"(la), "r"(owner));
        const uint32_t sel = e ? 0x7632u : 0x5410u;
#pragma unroll
        for (int hb = 0; hb < 2; hb++) {
          uint32_t x0 = __byte_perm(kv[8 * hb + 0], kv[8 * hb + 1], sel), x1 = __byte_perm(kv[8 * hb + 2], kv[8 * hb + 3], sel);
          uint32_t x2 = __byte_perm(kv[8 * hb + 4], kv[8 * hb + 5], sel), x3 = __byte_perm(kv[8 * hb + 6], kv[8 * hb + 7], sel);
          asm volatile("st.shared::cluster.v4.u32 [%0], {%1,%2,%3,%4};" ::"r"(ra + 16 * hb), "r"(x0), "r"(x1), "r"(x2), "r"(x3) : "memory");
        }
      }
    }
    asm volatile("fence.proxy.async;" ::: "memory");
    __syncwarp();
    asm volatile("barrier.cluster.arrive.release.aligned;" ::: "memory");
    asm volatile("barrier.cluster.wait.acquire.aligned;" ::: "memory");
    asm volatile("fence.proxy.async;" ::: "memory");
  }
  STAMP(1);

  const int wg = __shfl_sync(0xffffffffu, tid >> 7, 0);
  const int wtid = tid & 127;
  uint4* tile = reinterpret_cast<uint4*>(&sm.tab[0][0][0]);
  if (wg < 2) {
    asm volatile("setmaxnreg.inc.sync.aligned.u32 224;");
    const int w = (tid >> 5) & 3, g = lane >> 2, tq = lane & 3;
    float* zw = sm.z[wg][w];
    const int sw = 3 * (((tq + w) >> 1) & 1);
    const int off_even = 16 * (tq + w) + 4 * ((0 + (g >> 2)) ^ sw) + (g & 3);
    const int off_odd = 16 * (tq + w) + 4 * ((2 + (g >> 2)) ^ sw) + (g & 3);
    uint32_t a[8][8];
    const uint32_t* tp = &sm.tab[wg][g & 1][1019 - 8 * w - (g >> 1) + tq];
    load_a_all(a, tp);
    float acc[8][16];
#pragma unroll
    for (int b = 0; b < 8; b++)
#pragma unroll
      for (int i = 0; i < 16; i++) acc[b][i] = 0.f;
#pragma unroll 1
    for (int c = wg; c < CPC; c += 2) {
      const uint64_t desc = (uint64_t)((smem_u32(&sm.u[c][UPAD - 8]) & 0x3FFFF) >> 4) | ((uint64_t)1 << 16) | ((uint64_t)8 << 32);
      if (c > 0) bar_sync(1 + wg, 256);
      issue_g<0>(acc, a[0], desc);
      issue_g<1>(acc, a[1], desc);
      issue_g<2>(acc, a[2], desc);
      issue_g<3>(acc, a[3], desc);
      issue_g<4>(acc, a[4], desc);
      issue_g<5>(acc, a[5], desc);
      if (c + 1 < CPC) bar_arrive(1 + (wg ^ 1), 256);
      issue_g<6>(acc, a[6], desc);
      issue_g<7>(acc, a[7], desc);
      if (c >= 2) bar_sync(5 + wg, 256);
      wg_wait<4>();
      fence_blk<0>(acc); fence_blk<1>(acc); fence_blk<2>(acc); fence_blk<3>(acc);
      sts_blk<0>(acc, zw, off_even, off_odd);
      sts_blk<1>(acc, zw, off_even, off_odd);
      sts_blk<2>(acc, zw, off_even, off_odd);
      sts_blk<3>(acc, zw, off_even, off_odd);
      wg_wait<0>();
      fence_blk<4>(acc); fence_blk<5>(acc); fence_blk<6>(acc); fence_blk<7>(acc);
#pragma unroll
      for (int i = 0; i < 8; i++) fence_a(a[i]);
      sts_blk<4>(acc, zw, off_even, off_odd);
      sts_blk<5>(acc, zw, off_even, off_odd);
      sts_blk<6>(acc, zw, off_even, off_odd);
      sts_blk<7>(acc, zw, off_even, off_odd);
      bar_arrive(3 + wg, 256);
      tp += 2 * 2 * TABW;
      if (c + 2 < CPC) load_a_all(a, tp);
    }
    STAMP(2 + wg);
    asm volatile("setmaxnreg.dec.sync.aligned.u32 168;");
    if (wg == 1) {
      bar_sync(7, 160);
      wait_cleared(sm.target);
#pragma unroll 1
      for (int cc = 0; cc < 4; cc++) {
        const int ch = wtid * 5 + cc;
        const uint4* src = g_y2 + ch * 256 + cta * 2;
        uint4 v0 = ld_poll4(src), v1 = ld_poll4(src + 1);
        int it = 0;
        while (!ready4(v0) && ++it < SPIN_LIMIT) v0 = ld_poll4(src);
        while (!ready4(v1) && ++it < SPIN_LIMIT) v1 = ld_poll4(src + 1);
        const int pc = tile_perm(ch);
        tile[pc] = make_uint4(~v0.x, ~v0.y, ~v0.z, ~v0.w);
        tile[640 + pc] = make_uint4(~v1.x, ~v1.y, ~v1.z, ~v1.w);
      }
    }
  } else {
    asm volatile("setmaxnreg.dec.sync.aligned.u32 56;");
    if (wtid == 0) {
      __threadfence();
      const unsigned old = atomicAdd(&g_ctr, 1u);
      sm.target = (old / NCTA + 1u) * NCTA;
      const uint32_t mb = smem_u32(&sm.mbar);
      asm volatile("mbarrier.arrive.expect_tx.shared.b64 _, [%0], %1;" ::"r"(mb), "r"(16 * D_ * 2) : "memory");
#pragma unroll 1
      for (int r = 0; r < 16; r++)
        asm volatile("cp.async.bulk.shared::cluster.global.mbarrier::complete_tx::bytes [%0], [%1], %2, [%3];" ::"r"(smem_u32(&sm.q[r][0])),
                     "l"(gq + (size_t)(cta * 16 + r) * D_), "r"(D_ * 2), "r"(mb) : "memory");
    }
    if (wtid < 32) bar_arrive(7, 160);
    if (cta < N1) {
#pragma unroll 2
      for (int i = wtid; i < 3840; i += 128) {
        const int m = i >= 1920 ? 1 : 0, idx = i - 1920 * m, row = idx / 3, hc = idx - 3 * row;
        const bf16* src = (m ? gwu : gwg) + (size_t)row * F_ + cta * 24 + hc * 8;
        asm volatile("cp.async.cg.shared.global [%0], [%1], 16;" ::"r"(smem_u32(&sm.w[i])), "l"(src) : "memory");
      }
    } else if (cta < N1 + N2) {
#pragma unroll 2
      for (int i = wtid; i < 3072; i += 128) {
        const bf16* src = gwd + (size_t)(i >> 1) * D_ + (cta - N1) * 16 + (i & 1) * 8;
        asm volatile("cp.async.cg.shared.global [%0], [%1], 16;" ::"r"(smem_u32(&sm.w[i])), "l"(src) : "memory");
      }
    }
    asm volatile("cp.async.commit_group;" ::: "memory");
    const int rpb = wtid >> 1, re2 = wtid & 1;
    const int rsw = 3 * ((rpb >> 1) & 1);
    const int roff0 = 16 * rpb + 4 * ((2 * re2 + 0) ^ rsw);
    const int roff1 = 16 * rpb + 4 * ((2 * re2 + 1) ^ rsw);
    const uint32_t dvl = reinterpret_cast<const unsigned short*>(gD)[c0 + (lane < CPC ? lane : 0)];
#pragma unroll 1
    for (int c = 0; c < CPC; c++) {
      const int zg = c & 1;
      const uint32_t dvc = __shfl_sync(0xffffffffu, dvl, c);
      const bf162 d2 = u2b(dvc | (dvc << 16));
      bar_sync(3 + zg, 256);
#pragma unroll
      for (int half = 0; half < 2; half++) {
        const float* zb = sm.z[zg][0] + half * 1024;
        float4 x[4][2];
#pragma unroll
        for (int ww = 0; ww < 4; ww++) {
          x[ww][0] = *reinterpret_cast<const float4*>(zb + ww * ZPB * 16 + roff0);
          x[ww][1] = *reinterpret_cast<const float4*>(zb + ww * ZPB * 16 + roff1);
        }
        const int sidx = half * 1024 + wtid * 8;
        const uint4 kvv = *reinterpret_cast<const uint4*>(&sm.u[c][UPAD + sidx]);
        if (half == 1 && c + 2 < CPC) bar_arrive(5 + zg, 256);
        uint4 o;
        o.x = pack2((x[0][0].x + x[1][0].x) + (x[2][0].x + x[3][0].x), (x[0][0].y + x[1][0].y) + (x[2][0].y + x[3][0].y));
        o.y = pack2((x[0][0].z + x[1][0].z) + (x[2][0].z + x[3][0].z), (x[0][0].w + x[1][0].w) + (x[2][0].w + x[3][0].w));
        o.z = pack2((x[0][1].x + x[1][1].x) + (x[2][1].x + x[3][1].x), (x[0][1].y + x[1][1].y) + (x[2][1].y + x[3][1].y));
        o.w = pack2((x[0][1].z + x[1][1].z) + (x[2][1].z + x[3][1].z), (x[0][1].w + x[1][1].w) + (x[2][1].w + x[3][1].w));
        o.x = b2u(__hadd2_rn(u2b(o.x), __hmul2_rn(u2b(kvv.x), d2)));
        o.y = b2u(__hadd2_rn(u2b(o.y), __hmul2_rn(u2b(kvv.y), d2)));
        o.z = b2u(__hadd2_rn(u2b(o.z), __hmul2_rn(u2b(kvv.z), d2)));
        o.w = b2u(__hadd2_rn(u2b(o.w), __hmul2_rn(u2b(kvv.w), d2)));
        st_pub4(g_y2 + (c0 + c) * 256 + half * 128 + wtid, enc4(o));
      }
      if (c == 1) {
        const uint32_t mb = smem_u32(&sm.mbar);
        uint32_t ok = 0;
        int it = 0;
        while (!ok && ++it < SPIN_LIMIT)
          asm volatile("{ .reg .pred p; mbarrier.try_wait.parity.shared.b64 p, [%1], 0; selp.u32 %0, 1, 0, p; }" : "=r"(ok) : "r"(mb) : "memory");
#pragma unroll 1
        for (int rr = 0; rr < 4; rr++) {
          const int row = (wid - 8) * 4 + rr;
          const uint32_t* qp = reinterpret_cast<const uint32_t*>(&sm.q[row][0]);
          uint32_t qv[10];
          float s = 0.f;
#pragma unroll
          for (int i = 0; i < 10; i++) { qv[i] = qp[lane + 32 * i]; s += lo_f(qv[i]) + hi_f(qv[i]); }
#pragma unroll
          for (int o = 16; o > 0; o >>= 1) s += __shfl_xor_sync(0xffffffffu, s, o);
          const float mean = s * (1.f / D_);
          float m2 = 0.f;
#pragma unroll
          for (int i = 0; i < 10; i++) { float a = lo_f(qv[i]) - mean, b = hi_f(qv[i]) - mean; m2 += a * a + b * b; }
#pragma unroll
          for (int o = 16; o > 0; o >>= 1) m2 += __shfl_xor_sync(0xffffffffu, m2, o);
          if (lane == 0) {
            sm.qstat[row][0] = rbf(mean);
            sm.qstat[row][1] = rbf(sqrtf(rbf(rbf(m2 * (1.f / D_)) + 1e-5f)));
          }
        }
      }
    }
    asm volatile("cp.async.wait_all;" ::: "memory");
    STAMP(4);
    asm volatile("setmaxnreg.inc.sync.aligned.u32 168;");
  }

  __syncthreads();
  if (tid < 256) {
    if (wg == 0) wait_cleared(sm.target);
    const int ch = (tid >> 1) * 5 + 4, hh = tid & 1;
    const uint4 v = poll4(g_y2 + ch * 256 + cta * 2 + hh);
    tile[hh * 640 + tile_perm(ch)] = v;
  }
  __syncthreads();
  STAMP(5);

  const int g = lane >> 2, tq = lane & 3;
  const int hh = wid & 1, gqi = wid >> 1;
  const int row = hh * 8 + g;
  uint32_t hreg[16], hnreg[16];
  if (wid < 10) {
    const float qm = sm.qstat[row][0], qd = sm.qstat[row][1];
    const float qr = 1.f / qd;
    const bf162 qm2 = __float2bfloat162_rn(qm);
    float s = 0.f;
#pragma unroll
    for (int k = 0; k < 4; k++) {
      const int base = 32 * (4 * gqi + k);
      const int lch = base + 8 * ((lane & 7) >> 1) + 2 * (lane >> 3) + (lane & 1);
      uint32_t y[4];
      asm volatile("ldmatrix.sync.aligned.m8n8.x4.trans.shared.b16 {%0,%1,%2,%3}, [%4];"
                   : "=r"(y[0]), "=r"(y[1]), "=r"(y[2]), "=r"(y[3]) : "r"(smem_u32(&tile[hh * 640 + tile_perm(lch)])) : "memory");
      const uint4 qv4 = *reinterpret_cast<const uint4*>(&sm.q[row][base + 8 * tq]);
      const uint32_t qv[4] = {qv4.x, qv4.y, qv4.z, qv4.w};
#pragma unroll
      for (int i = 0; i < 4; i++) {
        const uint32_t d = b2u(__hsub2_rn(u2b(qv[i]), qm2));
        const uint32_t qn = pack2(fdivr(lo_f(d), qd, qr), fdivr(hi_f(d), qd, qr));
        const uint32_t h = b2u(__hadd2_rn(u2b(qv[i]), __hmul2_rn(u2b(qn), u2b(y[i]))));
        hreg[4 * k + i] = h;
        s += lo_f(h) + hi_f(h);
      }
    }
    float mean = s * (1.f / 32.f), m2 = 0.f;
#pragma unroll
    for (int i = 0; i < 16; i++) { float a = lo_f(hreg[i]) - mean, b = hi_f(hreg[i]) - mean; m2 += a * a + b * b; }
    {
      float mo = __shfl_xor_sync(0xffffffffu, mean, 1), qo = __shfl_xor_sync(0xffffffffu, m2, 1);
      float dl = mean - mo; m2 = m2 + qo + dl * dl * 16.f; mean = 0.5f * (mean + mo);
      mo = __shfl_xor_sync(0xffffffffu, mean, 2); qo = __shfl_xor_sync(0xffffffffu, m2, 2);
      dl = mean - mo; m2 = m2 + qo + dl * dl * 32.f; mean = 0.5f * (mean + mo);
    }
    if (tq == 0) sm.st[row][gqi] = make_float2(mean, m2);
  }
  __syncthreads();
  if (wid < 10) {
    float mean = 0.f, m2 = 0.f;
    float2 p[5];
#pragma unroll
    for (int i = 0; i < 5; i++) { p[i] = sm.st[row][i]; mean += p[i].x; }
    mean *= 0.2f;
#pragma unroll
    for (int i = 0; i < 5; i++) { const float dl = p[i].x - mean; m2 += p[i].y + 128.f * dl * dl; }
    const float hd = rbf(sqrtf(rbf(rbf(m2 * (1.f / D_)) + 1e-5f)));
    const float hr = 1.f / hd;
    const bf162 hm2 = __float2bfloat162_rn(mean);
    float r = 0.f;
#pragma unroll
    for (int k = 0; k < 4; k++) {
      const uint4 w4 = __ldg(reinterpret_cast<const uint4*>(gwr + 32 * (4 * gqi + k) + 8 * tq));
      const uint32_t wv[4] = {w4.x, w4.y, w4.z, w4.w};
#pragma unroll
      for (int i = 0; i < 4; i++) {
        const uint32_t d = b2u(__hsub2_rn(u2b(hreg[4 * k + i]), hm2));
        const uint32_t hn = pack2(fdivr(lo_f(d), hd, hr), fdivr(hi_f(d), hd, hr));
        hnreg[4 * k + i] = hn;
        r = fmaf(lo_f(hn), lo_f(wv[i]), r);
        r = fmaf(hi_f(hn), hi_f(wv[i]), r);
      }
    }
    r += __shfl_xor_sync(0xffffffffu, r, 1);
    r += __shfl_xor_sync(0xffffffffu, r, 2);
    if (tq == 0) sm.rp[row][gqi] = r;
  }
  __syncthreads();
  uint32_t best;
  {
    const int rr = lane & 15;
    const float r = ((sm.rp[rr][0] + sm.rp[rr][1]) + (sm.rp[rr][2] + sm.rp[rr][3])) + sm.rp[rr][4];
    const uint32_t bits = __bfloat16_as_ushort(__float2bfloat16_rn(r));
    const uint32_t ord = (bits & 0x8000u) ? (bits ^ 0xFFFFu) : (bits ^ 0x8000u);
    const uint32_t key = (ord << 16) | 0x8000u | (uint32_t)(2047 - (cta * 16 + rr));
    best = __reduce_max_sync(0xffffffffu, key);
  }
  if (tid == 352) asm volatile("st.relaxed.gpu.global.u32 [%0], %1;" ::"l"(&g_keys[cta]), "r"(best) : "memory");
  const int brow = (2047 - (int)(best & 0x7FFu)) - cta * 16;
  uint4 outv[4];
  if (wid < 10) {
#pragma unroll
    for (int k = 0; k < 4; k++) {
      outv[k].x = b2u(__hadd2_rn(u2b(hreg[4 * k + 0]), u2b(hnreg[4 * k + 0])));
      outv[k].y = b2u(__hadd2_rn(u2b(hreg[4 * k + 1]), u2b(hnreg[4 * k + 1])));
      outv[k].z = b2u(__hadd2_rn(u2b(hreg[4 * k + 2]), u2b(hnreg[4 * k + 2])));
      outv[k].w = b2u(__hadd2_rn(u2b(hreg[4 * k + 3]), u2b(hnreg[4 * k + 3])));
      const int chunk = 4 * (4 * gqi + k) + tq;
      if (row == brow) {
        st_pub4(&g_cand[cta][0][chunk], enc4(make_uint4(hnreg[4 * k], hnreg[4 * k + 1], hnreg[4 * k + 2], hnreg[4 * k + 3])));
        st_pub4(&g_cand[cta][1][chunk], enc4(make_uint4(hreg[4 * k], hreg[4 * k + 1], hreg[4 * k + 2], hreg[4 * k + 3])));
      } else {
        *reinterpret_cast<uint4*>(gout + (size_t)(cta * 16 + row) * D_ + chunk * 8) = outv[k];
      }
    }
  }
  STAMP(6);
  if (wid == 11) {
    const uint4* kp = reinterpret_cast<const uint4*>(g_keys) + lane;
    uint4 v = ld_poll4(kp);
    int it = 0;
    while (!ready4(v) && ++it < SPIN_LIMIT) v = ld_poll4(kp);
    const uint32_t m = max(max(v.x, v.y), max(v.z, v.w));
    const uint32_t wk = __reduce_max_sync(0xffffffffu, m);
    if (lane == 0) sm.win = wk;
  }
  __syncthreads();
  const uint32_t win = sm.win;
  const int wrow = 2047 - (int)(win & 0x7FFu);
  const int wcta = wrow >> 4;
  if (wid < 10 && row == brow && wcta != cta) {
#pragma unroll
    for (int k = 0; k < 4; k++)
      *reinterpret_cast<uint4*>(gout + (size_t)(cta * 16 + row) * D_ + (4 * (4 * gqi + k) + tq) * 8) = outv[k];
  }
  STAMP(7);
  float* xs = &sm.z[0][0][0];
  float* part = xs + 2048;
  if (cta < N1) {
    if (tid < 80) {
      const uint4 v = poll4(&g_cand[wcta][0][tid]);
      float4* xp = reinterpret_cast<float4*>(xs + tid * 8);
      xp[0] = make_float4(lo_f(v.x), hi_f(v.x), lo_f(v.y), hi_f(v.y));
      xp[1] = make_float4(lo_f(v.z), hi_f(v.z), lo_f(v.w), hi_f(v.w));
    }
    __syncthreads();
    const int m = wid / 6, hc = (wid % 6) >> 1, rs = (wid & 1) * 32 + lane;
    float a[8];
#pragma unroll
    for (int j = 0; j < 8; j++) a[j] = 0.f;
#pragma unroll
    for (int it = 0; it < 10; it++) {
      const int r = rs + 64 * it;
      const uint4 wv = sm.w[m * 1920 + r * 3 + hc];
      const float x = xs[r];
      a[0] = fmaf(x, lo_f(wv.x), a[0]); a[1] = fmaf(x, hi_f(wv.x), a[1]);
      a[2] = fmaf(x, lo_f(wv.y), a[2]); a[3] = fmaf(x, hi_f(wv.y), a[3]);
      a[4] = fmaf(x, lo_f(wv.z), a[4]); a[5] = fmaf(x, hi_f(wv.z), a[5]);
      a[6] = fmaf(x, lo_f(wv.w), a[6]); a[7] = fmaf(x, hi_f(wv.w), a[7]);
    }
    {
      const bool up = lane & 16;
#pragma unroll
      for (int j = 0; j < 4; j++) {
        const float send = up ? a[j] : a[j + 4], keep = up ? a[j + 4] : a[j];
        a[j] = keep + __shfl_xor_sync(0xffffffffu, send, 16);
      }
      const bool up2 = lane & 8;
#pragma unroll
      for (int j = 0; j < 2; j++) {
        const float send = up2 ? a[j] : a[j + 2], keep = up2 ? a[j + 2] : a[j];
        a[j] = keep + __shfl_xor_sync(0xffffffffu, send, 8);
      }
      const bool up3 = lane & 4;
      const float send = up3 ? a[0] : a[1], keep = up3 ? a[1] : a[0];
      a[0] = keep + __shfl_xor_sync(0xffffffffu, send, 4);
      a[0] += __shfl_xor_sync(0xffffffffu, a[0], 2);
      a[0] += __shfl_xor_sync(0xffffffffu, a[0], 1);
      if ((lane & 3) == 0) part[wid * 8 + (lane >> 2)] = a[0];
    }
    __syncthreads();
    if (wid == 0) {
      uint32_t bits = 0;
      if (lane < 24) {
        const int hc2 = lane >> 3, j = lane & 7;
        const float gt = rbf(part[(2 * hc2) * 8 + j] + part[(2 * hc2 + 1) * 8 + j]);
        const float up = rbf(part[(6 + 2 * hc2) * 8 + j] + part[(6 + 2 * hc2 + 1) * 8 + j]);
        const float sg = rbf(gt / (1.f + __expf(-gt)));
        bits = __bfloat16_as_ushort(__float2bfloat16_rn(sg * up));
      }
      const uint32_t nb = __shfl_down_sync(0xffffffffu, bits, 1);
      const uint32_t pw = bits | (nb << 16);
      const uint32_t w1 = __shfl_down_sync(0xffffffffu, pw, 2), w2 = __shfl_down_sync(0xffffffffu, pw, 4), w3 = __shfl_down_sync(0xffffffffu, pw, 6);
      if (lane < 24 && (lane & 7) == 0) st_pub4(&g_act[cta * 3 + (lane >> 3)], enc4(make_uint4(pw, w1, w2, w3)));
    }
  } else if (cta < N1 + N2) {
    const int j2 = cta - N1;
    uint4 rowv = make_uint4(0, 0, 0, 0);
    if (tid < 192) {
      const uint4 v = poll4(&g_act[tid]);
      float4* xp = reinterpret_cast<float4*>(xs + tid * 8);
      xp[0] = make_float4(lo_f(v.x), hi_f(v.x), lo_f(v.y), hi_f(v.y));
      xp[1] = make_float4(lo_f(v.z), hi_f(v.z), lo_f(v.w), hi_f(v.w));
    } else if (tid < 196) {
      const int t = tid - 192;
      rowv = poll4(&g_cand[wcta][t >> 1][j2 * 2 + (t & 1)]);
      reinterpret_cast<uint4*>(part + 256)[t] = rowv;
    }
    __syncthreads();
    const int hc = lane & 1, rs = wid * 16 + (lane >> 1);
    float a[8];
#pragma unroll
    for (int j = 0; j < 8; j++) a[j] = 0.f;
#pragma unroll
    for (int it = 0; it < 8; it++) {
      const int r = rs + 192 * it;
      const uint4 wv = sm.w[r * 2 + hc];
      const float x = xs[r];
      a[0] = fmaf(x, lo_f(wv.x), a[0]); a[1] = fmaf(x, hi_f(wv.x), a[1]);
      a[2] = fmaf(x, lo_f(wv.y), a[2]); a[3] = fmaf(x, hi_f(wv.y), a[3]);
      a[4] = fmaf(x, lo_f(wv.z), a[4]); a[5] = fmaf(x, hi_f(wv.z), a[5]);
      a[6] = fmaf(x, lo_f(wv.w), a[6]); a[7] = fmaf(x, hi_f(wv.w), a[7]);
    }
    {
      const bool up = lane & 16;
#pragma unroll
      for (int j = 0; j < 4; j++) {
        const float send = up ? a[j] : a[j + 4], keep = up ? a[j + 4] : a[j];
        a[j] = keep + __shfl_xor_sync(0xffffffffu, send, 16);
      }
      const bool up2 = lane & 8;
#pragma unroll
      for (int j = 0; j < 2; j++) {
        const float send = up2 ? a[j] : a[j + 2], keep = up2 ? a[j + 2] : a[j];
        a[j] = keep + __shfl_xor_sync(0xffffffffu, send, 8);
      }
      const bool up3 = lane & 4;
      const float send = up3 ? a[0] : a[1], keep = up3 ? a[1] : a[0];
      a[0] = keep + __shfl_xor_sync(0xffffffffu, send, 4);
      a[0] += __shfl_xor_sync(0xffffffffu, a[0], 2);
      if ((lane & 2) == 0) part[wid * 16 + hc * 8 + (lane >> 2)] = a[0];
    }
    __syncthreads();
    if (tid < 16) {
      float y = 0.f;
#pragma unroll
      for (int i = 0; i < 12; i++) y += part[i * 16 + tid];
      const uint32_t ord = win >> 16;
      const uint32_t rb = (ord & 0x8000u) ? (ord ^ 0x8000u) : (ord ^ 0xFFFFu);
      const float r = __uint_as_float(rb << 16);
      const float sg = rbf(1.f / (1.f + __expf(-r)));
      const float yy = rbf(rbf(y) * sg);
      const unsigned short* rv = reinterpret_cast<const unsigned short*>(part + 256);
      const float hn = __uint_as_float((uint32_t)rv[tid] << 16), h = __uint_as_float((uint32_t)rv[16 + tid] << 16);
      gout[(size_t)wrow * D_ + j2 * 16 + tid] = __float2bfloat16_rn(h + rbf(hn + yy));
    }
  }
  STAMP(8);
}

}

extern "C" void kernel_launch(void* const* d_in, const int* in_sizes, int n_in, void* d_out, int out_size) {
  (void)in_sizes; (void)n_in; (void)out_size;
  static bool init = false;
  if (!init) {
    cudaFuncSetAttribute(fused_kernel, cudaFuncAttributeMaxDynamicSharedMemorySize, (int)sizeof(Smem));
    init = true;
  }
  fused_kernel<<<NCTA, NTHR, sizeof(Smem), cudaStreamPerThread>>>(
      (const bf16*)d_in[0], (const bf16*)d_in[1], (const bf16*)d_in[2], (const bf16*)d_in[3], (const bf16*)d_in[4],
      (const bf16*)d_in[5], (const bf16*)d_in[7], (const bf16*)d_in[8], (const bf16*)d_in[9], (const bf16*)d_in[10],
      (bf16*)d_out);
}
```

```cpp
#include <cuda_runtime.h>
#include <cuda_bf16.h>
#include <cuda.h>
#include <stdint.h>

namespace {

typedef __nv_bfloat16 bf16;
typedef __nv_bfloat162 bf162;

constexpr int S_ = 2048, D_ = 640, F_ = 1536;
constexpr int NCTA = 128, CPC = 5, NTHR = 384;
constexpr int UPAD = 136, USTR = 2192;
constexpr int TABW = 1040;
constexpr int ZPB = 132;
constexpr int QSTR = 648;
constexpr int N1 = 64;
constexpr int N2 = 40;
constexpr int SPIN_LIMIT = 1 << 19;
#define H_DELAY_NS 0

struct __align__(128) Smem {
  bf16 u[CPC][USTR];
  uint32_t tab[CPC][2][TABW];
  float z[2][4][ZPB * 16];
  bf16 q[16][QSTR];
  alignas(128) uint4 w[3840];
  uint4 wr[80];
  float qstat[16][2];
  float2 st[16][5];
  float rp[16][5];
  unsigned long long mbar;
  unsigned long long mbarw;
  uint32_t best;
  uint32_t win;
};

__device__ uint4 g_kv[D_ * S_ / 8];
__device__ uint4 g_y2[D_ * S_ / 8];
__device__ uint32_t g_keys[NCTA];
__device__ uint4 g_cand[NCTA][2][80];
__device__ uint4 g_act[F_ / 8];
__device__ unsigned int g_ctr;
#define STAMP(i)

__device__ __forceinline__ uint32_t smem_u32(const void* p) { return (uint32_t)__cvta_generic_to_shared(p); }
__device__ __forceinline__ void wg_fence() { asm volatile("wgmma.fence.sync.aligned;" ::: "memory"); }
__device__ __forceinline__ void wg_commit() { asm volatile("wgmma.commit_group.sync.aligned;" ::: "memory"); }
template <int N> __device__ __forceinline__ void wg_wait() { asm volatile("wgmma.wait_group.sync.aligned %0;" ::"n"(N) : "memory"); }
__device__ __forceinline__ void bar_sync(int id, int n) { asm volatile("bar.sync %0, %1;" ::"r"(id), "r"(n) : "memory"); }
__device__ __forceinline__ void bar_arrive(int id, int n) { asm volatile("bar.arrive %0, %1;" ::"r"(id), "r"(n) : "memory"); }
__device__ __forceinline__ bf162 u2b(uint32_t u) { return *reinterpret_cast<bf162*>(&u); }
__device__ __forceinline__ uint32_t b2u(bf162 b) { return *reinterpret_cast<uint32_t*>(&b); }
__device__ __forceinline__ float lo_f(uint32_t u) { return __uint_as_float(u << 16); }
__device__ __forceinline__ float hi_f(uint32_t u) { return __uint_as_float(u & 0xFFFF0000u); }
__device__ __forceinline__ float rbf(float x) { return __bfloat162float(__float2bfloat16_rn(x)); }
__device__ __forceinline__ uint32_t pack2(float a, float b) { return b2u(__floats2bfloat162_rn(a, b)); }
__device__ __forceinline__ uint32_t enc(uint32_t w) {
  uint32_t e = ~w;
  if ((e & 0xFFFFu) == 0u) e |= 0x8000u;
  if ((e >> 16) == 0u) e |= 0x80000000u;
  return e;
}
__device__ __forceinline__ uint4 enc4(uint4 v) { return make_uint4(enc(v.x), enc(v.y), enc(v.z), enc(v.w)); }
__device__ __forceinline__ uint4 ld_poll4(const uint4* p) {
  uint4 v;
  asm volatile("ld.relaxed.gpu.global.v4.u32 {%0,%1,%2,%3}, [%4];" : "=r"(v.x), "=r"(v.y), "=r"(v.z), "=r"(v.w) : "l"(p) : "memory");
  return v;
}
__device__ __forceinline__ bool ready4(uint4 v) { return v.x != 0u && v.y != 0u && v.z != 0u && v.w != 0u; }
__device__ __forceinline__ uint4 poll4(const uint4* p) {
  uint4 v = ld_poll4(p);
  int it = 0;
  while (!ready4(v) && ++it < SPIN_LIMIT) v = ld_poll4(p);
  return make_uint4(~v.x, ~v.y, ~v.z, ~v.w);
}
__device__ __forceinline__ void st_pub4(uint4* p, uint4 v) {
  asm volatile("st.relaxed.gpu.global.v4.u32 [%0], {%1,%2,%3,%4};" ::"l"(p), "r"(v.x), "r"(v.y), "r"(v.z), "r"(v.w) : "memory");
}
__device__ __forceinline__ float fdivr(float a, float d, float r) {
  float q = a * r;
  float e = fmaf(-q, d, a);
  return fmaf(e, r, q);
}

template <bool FIRST> __device__ __forceinline__ void wgmma32(float (&d)[16], const uint32_t* a, uint64_t desc) {
  if (FIRST) {
    asm volatile("wgmma.mma_async.sync.aligned.m64n32k16.f32.bf16.bf16 {%0,%1,%2,%3,%4,%5,%6,%7,%8,%9,%10,%11,%12,%13,%14,%15}, {%16,%17,%18,%19}, %20, 0, 1, 1, 0;"
                 : "+f"(d[0]), "+f"(d[1]), "+f"(d[2]), "+f"(d[3]), "+f"(d[4]), "+f"(d[5]), "+f"(d[6]), "+f"(d[7]),
                   "+f"(d[8]), "+f"(d[9]), "+f"(d[10]), "+f"(d[11]), "+f"(d[12]), "+f"(d[13]), "+f"(d[14]), "+f"(d[15])
                 : "r"(a[0]), "r"(a[1]), "r"(a[2]), "r"(a[3]), "l"(desc));
  } else {
    asm volatile("wgmma.mma_async.sync.aligned.m64n32k16.f32.bf16.bf16 {%0,%1,%2,%3,%4,%5,%6,%7,%8,%9,%10,%11,%12,%13,%14,%15}, {%16,%17,%18,%19}, %20, 1, 1, 1, 0;"
                 : "+f"(d[0]), "+f"(d[1]), "+f"(d[2]), "+f"(d[3]), "+f"(d[4]), "+f"(d[5]), "+f"(d[6]), "+f"(d[7]),
                   "+f"(d[8]), "+f"(d[9]), "+f"(d[10]), "+f"(d[11]), "+f"(d[12]), "+f"(d[13]), "+f"(d[14]), "+f"(d[15])
                 : "r"(a[0]), "r"(a[1]), "r"(a[2]), "r"(a[3]), "l"(desc));
  }
}

template <int G> __device__ __forceinline__ void load_a(uint32_t (&a)[8], const uint32_t* tp) {
#pragma unroll
  for (int q = 0; q < 2; q++) {
    const int e = 2 * G + q;
    a[4 * q + 0] = tp[-64 * e];
    a[4 * q + 1] = tp[-64 * e - 32];
    a[4 * q + 2] = tp[-64 * e + 4];
    a[4 * q + 3] = tp[-64 * e - 28];
  }
}
__device__ __forceinline__ void load_a_all(uint32_t (&a)[8][8], const uint32_t* tp) {
  load_a<0>(a[0], tp); load_a<1>(a[1], tp); load_a<2>(a[2], tp); load_a<3>(a[3], tp);
  load_a<4>(a[4], tp); load_a<5>(a[5], tp); load_a<6>(a[6], tp); load_a<7>(a[7], tp);
}
template <int G> __device__ __forceinline__ void issue_g(float (&acc)[8][16], uint32_t (&a)[8], uint64_t desc0) {
  wg_fence();
#pragma unroll
  for (int q = 0; q < 2; q++) {
#pragma unroll
    for (int b = G; b < 8; b++) {
      const int delta = 2 * b - (2 * G + q);
      if (G == 0 && q == 0) wgmma32<true>(acc[b], &a[4 * q], desc0 + (uint64_t)(int64_t)(16 * delta));
      else wgmma32<false>(acc[b], &a[4 * q], desc0 + (uint64_t)(int64_t)(16 * delta));
    }
  }
  wg_commit();
}
template <int B> __device__ __forceinline__ void fence_blk(float (&acc)[8][16]) {
#pragma unroll
  for (int i = 0; i < 16; i++) asm volatile("" : "+f"(acc[B][i])::"memory");
}
__device__ __forceinline__ void fence_a(uint32_t (&a)[8]) {
#pragma unroll
  for (int i = 0; i < 8; i++) asm volatile("" : "+r"(a[i])::"memory");
}
template <int B> __device__ __forceinline__ void sts_blk(float (&acc)[8][16], float* zw, int off_even, int off_odd) {
#pragma unroll
  for (int jj = 0; jj < 4; jj++) {
    const int j = 4 * B + jj;
    float p0 = acc[B][4 * jj + 0], p1 = acc[B][4 * jj + 1];
    if (jj > 0) { p0 += acc[B][4 * (jj - 1) + 2]; p1 += acc[B][4 * (jj - 1) + 3]; }
    else if (B > 0) { p0 += acc[B > 0 ? B - 1 : 0][14]; p1 += acc[B > 0 ? B - 1 : 0][15]; }
    zw[64 * j + off_even] = p0;
    zw[64 * j + off_odd] = p1;
  }
}
__device__ __forceinline__ int tile_perm(int ch) { return ch ^ (((ch >> 3) & 3) << 1); }

__device__ __forceinline__ void wait_cleared(uint32_t target) {
  uint32_t v;
  int it = 0;
  do {
    asm volatile("ld.acquire.gpu.global.u32 %0, [%1];" : "=r"(v) : "l"(&g_ctr) : "memory");
  } while ((int)(v - target) < 0 && ++it < SPIN_LIMIT);
}

__global__ void __launch_bounds__(NTHR, 1)
fused_kernel(const __grid_constant__ CUtensorMap tmg, const __grid_constant__ CUtensorMap tmu,
             const __grid_constant__ CUtensorMap tmd, const bf16* __restrict__ gq, const bf16* __restrict__ gk, const bf16* __restrict__ gv,
             const bf16* __restrict__ gsk, const bf16* __restrict__ gh, const bf16* __restrict__ gD,
             const bf16* __restrict__ gwr, bf16* __restrict__ gout) {
  extern __shared__ __align__(128) unsigned char smraw[];
  Smem& sm = *reinterpret_cast<Smem*>(smraw);
  const int tid = threadIdx.x;
  const int cta = blockIdx.x;
  const int c0 = cta * CPC;
  const int lane = tid & 31;
  const int wid = tid >> 5;
  STAMP(0);

  if (tid < 160) {
    const int oc = tid % 80, hf = tid / 80;
    const int r0 = cta * 16 + hf * 8;
    const uint4* kp = reinterpret_cast<const uint4*>(gk) + (size_t)r0 * 80 + oc;
    const uint4* vp = reinterpret_cast<const uint4*>(gv) + (size_t)r0 * 80 + oc;
    uint4 kk[11], vv[8], sk[4];
#pragma unroll
    for (int i = 0; i < 11; i++) kk[i] = (i >= 3 || r0 > 0) ? __ldg(kp + (i - 3) * 80) : make_uint4(0, 0, 0, 0);
#pragma unroll
    for (int i = 0; i < 8; i++) vv[i] = __ldg(vp + i * 80);
#pragma unroll
    for (int i = 0; i < 4; i++) sk[i] = __ldg(reinterpret_cast<const uint4*>(gsk) + oc * 4 + i);
    STAMP(9);
#pragma unroll
    for (int p = 0; p < 4; p++) {
      const bf162 w0 = u2b(__byte_perm(sk[p].x, sk[p].z, 0x5410)), w1 = u2b(__byte_perm(sk[p].x, sk[p].z, 0x7632));
      const bf162 w2 = u2b(__byte_perm(sk[p].y, sk[p].w, 0x5410)), w3 = u2b(__byte_perm(sk[p].y, sk[p].w, 0x7632));
      uint32_t kv[8];
#pragma unroll
      for (int i = 0; i < 8; i++) {
        const uint32_t k0 = p == 0 ? kk[i].x : p == 1 ? kk[i].y : p == 2 ? kk[i].z : kk[i].w;
        const uint32_t k1 = p == 0 ? kk[i + 1].x : p == 1 ? kk[i + 1].y : p == 2 ? kk[i + 1].z : kk[i + 1].w;
        const uint32_t k2 = p == 0 ? kk[i + 2].x : p == 1 ? kk[i + 2].y : p == 2 ? kk[i + 2].z : kk[i + 2].w;
        const uint32_t k3 = p == 0 ? kk[i + 3].x : p == 1 ? kk[i + 3].y : p == 2 ? kk[i + 3].z : kk[i + 3].w;
        const uint32_t vx = p == 0 ? vv[i].x : p == 1 ? vv[i].y : p == 2 ? vv[i].z : vv[i].w;
        bf162 a = __hmul2_rn(u2b(k0), w3);
        a = __hadd2_rn(a, __hmul2_rn(u2b(k1), w2));
        a = __hadd2_rn(a, __hmul2_rn(u2b(k2), w1));
        a = __hadd2_rn(a, __hmul2_rn(u2b(k3), w0));
        kv[i] = enc(b2u(__hmul2_rn(a, u2b(vx))));
      }
      uint4* dst = g_kv + (size_t)(oc * 8 + 2 * p) * 256 + (r0 >> 3);
      st_pub4(dst, make_uint4(__byte_perm(kv[0], kv[1], 0x5410), __byte_perm(kv[2], kv[3], 0x5410),
                              __byte_perm(kv[4], kv[5], 0x5410), __byte_perm(kv[6], kv[7], 0x5410)));
      st_pub4(dst + 256, make_uint4(__byte_perm(kv[0], kv[1], 0x7632), __byte_perm(kv[2], kv[3], 0x7632),
                                    __byte_perm(kv[4], kv[5], 0x7632), __byte_perm(kv[6], kv[7], 0x7632)));
    }
    STAMP(10);
  } else {
    const int t0 = tid - 160;
    const uint4 zz = make_uint4(0, 0, 0, 0);
    if (t0 < CPC * 17) *reinterpret_cast<uint4*>(&sm.u[t0 / 17][(t0 % 17) * 8]) = zz;
    else if (t0 < CPC * 17 + 40) { const int t = t0 - CPC * 17; *reinterpret_cast<uint4*>(&sm.tab[t >> 3][(t >> 2) & 1][1024 + 4 * (t & 3)]) = zz; }
    if (t0 < 128) *reinterpret_cast<uint4*>(&sm.z[t0 >> 6][(t0 >> 4) & 3][(t0 & 15) * 4]) = zz;
    if (t0 == 0) {
      asm volatile("mbarrier.init.shared.b64 [%0], 1;" ::"r"(smem_u32(&sm.mbar)) : "memory");
      asm volatile("mbarrier.init.shared.b64 [%0], 1;" ::"r"(smem_u32(&sm.mbarw)) : "memory");
    }
    if (H_DELAY_NS > 0) __nanosleep(H_DELAY_NS);
    uint4 hv[6];
    uint32_t hp[6];
#pragma unroll
    for (int i = 0; i < 6; i++) {
      const int t = t0 + 224 * i;
      hp[i] = 0;
      if (t < CPC * 256) {
        const bf16* p = gh + (size_t)c0 * S_ + t * 8;
        hv[i] = __ldg(reinterpret_cast<const uint4*>(p));
        if (t & 255) hp[i] = __ldg(reinterpret_cast<const unsigned short*>(p) - 1);
      }
    }
#pragma unroll
    for (int i = 0; i < 6; i++) {
      const int t = t0 + 224 * i;
      if (t < CPC * 256) {
        const int c = t >> 8, ch = t & 255;
        uint4 h = hv[i], r1, rr;
        r1.x = __byte_perm(h.w, 0, 0x1032); r1.y = __byte_perm(h.z, 0, 0x1032);
        r1.z = __byte_perm(h.y, 0, 0x1032); r1.w = __byte_perm(h.x, 0, 0x1032);
        rr.x = __byte_perm(h.w, h.z, 0x7610); rr.y = __byte_perm(h.z, h.y, 0x7610);
        rr.z = __byte_perm(h.y, h.x, 0x7610); rr.w = __byte_perm(h.x, hp[i], 0x5410);
        *reinterpret_cast<uint4*>(&sm.tab[c][0][(255 - ch) * 4]) = rr;
        *reinterpret_cast<uint4*>(&sm.tab[c][1][(255 - ch) * 4]) = r1;
      }
    }
  }
  {
    uint4 v[4];
    uint4* src = g_kv + c0 * 256 + tid;
#pragma unroll
    for (int i = 0; i < 4; i++) if (i < 3 || tid < 128) v[i] = ld_poll4(src + NTHR * i);
#pragma unroll
    for (int i = 0; i < 4; i++) {
      if (i < 3 || tid < 128) {
        int it = 0;
        while (!ready4(v[i]) && ++it < SPIN_LIMIT) v[i] = ld_poll4(src + NTHR * i);
        const int t = tid + NTHR * i;
        *reinterpret_cast<uint4*>(&sm.u[t >> 8][UPAD + (t & 255) * 8]) = make_uint4(~v[i].x, ~v[i].y, ~v[i].z, ~v[i].w);
        src[NTHR * i] = make_uint4(0, 0, 0, 0);
      }
    }
    STAMP(11);
    asm volatile("fence.proxy.async.shared::cta;" ::: "memory");
    __syncthreads();
  }
  STAMP(1);

  const int wg = __shfl_sync(0xffffffffu, tid >> 7, 0);
  const int wtid = tid & 127;
  uint4* tile = reinterpret_cast<uint4*>(&sm.tab[0][0][0]);
  if (wg < 2) {
    asm volatile("setmaxnreg.inc.sync.aligned.u32 224;");
    const int w = (tid >> 5) & 3, g = lane >> 2, tq = lane & 3;
    float* zw = sm.z[wg][w];
    const int sw = 3 * (((tq + w) >> 1) & 1);
    const int off_even = 16 * (tq + w) + 4 * ((0 + (g >> 2)) ^ sw) + (g & 3);
    const int off_odd = 16 * (tq + w) + 4 * ((2 + (g >> 2)) ^ sw) + (g & 3);
    uint32_t a[8][8];
    const uint32_t* tp = &sm.tab[wg][g & 1][1019 - 8 * w - (g >> 1) + tq];
    load_a_all(a, tp);
    float acc[8][16];
#pragma unroll
    for (int b = 0; b < 8; b++)
#pragma unroll
      for (int i = 0; i < 16; i++) acc[b][i] = 0.f;
#pragma unroll 1
    for (int c = wg; c < CPC; c += 2) {
      const uint64_t desc = (uint64_t)((smem_u32(&sm.u[c][UPAD - 8]) & 0x3FFFF) >> 4) | ((uint64_t)1 << 16) | ((uint64_t)8 << 32);
      if (c > 0) bar_sync(1 + wg, 256);
      issue_g<0>(acc, a[0], desc);
      issue_g<1>(acc, a[1], desc);
      issue_g<2>(acc, a[2], desc);
      issue_g<3>(acc, a[3], desc);
      issue_g<4>(acc, a[4], desc);
      issue_g<5>(acc, a[5], desc);
      if (c + 1 < CPC) bar_arrive(1 + (wg ^ 1), 256);
      issue_g<6>(acc, a[6], desc);
      issue_g<7>(acc, a[7], desc);
      if (c >= 2) bar_sync(5 + wg, 256);
      wg_wait<4>();
      fence_blk<0>(acc); fence_blk<1>(acc); fence_blk<2>(acc); fence_blk<3>(acc);
      sts_blk<0>(acc, zw, off_even, off_odd);
      sts_blk<1>(acc, zw, off_even, off_odd);
      sts_blk<2>(acc, zw, off_even, off_odd);
      sts_blk<3>(acc, zw, off_even, off_odd);
      wg_wait<0>();
      fence_blk<4>(acc); fence_blk<5>(acc); fence_blk<6>(acc); fence_blk<7>(acc);
#pragma unroll
      for (int i = 0; i < 8; i++) fence_a(a[i]);
      sts_blk<4>(acc, zw, off_even, off_odd);
      sts_blk<5>(acc, zw, off_even, off_odd);
      sts_blk<6>(acc, zw, off_even, off_odd);
      sts_blk<7>(acc, zw, off_even, off_odd);
      bar_arrive(3 + wg, 256);
      tp += 2 * 2 * TABW;
      if (c + 2 < CPC) load_a_all(a, tp);
    }
    STAMP(2 + wg);
    asm volatile("setmaxnreg.dec.sync.aligned.u32 168;");
    if (wg == 1) {
#pragma unroll 1
      for (int cc = 0; cc < 4; cc++) {
        const int ch = wtid * 5 + cc;
        const uint4* src = g_y2 + cta * 1280 + ch * 2;
        uint4 v0 = ld_poll4(src), v1 = ld_poll4(src + 1);
        int it = 0;
        while (!ready4(v0) && ++it < SPIN_LIMIT) v0 = ld_poll4(src);
        while (!ready4(v1) && ++it < SPIN_LIMIT) v1 = ld_poll4(src + 1);
        const int pc = tile_perm(ch);
        tile[pc] = make_uint4(~v0.x, ~v0.y, ~v0.z, ~v0.w);
        tile[640 + pc] = make_uint4(~v1.x, ~v1.y, ~v1.z, ~v1.w);
      }
    }
  } else {
    asm volatile("setmaxnreg.dec.sync.aligned.u32 56;");
    if (wtid == 32) {
      const uint32_t mb = smem_u32(&sm.mbar), mw = smem_u32(&sm.mbarw);
      asm volatile("mbarrier.arrive.expect_tx.shared.b64 _, [%0], %1;" ::"r"(mb), "r"(17 * D_ * 2) : "memory");
#pragma unroll 1
      for (int r = 0; r < 16; r++)
        asm volatile("cp.async.bulk.shared::cluster.global.mbarrier::complete_tx::bytes [%0], [%1], %2, [%3];" ::"r"(smem_u32(&sm.q[r][0])),
                     "l"(gq + (size_t)(cta * 16 + r) * D_), "r"(D_ * 2), "r"(mb) : "memory");
      asm volatile("cp.async.bulk.shared::cluster.global.mbarrier::complete_tx::bytes [%0], [%1], %2, [%3];" ::"r"(smem_u32(&sm.wr[0])),
                   "l"(gwr), "r"(D_ * 2), "r"(mb) : "memory");
      if (cta < N1) {
        asm volatile("mbarrier.arrive.expect_tx.shared.b64 _, [%0], %1;" ::"r"(mw), "r"(3840 * 16) : "memory");
#pragma unroll 1
        for (int i = 0; i < 4; i++) {
          asm volatile("cp.async.bulk.tensor.2d.shared::cluster.global.mbarrier::complete_tx::bytes [%0], [%1, {%3, %4}], [%2];" ::"r"(smem_u32(&sm.w[i * 480])),
                       "l"(&tmg), "r"(mw), "r"(cta * 24), "r"(i * 160) : "memory");
          asm volatile("cp.async.bulk.tensor.2d.shared::cluster.global.mbarrier::complete_tx::bytes [%0], [%1, {%3, %4}], [%2];" ::"r"(smem_u32(&sm.w[1920 + i * 480])),
                       "l"(&tmu), "r"(mw), "r"(cta * 24), "r"(i * 160) : "memory");
        }
      } else if (cta < N1 + N2) {
        asm volatile("mbarrier.arrive.expect_tx.shared.b64 _, [%0], %1;" ::"r"(mw), "r"(3072 * 16) : "memory");
#pragma unroll 1
        for (int i = 0; i < 6; i++)
          asm volatile("cp.async.bulk.tensor.2d.shared::cluster.global.mbarrier::complete_tx::bytes [%0], [%1, {%3, %4}], [%2];" ::"r"(smem_u32(&sm.w[i * 512])),
                       "l"(&tmd), "r"(mw), "r"((cta - N1) * 16), "r"(i * 256) : "memory");
      }
    }
    {
      const uint4 zz = make_uint4(0, 0, 0, 0);
#pragma unroll
      for (int i = 0; i < 10; i++) g_y2[cta * 1280 + wtid + 128 * i] = zz;
      (&g_cand[cta][0][0])[wtid] = zz;
      if (wtid < 32) (&g_cand[cta][0][0])[128 + wtid] = zz;
      else if (wtid < 35) { if (cta < N1) g_act[cta * 3 + (wtid - 32)] = zz; }
      else if (wtid == 35) g_keys[cta] = 0u;
      bar_sync(7, 128);
      if (wtid == 0) {
        __threadfence();
        const unsigned old = atomicAdd(&g_ctr, 1u);
        wait_cleared((old / NCTA + 1u) * NCTA);
      }
    }
    const int rpb = wtid >> 1, re2 = wtid & 1;
    const int rsw = 3 * ((rpb >> 1) & 1);
    const int roff0 = 16 * rpb + 4 * ((2 * re2 + 0) ^ rsw);
    const int roff1 = 16 * rpb + 4 * ((2 * re2 + 1) ^ rsw);
    const uint32_t dvl = reinterpret_cast<const unsigned short*>(gD)[c0 + (lane < CPC ? lane : 0)];
#pragma unroll 1
    for (int c = 0; c < CPC; c++) {
      const int zg = c & 1;
      const uint32_t dvc = __shfl_sync(0xffffffffu, dvl, c);
      const bf162 d2 = u2b(dvc | (dvc << 16));
      bar_sync(3 + zg, 256);
#pragma unroll
      for (int half = 0; half < 2; half++) {
        const float* zb = sm.z[zg][0] + half * 1024;
        float4 x[4][2];
#pragma unroll
        for (int ww = 0; ww < 4; ww++) {
          x[ww][0] = *reinterpret_cast<const float4*>(zb + ww * ZPB * 16 + roff0);
          x[ww][1] = *reinterpret_cast<const float4*>(zb + ww * ZPB * 16 + roff1);
        }
        const int sidx = half * 1024 + wtid * 8;
        const uint4 kvv = *reinterpret_cast<const uint4*>(&sm.u[c][UPAD + sidx]);
        if (half == 1 && c + 2 < CPC) bar_arrive(5 + zg, 256);
        uint4 o;
        o.x = pack2((x[0][0].x + x[1][0].x) + (x[2][0].x + x[3][0].x), (x[0][0].y + x[1][0].y) + (x[2][0].y + x[3][0].y));
        o.y = pack2((x[0][0].z + x[1][0].z) + (x[2][0].z + x[3][0].z), (x[0][0].w + x[1][0].w) + (x[2][0].w + x[3][0].w));
        o.z = pack2((x[0][1].x + x[1][1].x) + (x[2][1].x + x[3][1].x), (x[0][1].y + x[1][1].y) + (x[2][1].y + x[3][1].y));
        o.w = pack2((x[0][1].z + x[1][1].z) + (x[2][1].z + x[3][1].z), (x[0][1].w + x[1][1].w) + (x[2][1].w + x[3][1].w));
        o.x = b2u(__hadd2_rn(u2b(o.x), __hmul2_rn(u2b(kvv.x), d2)));
        o.y = b2u(__hadd2_rn(u2b(o.y), __hmul2_rn(u2b(kvv.y), d2)));
        o.z = b2u(__hadd2_rn(u2b(o.z), __hmul2_rn(u2b(kvv.z), d2)));
        o.w = b2u(__hadd2_rn(u2b(o.w), __hmul2_rn(u2b(kvv.w), d2)));
        st_pub4(g_y2 + ((64 * half + rpb) * 640 + c0 + c) * 2 + re2, enc4(o));
      }
      if (c == 1) {
        const uint32_t mb = smem_u32(&sm.mbar);
        uint32_t ok = 0;
        int it = 0;
        while (!ok && ++it < SPIN_LIMIT)
          asm volatile("{ .reg .pred p; mbarrier.try_wait.parity.shared.b64 p, [%1], 0; selp.u32 %0, 1, 0, p; }" : "=r"(ok) : "r"(mb) : "memory");
#pragma unroll 1
        for (int rr = 0; rr < 4; rr++) {
          const int row = (wid - 8) * 4 + rr;
          const uint32_t* qp = reinterpret_cast<const uint32_t*>(&sm.q[row][0]);
          uint32_t qv[10];
          float s = 0.f;
#pragma unroll
          for (int i = 0; i < 10; i++) { qv[i] = qp[lane + 32 * i]; s += lo_f(qv[i]) + hi_f(qv[i]); }
#pragma unroll
          for (int o = 16; o > 0; o >>= 1) s += __shfl_xor_sync(0xffffffffu, s, o);
          const float mean = s * (1.f / D_);
          float m2 = 0.f;
#pragma unroll
          for (int i = 0; i < 10; i++) { float a = lo_f(qv[i]) - mean, b = hi_f(qv[i]) - mean; m2 += a * a + b * b; }
#pragma unroll
          for (int o = 16; o > 0; o >>= 1) m2 += __shfl_xor_sync(0xffffffffu, m2, o);
          if (lane == 0) {
            sm.qstat[row][0] = rbf(mean);
            sm.qstat[row][1] = rbf(sqrtf(rbf(rbf(m2 * (1.f / D_)) + 1e-5f)));
          }
        }
      }
    }
    STAMP(4);
    asm volatile("setmaxnreg.inc.sync.aligned.u32 168;");
  }

  if (tid < 128 || tid >= 256) {
    const int t = tid < 128 ? tid : tid - 128;
    const int ch = (t >> 1) * 5 + 4, hh = t & 1;
    const uint4 v = poll4(g_y2 + cta * 1280 + ch * 2 + hh);
    tile[hh * 640 + tile_perm(ch)] = v;
  }
  __syncthreads();
  STAMP(5);

  const int g = lane >> 2, tq = lane & 3;
  const int hh = wid & 1, gqi = wid >> 1;
  const int row = hh * 8 + g;
  uint32_t hreg[16], hnreg[16];
  if (wid < 10) {
    const float qm = sm.qstat[row][0], qd = sm.qstat[row][1];
    const float qr = 1.f / qd;
    const bf162 qm2 = __float2bfloat162_rn(qm);
    float s = 0.f;
#pragma unroll
    for (int k = 0; k < 4; k++) {
      const int base = 32 * (4 * gqi + k);
      const int lch = base + 8 * ((lane & 7) >> 1) + 2 * (lane >> 3) + (lane & 1);
      uint32_t y[4];
      asm volatile("ldmatrix.sync.aligned.m8n8.x4.trans.shared.b16 {%0,%1,%2,%3}, [%4];"
                   : "=r"(y[0]), "=r"(y[1]), "=r"(y[2]), "=r"(y[3]) : "r"(smem_u32(&tile[hh * 640 + tile_perm(lch)])) : "memory");
      const uint4 qv4 = *reinterpret_cast<const uint4*>(&sm.q[row][base + 8 * tq]);
      const uint32_t qv[4] = {qv4.x, qv4.y, qv4.z, qv4.w};
#pragma unroll
      for (int i = 0; i < 4; i++) {
        const uint32_t d = b2u(__hsub2_rn(u2b(qv[i]), qm2));
        const uint32_t qn = pack2(fdivr(lo_f(d), qd, qr), fdivr(hi_f(d), qd, qr));
        const uint32_t h = b2u(__hadd2_rn(u2b(qv[i]), __hmul2_rn(u2b(qn), u2b(y[i]))));
        hreg[4 * k + i] = h;
        s += lo_f(h) + hi_f(h);
      }
    }
    float mean = s * (1.f / 32.f), m2 = 0.f;
#pragma unroll
    for (int i = 0; i < 16; i++) { float a = lo_f(hreg[i]) - mean, b = hi_f(hreg[i]) - mean; m2 += a * a + b * b; }
    {
      float mo = __shfl_xor_sync(0xffffffffu, mean, 1), qo = __shfl_xor_sync(0xffffffffu, m2, 1);
      float dl = mean - mo; m2 = m2 + qo + dl * dl * 16.f; mean = 0.5f * (mean + mo);
      mo = __shfl_xor_sync(0xffffffffu, mean, 2); qo = __shfl_xor_sync(0xffffffffu, m2, 2);
      dl = mean - mo; m2 = m2 + qo + dl * dl * 32.f; mean = 0.5f * (mean + mo);
    }
    if (tq == 0) sm.st[row][gqi] = make_float2(mean, m2);
  }
  __syncthreads();
  if (wid < 10) {
    float mean = 0.f, m2 = 0.f;
    float2 p[5];
#pragma unroll
    for (int i = 0; i < 5; i++) { p[i] = sm.st[row][i]; mean += p[i].x; }
    mean *= 0.2f;
#pragma unroll
    for (int i = 0; i < 5; i++) { const float dl = p[i].x - mean; m2 += p[i].y + 128.f * dl * dl; }
    const float hd = rbf(sqrtf(rbf(rbf(m2 * (1.f / D_)) + 1e-5f)));
    const float hr = 1.f / hd;
    const bf162 hm2 = __float2bfloat162_rn(mean);
    float r = 0.f;
#pragma unroll
    for (int k = 0; k < 4; k++) {
      const uint4 w4 = sm.wr[4 * (4 * gqi + k) + tq];
      const uint32_t wv[4] = {w4.x, w4.y, w4.z, w4.w};
#pragma unroll
      for (int i = 0; i < 4; i++) {
        const uint32_t d = b2u(__hsub2_rn(u2b(hreg[4 * k + i]), hm2));
        const uint32_t hn = pack2(fdivr(lo_f(d), hd, hr), fdivr(hi_f(d), hd, hr));
        hnreg[4 * k + i] = hn;
        r = fmaf(lo_f(hn), lo_f(wv[i]), r);
        r = fmaf(hi_f(hn), hi_f(wv[i]), r);
      }
    }
    r += __shfl_xor_sync(0xffffffffu, r, 1);
    r += __shfl_xor_sync(0xffffffffu, r, 2);
    if (tq == 0) sm.rp[row][gqi] = r;
  }
  __syncthreads();
  uint32_t best;
  {
    const int rr = lane & 15;
    const float r = ((sm.rp[rr][0] + sm.rp[rr][1]) + (sm.rp[rr][2] + sm.rp[rr][3])) + sm.rp[rr][4];
    const uint32_t bits = __bfloat16_as_ushort(__float2bfloat16_rn(r));
    const uint32_t ord = (bits & 0x8000u) ? (bits ^ 0xFFFFu) : (bits ^ 0x8000u);
    const uint32_t key = (ord << 16) | 0x8000u | (uint32_t)(2047 - (cta * 16 + rr));
    best = __reduce_max_sync(0xffffffffu, key);
  }
  if (tid == 352) asm volatile("st.relaxed.gpu.global.u32 [%0], %1;" ::"l"(&g_keys[cta]), "r"(best) : "memory");
  const int brow = (2047 - (int)(best & 0x7FFu)) - cta * 16;
  uint4 outv[4];
  if (wid < 10) {
#pragma unroll
    for (int k = 0; k < 4; k++) {
      outv[k].x = b2u(__hadd2_rn(u2b(hreg[4 * k + 0]), u2b(hnreg[4 * k + 0])));
      outv[k].y = b2u(__hadd2_rn(u2b(hreg[4 * k + 1]), u2b(hnreg[4 * k + 1])));
      outv[k].z = b2u(__hadd2_rn(u2b(hreg[4 * k + 2]), u2b(hnreg[4 * k + 2])));
      outv[k].w = b2u(__hadd2_rn(u2b(hreg[4 * k + 3]), u2b(hnreg[4 * k + 3])));
      const int chunk = 4 * (4 * gqi + k) + tq;
      if (row == brow) {
        st_pub4(&g_cand[cta][0][chunk], enc4(make_uint4(hnreg[4 * k], hnreg[4 * k + 1], hnreg[4 * k + 2], hnreg[4 * k + 3])));
        st_pub4(&g_cand[cta][1][chunk], enc4(make_uint4(hreg[4 * k], hreg[4 * k + 1], hreg[4 * k + 2], hreg[4 * k + 3])));
      } else {
        *reinterpret_cast<uint4*>(gout + (size_t)(cta * 16 + row) * D_ + chunk * 8) = outv[k];
      }
    }
  }
  STAMP(6);
  if (wid == 11) {
    const uint4* kp = reinterpret_cast<const uint4*>(g_keys) + lane;
    uint4 v = ld_poll4(kp);
    int it = 0;
    while (!ready4(v) && ++it < SPIN_LIMIT) v = ld_poll4(kp);
    const uint32_t m = max(max(v.x, v.y), max(v.z, v.w));
    const uint32_t wk = __reduce_max_sync(0xffffffffu, m);
    if (lane == 0) sm.win = wk;
  }
  __syncthreads();
  const uint32_t win = sm.win;
  const int wrow = 2047 - (int)(win & 0x7FFu);
  const int wcta = wrow >> 4;
  if (wid < 10 && row == brow && wcta != cta) {
#pragma unroll
    for (int k = 0; k < 4; k++)
      *reinterpret_cast<uint4*>(gout + (size_t)(cta * 16 + row) * D_ + (4 * (4 * gqi + k) + tq) * 8) = outv[k];
  }
  STAMP(7);
  if (cta < N1 + N2) {
    const uint32_t mw = smem_u32(&sm.mbarw);
    uint32_t ok = 0;
    int it = 0;
    while (!ok && ++it < SPIN_LIMIT)
      asm volatile("{ .reg .pred p; mbarrier.try_wait.parity.shared.b64 p, [%1], 0; selp.u32 %0, 1, 0, p; }" : "=r"(ok) : "r"(mw) : "memory");
  }
  float* xs = &sm.z[0][0][0];
  float* part = xs + 2048;
  if (cta < N1) {
    if (tid < 80) {
      const uint4 v = poll4(&g_cand[wcta][0][tid]);
      float4* xp = reinterpret_cast<float4*>(xs + tid * 8);
      xp[0] = make_float4(lo_f(v.x), hi_f(v.x), lo_f(v.y), hi_f(v.y));
      xp[1] = make_float4(lo_f(v.z), hi_f(v.z), lo_f(v.w), hi_f(v.w));
    }
    __syncthreads();
    const int m = wid / 6, hc = (wid % 6) >> 1, rs = (wid & 1) * 32 + lane;
    float a[8];
#pragma unroll
    for (int j = 0; j < 8; j++) a[j] = 0.f;
#pragma unroll
    for (int it = 0; it < 10; it++) {
      const int r = rs + 64 * it;
      const uint4 wv = sm.w[m * 1920 + r * 3 + hc];
      const float x = xs[r];
      a[0] = fmaf(x, lo_f(wv.x), a[0]); a[1] = fmaf(x, hi_f(wv.x), a[1]);
      a[2] = fmaf(x, lo_f(wv.y), a[2]); a[3] = fmaf(x, hi_f(wv.y), a[3]);
      a[4] = fmaf(x, lo_f(wv.z), a[4]); a[5] = fmaf(x, hi_f(wv.z), a[5]);
      a[6] = fmaf(x, lo_f(wv.w), a[6]); a[7] = fmaf(x, hi_f(wv.w), a[7]);
    }
    {
      const bool up = lane & 16;
#pragma unroll
      for (int j = 0; j < 4; j++) {
        const float send = up ? a[j] : a[j + 4], keep = up ? a[j + 4] : a[j];
        a[j] = keep + __shfl_xor_sync(0xffffffffu, send, 16);
      }
      const bool up2 = lane & 8;
#pragma unroll
      for (int j = 0; j < 2; j++) {
        const float send = up2 ? a[j] : a[j + 2], keep = up2 ? a[j + 2] : a[j];
        a[j] = keep + __shfl_xor_sync(0xffffffffu, send, 8);
      }
      const bool up3 = lane & 4;
      const float send = up3 ? a[0] : a[1], keep = up3 ? a[1] : a[0];
      a[0] = keep + __shfl_xor_sync(0xffffffffu, send, 4);
      a[0] += __shfl_xor_sync(0xffffffffu, a[0], 2);
      a[0] += __shfl_xor_sync(0xffffffffu, a[0], 1);
      if ((lane & 3) == 0) part[wid * 8 + (lane >> 2)] = a[0];
    }
    __syncthreads();
    if (wid == 0) {
      uint32_t bits = 0;
      if (lane < 24) {
        const int hc2 = lane >> 3, j = lane & 7;
        const float gt = rbf(part[(2 * hc2) * 8 + j] + part[(2 * hc2 + 1) * 8 + j]);
        const float up = rbf(part[(6 + 2 * hc2) * 8 + j] + part[(6 + 2 * hc2 + 1) * 8 + j]);
        const float sg = rbf(gt / (1.f + __expf(-gt)));
        bits = __bfloat16_as_ushort(__float2bfloat16_rn(sg * up));
      }
      const uint32_t nb = __shfl_down_sync(0xffffffffu, bits, 1);
      const uint32_t pw = bits | (nb << 16);
      const uint32_t w1 = __shfl_down_sync(0xffffffffu, pw, 2), w2 = __shfl_down_sync(0xffffffffu, pw, 4), w3 = __shfl_down_sync(0xffffffffu, pw, 6);
      if (lane < 24 && (lane & 7) == 0) st_pub4(&g_act[cta * 3 + (lane >> 3)], enc4(make_uint4(pw, w1, w2, w3)));
    }
  } else if (cta < N1 + N2) {
    const int j2 = cta - N1;
    uint4 rowv = make_uint4(0, 0, 0, 0);
    if (tid < 192) {
      const uint4 v = poll4(&g_act[tid]);
      float4* xp = reinterpret_cast<float4*>(xs + tid * 8);
      xp[0] = make_float4(lo_f(v.x), hi_f(v.x), lo_f(v.y), hi_f(v.y));
      xp[1] = make_float4(lo_f(v.z), hi_f(v.z), lo_f(v.w), hi_f(v.w));
    } else if (tid < 196) {
      const int t = tid - 192;
      rowv = poll4(&g_cand[wcta][t >> 1][j2 * 2 + (t & 1)]);
      reinterpret_cast<uint4*>(part + 256)[t] = rowv;
    }
    __syncthreads();
    const int hc = lane & 1, rs = wid * 16 + (lane >> 1);
    float a[8];
#pragma unroll
    for (int j = 0; j < 8; j++) a[j] = 0.f;
#pragma unroll
    for (int it = 0; it < 8; it++) {
      const int r = rs + 192 * it;
      const uint4 wv = sm.w[r * 2 + hc];
      const float x = xs[r];
      a[0] = fmaf(x, lo_f(wv.x), a[0]); a[1] = fmaf(x, hi_f(wv.x), a[1]);
      a[2] = fmaf(x, lo_f(wv.y), a[2]); a[3] = fmaf(x, hi_f(wv.y), a[3]);
      a[4] = fmaf(x, lo_f(wv.z), a[4]); a[5] = fmaf(x, hi_f(wv.z), a[5]);
      a[6] = fmaf(x, lo_f(wv.w), a[6]); a[7] = fmaf(x, hi_f(wv.w), a[7]);
    }
    {
      const bool up = lane & 16;
#pragma unroll
      for (int j = 0; j < 4; j++) {
        const float send = up ? a[j] : a[j + 4], keep = up ? a[j + 4] : a[j];
        a[j] = keep + __shfl_xor_sync(0xffffffffu, send, 16);
      }
      const bool up2 = lane & 8;
#pragma unroll
      for (int j = 0; j < 2; j++) {
        const float send = up2 ? a[j] : a[j + 2], keep = up2 ? a[j + 2] : a[j];
        a[j] = keep + __shfl_xor_sync(0xffffffffu, send, 8);
      }
      const bool up3 = lane & 4;
      const float send = up3 ? a[0] : a[1], keep = up3 ? a[1] : a[0];
      a[0] = keep + __shfl_xor_sync(0xffffffffu, send, 4);
      a[0] += __shfl_xor_sync(0xffffffffu, a[0], 2);
      if ((lane & 2) == 0) part[wid * 16 + hc * 8 + (lane >> 2)] = a[0];
    }
    __syncthreads();
    if (tid < 16) {
      float y = 0.f;
#pragma unroll
      for (int i = 0; i < 12; i++) y += part[i * 16 + tid];
      const uint32_t ord = win >> 16;
      const uint32_t rb = (ord & 0x8000u) ? (ord ^ 0x8000u) : (ord ^ 0xFFFFu);
      const float r = __uint_as_float(rb << 16);
      const float sg = rbf(1.f / (1.f + __expf(-r)));
      const float yy = rbf(rbf(y) * sg);
      const unsigned short* rv = reinterpret_cast<const unsigned short*>(part + 256);
      const float hn = __uint_as_float((uint32_t)rv[tid] << 16), h = __uint_as_float((uint32_t)rv[16 + tid] << 16);
      gout[(size_t)wrow * D_ + j2 * 16 + tid] = __float2bfloat16_rn(h + rbf(hn + yy));
    }
  }
  STAMP(8);
}

}

typedef CUresult (*EncodeFn)(CUtensorMap*, CUtensorMapDataType, cuuint32_t, void*, const cuuint64_t*, const cuuint64_t*,
                             const cuuint32_t*, const cuuint32_t*, CUtensorMapInterleave, CUtensorMapSwizzle,
                             CUtensorMapL2promotion, CUtensorMapFloatOOBfill);

extern "C" void kernel_launch(void* const* d_in, const int* in_sizes, int n_in, void* d_out, int out_size) {
  (void)in_sizes; (void)n_in; (void)out_size;
  static EncodeFn encode = nullptr;
  static CUtensorMap tmg, tmu, tmd;
  static void* cached[3] = {nullptr, nullptr, nullptr};
  if (!encode) {
    cudaFuncSetAttribute(fused_kernel, cudaFuncAttributeMaxDynamicSharedMemorySize, (int)sizeof(Smem));
    void* fn = nullptr;
    cudaDriverEntryPointQueryResult qr;
    cudaGetDriverEntryPoint("cuTensorMapEncodeTiled", &fn, cudaEnableDefault, &qr);
    encode = (EncodeFn)fn;
  }
  if (cached[0] != d_in[8] || cached[1] != d_in[9] || cached[2] != d_in[10]) {
    const cuuint32_t es[2] = {1, 1};
    {
      const cuuint64_t dims[2] = {F_, D_}, strides[1] = {F_ * 2};
      const cuuint32_t box[2] = {24, 160};
      encode(&tmg, CU_TENSOR_MAP_DATA_TYPE_BFLOAT16, 2, d_in[8], dims, strides, box, es, CU_TENSOR_MAP_INTERLEAVE_NONE,
             CU_TENSOR_MAP_SWIZZLE_NONE, CU_TENSOR_MAP_L2_PROMOTION_NONE, CU_TENSOR_MAP_FLOAT_OOB_FILL_NONE);
      encode(&tmu, CU_TENSOR_MAP_DATA_TYPE_BFLOAT16, 2, d_in[9], dims, strides, box, es, CU_TENSOR_MAP_INTERLEAVE_NONE,
             CU_TENSOR_MAP_SWIZZLE_NONE, CU_TENSOR_MAP_L2_PROMOTION_NONE, CU_TENSOR_MAP_FLOAT_OOB_FILL_NONE);
    }
    {
      const cuuint64_t dims[2] = {D_, F_}, strides[1] = {D_ * 2};
      const cuuint32_t box[2] = {16, 256};
      encode(&tmd, CU_TENSOR_MAP_DATA_TYPE_BFLOAT16, 2, d_in[10], dims, strides, box, es, CU_TENSOR_MAP_INTERLEAVE_NONE,
             CU_TENSOR_MAP_SWIZZLE_NONE, CU_TENSOR_MAP_L2_PROMOTION_NONE, CU_TENSOR_MAP_FLOAT_OOB_FILL_NONE);
    }
    cached[0] = d_in[8]; cached[1] = d_in[9]; cached[2] = d_in[10];
  }
  fused_kernel<<<NCTA, NTHR, sizeof(Smem), cudaStreamPerThread>>>(
      tmg, tmu, tmd, (const bf16*)d_in[0], (const bf16*)d_in[1], (const bf16*)d_in[2], (const bf16*)d_in[3],
      (const bf16*)d_in[4], (const bf16*)d_in[5], (const bf16*)d_in[7], (bf16*)d_out);
}
```

```cpp
#include <cuda_runtime.h>
#include <cuda_bf16.h>
#include <cuda.h>
#include <stdint.h>

namespace {

typedef __nv_bfloat16 bf16;
typedef __nv_bfloat162 bf162;

constexpr int S_ = 2048, D_ = 640, F_ = 1536;
constexpr int NCTA = 128, CPC = 5, NTHR = 384;
constexpr int UPAD = 136, USTR = 2192;
constexpr int TABW = 1040;
constexpr int ZPB = 132;
constexpr int QSTR = 648;
constexpr int N1 = 64;
constexpr int N2 = 40;
constexpr int SPIN_LIMIT = 1 << 19;
#define POLL_NS 100
#define H_DELAY_NS 0

struct __align__(128) Smem {
  uint32_t tab[CPC][2][TABW];
  bf16 u[CPC][USTR];
  float z[2][4][ZPB * 16];
  bf16 q[16][QSTR];
  alignas(128) uint4 w[3840];
  uint4 wr[80];
  float2 st[16][5];
  float rp[16][5];
  unsigned long long mbar;
  unsigned long long mbarw;
  uint32_t target;
  uint32_t target2;
  uint32_t best;
  uint32_t win;
};

__device__ uint4 g_kv[D_ * S_ / 8];
__device__ uint4 g_y2[D_ * S_ / 8];
__device__ uint32_t g_keys[NCTA];
__device__ uint4 g_cand[NCTA][2][80];
__device__ uint4 g_act[F_ / 8];
__device__ unsigned int g_ctr;
__device__ unsigned int g_ctr2;
#define STAMP(i)

__device__ __forceinline__ uint32_t smem_u32(const void* p) { return (uint32_t)__cvta_generic_to_shared(p); }
__device__ __forceinline__ void wg_fence() { asm volatile("wgmma.fence.sync.aligned;" ::: "memory"); }
__device__ __forceinline__ void wg_commit() { asm volatile("wgmma.commit_group.sync.aligned;" ::: "memory"); }
template <int N> __device__ __forceinline__ void wg_wait() { asm volatile("wgmma.wait_group.sync.aligned %0;" ::"n"(N) : "memory"); }
__device__ __forceinline__ void bar_sync(int id, int n) { asm volatile("bar.sync %0, %1;" ::"r"(id), "r"(n) : "memory"); }
__device__ __forceinline__ void bar_arrive(int id, int n) { asm volatile("bar.arrive %0, %1;" ::"r"(id), "r"(n) : "memory"); }
__device__ __forceinline__ bf162 u2b(uint32_t u) { return *reinterpret_cast<bf162*>(&u); }
__device__ __forceinline__ uint32_t b2u(bf162 b) { return *reinterpret_cast<uint32_t*>(&b); }
__device__ __forceinline__ float lo_f(uint32_t u) { return __uint_as_float(u << 16); }
__device__ __forceinline__ float hi_f(uint32_t u) { return __uint_as_float(u & 0xFFFF0000u); }
__device__ __forceinline__ float rbf(float x) { return __bfloat162float(__float2bfloat16_rn(x)); }
__device__ __forceinline__ uint32_t pack2(float a, float b) { return b2u(__floats2bfloat162_rn(a, b)); }
__device__ __forceinline__ uint32_t enc(uint32_t w) { return max(~w, 1u); }
__device__ __forceinline__ uint4 enc4(uint4 v) { return make_uint4(enc(v.x), enc(v.y), enc(v.z), enc(v.w)); }
__device__ __forceinline__ uint4 ld_poll4(const uint4* p) {
  uint4 v;
  asm volatile("ld.relaxed.gpu.global.v4.u32 {%0,%1,%2,%3}, [%4];" : "=r"(v.x), "=r"(v.y), "=r"(v.z), "=r"(v.w) : "l"(p) : "memory");
  return v;
}
__device__ __forceinline__ bool ready4(uint4 v) { return v.x != 0u && v.y != 0u && v.z != 0u && v.w != 0u; }
__device__ __forceinline__ uint4 poll4(const uint4* p) {
  uint4 v = ld_poll4(p);
  int it = 0;
  while (!ready4(v) && ++it < SPIN_LIMIT) v = ld_poll4(p);
  return make_uint4(~v.x, ~v.y, ~v.z, ~v.w);
}
__device__ __forceinline__ void st_pub4(uint4* p, uint4 v) {
  asm volatile("st.relaxed.gpu.global.v4.u32 [%0], {%1,%2,%3,%4};" ::"l"(p), "r"(v.x), "r"(v.y), "r"(v.z), "r"(v.w) : "memory");
}
__device__ __forceinline__ void st_pub2(uint2* p, uint32_t a, uint32_t b) {
  asm volatile("st.relaxed.gpu.global.v2.u32 [%0], {%1,%2};" ::"l"(p), "r"(a), "r"(b) : "memory");
}
__device__ __forceinline__ void mma_bf16(float (&c)[4], uint32_t a0, uint32_t a2, uint32_t b0, uint32_t b1) {
  asm volatile("mma.sync.aligned.m16n8k16.row.col.f32.bf16.bf16.f32 {%0,%1,%2,%3}, {%4,%5,%6,%5}, {%7,%8}, {%0,%1,%2,%3};"
               : "+f"(c[0]), "+f"(c[1]), "+f"(c[2]), "+f"(c[3]) : "r"(a0), "r"(0u), "r"(a2), "r"(b0), "r"(b1));
}
__device__ __forceinline__ float fdivr(float a, float d, float r) {
  float q = a * r;
  float e = fmaf(-q, d, a);
  return fmaf(e, r, q);
}

template <bool FIRST> __device__ __forceinline__ void wgmma32(float (&d)[16], const uint32_t* a, uint64_t desc) {
  if (FIRST) {
    asm volatile("wgmma.mma_async.sync.aligned.m64n32k16.f32.bf16.bf16 {%0,%1,%2,%3,%4,%5,%6,%7,%8,%9,%10,%11,%12,%13,%14,%15}, {%16,%17,%18,%19}, %20, 0, 1, 1, 0;"
                 : "+f"(d[0]), "+f"(d[1]), "+f"(d[2]), "+f"(d[3]), "+f"(d[4]), "+f"(d[5]), "+f"(d[6]), "+f"(d[7]),
                   "+f"(d[8]), "+f"(d[9]), "+f"(d[10]), "+f"(d[11]), "+f"(d[12]), "+f"(d[13]), "+f"(d[14]), "+f"(d[15])
                 : "r"(a[0]), "r"(a[1]), "r"(a[2]), "r"(a[3]), "l"(desc));
  } else {
    asm volatile("wgmma.mma_async.sync.aligned.m64n32k16.f32.bf16.bf16 {%0,%1,%2,%3,%4,%5,%6,%7,%8,%9,%10,%11,%12,%13,%14,%15}, {%16,%17,%18,%19}, %20, 1, 1, 1, 0;"
                 : "+f"(d[0]), "+f"(d[1]), "+f"(d[2]), "+f"(d[3]), "+f"(d[4]), "+f"(d[5]), "+f"(d[6]), "+f"(d[7]),
                   "+f"(d[8]), "+f"(d[9]), "+f"(d[10]), "+f"(d[11]), "+f"(d[12]), "+f"(d[13]), "+f"(d[14]), "+f"(d[15])
                 : "r"(a[0]), "r"(a[1]), "r"(a[2]), "r"(a[3]), "l"(desc));
  }
}

template <int G> __device__ __forceinline__ void load_a(uint32_t (&a)[8], const uint32_t* tp) {
#pragma unroll
  for (int q = 0; q < 2; q++) {
    const int e = 2 * G + q;
    a[4 * q + 0] = tp[-64 * e];
    a[4 * q + 1] = tp[-64 * e - 32];
    a[4 * q + 2] = tp[-64 * e + 4];
    a[4 * q + 3] = tp[-64 * e - 28];
  }
}
__device__ __forceinline__ void load_a_all(uint32_t (&a)[8][8], const uint32_t* tp) {
  load_a<0>(a[0], tp); load_a<1>(a[1], tp); load_a<2>(a[2], tp); load_a<3>(a[3], tp);
  load_a<4>(a[4], tp); load_a<5>(a[5], tp); load_a<6>(a[6], tp); load_a<7>(a[7], tp);
}
template <int G> __device__ __forceinline__ void issue_g(float (&acc)[8][16], uint32_t (&a)[8], uint64_t desc0) {
  wg_fence();
#pragma unroll
  for (int q = 0; q < 2; q++) {
#pragma unroll
    for (int b = G; b < 8; b++) {
      const int delta = 2 * b - (2 * G + q);
      if (G == 0 && q == 0) wgmma32<true>(acc[b], &a[4 * q], desc0 + (uint64_t)(int64_t)(16 * delta));
      else wgmma32<false>(acc[b], &a[4 * q], desc0 + (uint64_t)(int64_t)(16 * delta));
    }
  }
  wg_commit();
}
template <int B> __device__ __forceinline__ void fence_blk(float (&acc)[8][16]) {
#pragma unroll
  for (int i = 0; i < 16; i++) asm volatile("" : "+f"(acc[B][i])::"memory");
}
__device__ __forceinline__ void fence_a(uint32_t (&a)[8]) {
#pragma unroll
  for (int i = 0; i < 8; i++) asm volatile("" : "+r"(a[i])::"memory");
}
template <int B> __device__ __forceinline__ void sts_blk(float (&acc)[8][16], float* zw, int off_even, int off_odd) {
#pragma unroll
  for (int jj = 0; jj < 4; jj++) {
    const int j = 4 * B + jj;
    float p0 = acc[B][4 * jj + 0], p1 = acc[B][4 * jj + 1];
    if (jj > 0) { p0 += acc[B][4 * (jj - 1) + 2]; p1 += acc[B][4 * (jj - 1) + 3]; }
    else if (B > 0) { p0 += acc[B > 0 ? B - 1 : 0][14]; p1 += acc[B > 0 ? B - 1 : 0][15]; }
    zw[64 * j + off_even] = p0;
    zw[64 * j + off_odd] = p1;
  }
}
__device__ __forceinline__ int tile_perm(int ch) { return ch ^ (((ch >> 3) & 3) << 1); }

__device__ __forceinline__ void wait_cleared(uint32_t target) {
  uint32_t v;
  int it = 0;
  do {
    asm volatile("ld.acquire.gpu.global.u32 %0, [%1];" : "=r"(v) : "l"(&g_ctr) : "memory");
  } while ((int)(v - target) < 0 && ++it < SPIN_LIMIT);
}

__global__ void __launch_bounds__(NTHR, 1)
fused_kernel(const __grid_constant__ CUtensorMap tmg, const __grid_constant__ CUtensorMap tmu,
             const __grid_constant__ CUtensorMap tmd, const bf16* __restrict__ gq, const bf16* __restrict__ gk, const bf16* __restrict__ gv,
             const bf16* __restrict__ gsk, const bf16* __restrict__ gh, const bf16* __restrict__ gD,
             const bf16* __restrict__ gwr, bf16* __restrict__ gout) {
  extern __shared__ __align__(128) unsigned char smraw[];
  Smem& sm = *reinterpret_cast<Smem*>(smraw);
  const int tid = threadIdx.x;
  const int cta = blockIdx.x;
  const int c0 = cta * CPC;
  const int lane = tid & 31;
  const int wid = tid >> 5;
  STAMP(0);

  {
    const int oc = tid >> 2;
    const int r0 = cta * 16 + (tid & 3) * 4;
    uint4 kk[7], vv[4], sk[4];
    if (tid < 320) {
      const uint4* kp = reinterpret_cast<const uint4*>(gk) + (size_t)r0 * 80 + oc;
      const uint4* vp = reinterpret_cast<const uint4*>(gv) + (size_t)r0 * 80 + oc;
#pragma unroll
      for (int i = 0; i < 7; i++) kk[i] = (i >= 3 || r0 > 0) ? __ldg(kp + (i - 3) * 80) : make_uint4(0, 0, 0, 0);
#pragma unroll
      for (int i = 0; i < 4; i++) vv[i] = __ldg(vp + i * 80);
#pragma unroll
      for (int i = 0; i < 4; i++) sk[i] = __ldg(reinterpret_cast<const uint4*>(gsk) + oc * 4 + i);
    }
    uint4 hv[4];
    uint32_t hp[4];
#pragma unroll
    for (int i = 0; i < 4; i++) {
      const int t = (NTHR - 1 - tid) + NTHR * i;
      hp[i] = 0;
      if (t < CPC * 256) {
        const bf16* p = gh + (size_t)c0 * S_ + t * 8;
        hv[i] = __ldg(reinterpret_cast<const uint4*>(p));
        if (t & 255) hp[i] = __ldg(reinterpret_cast<const unsigned short*>(p) - 1);
      }
    }
    STAMP(9);
    if (tid < 320) {
#pragma unroll
      for (int p = 0; p < 4; p++) {
        const bf162 w0 = u2b(__byte_perm(sk[p].x, sk[p].z, 0x5410)), w1 = u2b(__byte_perm(sk[p].x, sk[p].z, 0x7632));
        const bf162 w2 = u2b(__byte_perm(sk[p].y, sk[p].w, 0x5410)), w3 = u2b(__byte_perm(sk[p].y, sk[p].w, 0x7632));
        uint32_t kv[4];
#pragma unroll
        for (int i = 0; i < 4; i++) {
          const uint32_t k0 = p == 0 ? kk[i].x : p == 1 ? kk[i].y : p == 2 ? kk[i].z : kk[i].w;
          const uint32_t k1 = p == 0 ? kk[i + 1].x : p == 1 ? kk[i + 1].y : p == 2 ? kk[i + 1].z : kk[i + 1].w;
          const uint32_t k2 = p == 0 ? kk[i + 2].x : p == 1 ? kk[i + 2].y : p == 2 ? kk[i + 2].z : kk[i + 2].w;
          const uint32_t k3 = p == 0 ? kk[i + 3].x : p == 1 ? kk[i + 3].y : p == 2 ? kk[i + 3].z : kk[i + 3].w;
          const uint32_t vx = p == 0 ? vv[i].x : p == 1 ? vv[i].y : p == 2 ? vv[i].z : vv[i].w;
          bf162 a = __hmul2_rn(u2b(k0), w3);
          a = __hadd2_rn(a, __hmul2_rn(u2b(k1), w2));
          a = __hadd2_rn(a, __hmul2_rn(u2b(k2), w1));
          a = __hadd2_rn(a, __hmul2_rn(u2b(k3), w0));
          kv[i] = b2u(__hmul2_rn(a, u2b(vx)));
        }
        uint2* dst = reinterpret_cast<uint2*>(g_kv) + (size_t)(oc * 8 + 2 * p) * 512 + (r0 >> 2);
        st_pub2(dst, enc(__byte_perm(kv[0], kv[1], 0x5410)), enc(__byte_perm(kv[2], kv[3], 0x5410)));
        st_pub2(dst + 512, enc(__byte_perm(kv[0], kv[1], 0x7632)), enc(__byte_perm(kv[2], kv[3], 0x7632)));
      }
      STAMP(10);
      if (wid == 0) bar_sync(6, 320); else bar_arrive(6, 320);
      if (tid == 0) {
        const unsigned old = atomicAdd(&g_ctr2, 1u);
        sm.target2 = (old / NCTA + 1u) * NCTA;
      }
    } else {
      const int t0 = tid - 320;
      const uint4 zz = make_uint4(0, 0, 0, 0);
#pragma unroll 4
      for (int i = 0; i < 20; i++) g_y2[cta * 1280 + t0 + 64 * i] = zz;
      (&g_cand[cta][0][0])[t0] = zz;
      (&g_cand[cta][0][0])[64 + t0] = zz;
      if (t0 < 32) (&g_cand[cta][0][0])[128 + t0] = zz;
      else if (t0 < 35) { if (cta < N1) g_act[cta * 3 + (t0 - 32)] = zz; }
      else if (t0 == 35) g_keys[cta] = 0u;
      for (int t = t0; t < CPC * 17; t += 64) *reinterpret_cast<uint4*>(&sm.u[t / 17][(t % 17) * 8]) = zz;
      if (t0 < 40) *reinterpret_cast<uint4*>(&sm.tab[t0 >> 3][(t0 >> 2) & 1][1024 + 4 * (t0 & 3)]) = zz;
      *reinterpret_cast<uint4*>(&sm.z[0][t0 >> 4][(t0 & 15) * 4]) = zz;
      *reinterpret_cast<uint4*>(&sm.z[1][t0 >> 4][(t0 & 15) * 4]) = zz;
      if (t0 == 0) {
        asm volatile("mbarrier.init.shared.b64 [%0], 1;" ::"r"(smem_u32(&sm.mbar)) : "memory");
        asm volatile("mbarrier.init.shared.b64 [%0], 1;" ::"r"(smem_u32(&sm.mbarw)) : "memory");
      }
      bar_sync(7, 64);
      if (t0 == 32) {
        __threadfence();
        const unsigned old = atomicAdd(&g_ctr, 1u);
        sm.target = (old / NCTA + 1u) * NCTA;
      }
    }
#pragma unroll
    for (int i = 0; i < 4; i++) {
      const int t = (NTHR - 1 - tid) + NTHR * i;
      if (t < CPC * 256) {
        const int c = (t >> 8) == 4 ? 0 : (t >> 8) + 1, ch = t & 255;
        uint4 h = hv[i], r1, rr;
        r1.x = __byte_perm(h.w, 0, 0x1032); r1.y = __byte_perm(h.z, 0, 0x1032);
        r1.z = __byte_perm(h.y, 0, 0x1032); r1.w = __byte_perm(h.x, 0, 0x1032);
        rr.x = __byte_perm(h.w, h.z, 0x7610); rr.y = __byte_perm(h.z, h.y, 0x7610);
        rr.z = __byte_perm(h.y, h.x, 0x7610); rr.w = __byte_perm(h.x, hp[i], 0x5410);
        *reinterpret_cast<uint4*>(&sm.tab[c][0][(255 - ch) * 4]) = rr;
        *reinterpret_cast<uint4*>(&sm.tab[c][1][(255 - ch) * 4]) = r1;
      }
    }
    if (tid == 0) {
      const unsigned target = sm.target2;
      uint32_t v;
      int it = 0;
      do {
        asm volatile("ld.relaxed.gpu.global.u32 %0, [%1];" : "=r"(v) : "l"(&g_ctr2) : "memory");
      } while ((int)(v - target) < 0 && ++it < SPIN_LIMIT);
    }
    STAMP(12);
  }
  __syncthreads();
  {
    uint4 v[4];
    uint4* src = g_kv + c0 * 256 + tid;
#pragma unroll
    for (int i = 0; i < 4; i++) if (i < 3 || tid < 128) v[i] = ld_poll4(src + NTHR * i);
#pragma unroll
    for (int i = 0; i < 4; i++) {
      if (i < 3 || tid < 128) {
        int it = 0;
        while (!ready4(v[i]) && ++it < SPIN_LIMIT) { __nanosleep(POLL_NS); v[i] = ld_poll4(src + NTHR * i); }
        const int t = tid + NTHR * i;
        *reinterpret_cast<uint4*>(&sm.u[t >> 8][UPAD + (t & 255) * 8]) = make_uint4(~v[i].x, ~v[i].y, ~v[i].z, ~v[i].w);
        src[NTHR * i] = make_uint4(0, 0, 0, 0);
      }
    }
    STAMP(11);
    asm volatile("fence.proxy.async.shared::cta;" ::: "memory");
    __syncthreads();
  }
  STAMP(1);

  const int wg = __shfl_sync(0xffffffffu, tid >> 7, 0);
  const int wtid = tid & 127;
  uint4* tile = reinterpret_cast<uint4*>(&sm.tab[1][0][0]);
  bf16* qn_s = reinterpret_cast<bf16*>(tile + 1280);
  if (wg < 2) {
    asm volatile("setmaxnreg.inc.sync.aligned.u32 224;");
    const int w = (tid >> 5) & 3, g = lane >> 2, tq = lane & 3;
    float* zw = sm.z[wg][w];
    const int sw = 3 * (((tq + w) >> 1) & 1);
    const int off_even = 16 * (tq + w) + 4 * ((0 + (g >> 2)) ^ sw) + (g & 3);
    const int off_odd = 16 * (tq + w) + 4 * ((2 + (g >> 2)) ^ sw) + (g & 3);
    uint32_t a[8][8];
    const uint32_t* tp0 = &sm.tab[0][g & 1][1019 - 8 * w - (g >> 1) + tq];
    load_a_all(a, tp0 + (wg + 1) * 2 * TABW);
    float acc[8][16];
#pragma unroll
    for (int b = 0; b < 8; b++)
#pragma unroll
      for (int i = 0; i < 16; i++) acc[b][i] = 0.f;
#pragma unroll 1
    for (int c = wg; c < CPC; c += 2) {
      const uint64_t desc = (uint64_t)((smem_u32(&sm.u[c][UPAD - 8]) & 0x3FFFF) >> 4) | ((uint64_t)1 << 16) | ((uint64_t)8 << 32);
      if (c > 0) bar_sync(1 + wg, 256);
      issue_g<0>(acc, a[0], desc);
      issue_g<1>(acc, a[1], desc);
      issue_g<2>(acc, a[2], desc);
      issue_g<3>(acc, a[3], desc);
      issue_g<4>(acc, a[4], desc);
      issue_g<5>(acc, a[5], desc);
      if (c + 1 < CPC) bar_arrive(1 + (wg ^ 1), 256);
      issue_g<6>(acc, a[6], desc);
      issue_g<7>(acc, a[7], desc);
      if (c >= 2) bar_sync(5 + wg, 256);
      wg_wait<4>();
      fence_blk<0>(acc); fence_blk<1>(acc); fence_blk<2>(acc); fence_blk<3>(acc);
      sts_blk<0>(acc, zw, off_even, off_odd);
      sts_blk<1>(acc, zw, off_even, off_odd);
      sts_blk<2>(acc, zw, off_even, off_odd);
      sts_blk<3>(acc, zw, off_even, off_odd);
      wg_wait<0>();
      fence_blk<4>(acc); fence_blk<5>(acc); fence_blk<6>(acc); fence_blk<7>(acc);
#pragma unroll
      for (int i = 0; i < 8; i++) fence_a(a[i]);
      sts_blk<4>(acc, zw, off_even, off_odd);
      sts_blk<5>(acc, zw, off_even, off_odd);
      sts_blk<6>(acc, zw, off_even, off_odd);
      sts_blk<7>(acc, zw, off_even, off_odd);
      bar_arrive(3 + wg, 256);
      if (c + 2 < CPC) load_a_all(a, tp0 + (c == 2 ? 0 : (c + 3) * 2 * TABW));
    }
    STAMP(2 + wg);
    asm volatile("setmaxnreg.dec.sync.aligned.u32 168;");
    if (wg == 1) {
      {
        const uint32_t mb = smem_u32(&sm.mbar);
        uint32_t ok = 0;
        int it = 0;
        while (!ok && ++it < SPIN_LIMIT)
          asm volatile("{ .reg .pred p; mbarrier.try_wait.parity.shared.b64 p, [%1], 0; selp.u32 %0, 1, 0, p; }" : "=r"(ok) : "r"(mb) : "memory");
        uint32_t qv[4][10];
        float sv[4];
#pragma unroll
        for (int rr = 0; rr < 4; rr++) {
          const uint32_t* qp = reinterpret_cast<const uint32_t*>(&sm.q[w * 4 + rr][0]);
          float s = 0.f;
#pragma unroll
          for (int i = 0; i < 10; i++) { qv[rr][i] = qp[lane + 32 * i]; s += lo_f(qv[rr][i]) + hi_f(qv[rr][i]); }
          sv[rr] = s;
        }
#pragma unroll
        for (int o = 16; o > 0; o >>= 1)
#pragma unroll
          for (int rr = 0; rr < 4; rr++) sv[rr] += __shfl_xor_sync(0xffffffffu, sv[rr], o);
        float m2[4];
#pragma unroll
        for (int rr = 0; rr < 4; rr++) {
          sv[rr] *= (1.f / D_);
          float t = 0.f;
#pragma unroll
          for (int i = 0; i < 10; i++) { const float x = lo_f(qv[rr][i]) - sv[rr], y = hi_f(qv[rr][i]) - sv[rr]; t = fmaf(x, x, fmaf(y, y, t)); }
          m2[rr] = t;
        }
#pragma unroll
        for (int o = 16; o > 0; o >>= 1)
#pragma unroll
          for (int rr = 0; rr < 4; rr++) m2[rr] += __shfl_xor_sync(0xffffffffu, m2[rr], o);
#pragma unroll
        for (int rr = 0; rr < 4; rr++) {
          const float qd = rbf(sqrtf(rbf(rbf(m2[rr] * (1.f / D_)) + 1e-5f)));
          const float qr = 1.f / qd;
          const bf162 qm2 = __float2bfloat162_rn(sv[rr]);
          uint32_t* np = reinterpret_cast<uint32_t*>(qn_s + (w * 4 + rr) * QSTR);
#pragma unroll
          for (int i = 0; i < 10; i++) {
            const uint32_t d = b2u(__hsub2_rn(u2b(qv[rr][i]), qm2));
            np[lane + 32 * i] = pack2(fdivr(lo_f(d), qd, qr), fdivr(hi_f(d), qd, qr));
          }
        }
      }
#pragma unroll 1
      for (int cc = 0; cc < 4; cc++) {
        const int ch = wtid * 5 + cc;
        const uint4* src = g_y2 + cta * 1280 + ch * 2;
        uint4 v0 = ld_poll4(src), v1 = ld_poll4(src + 1);
        int it = 0;
        while (!ready4(v0) && ++it < SPIN_LIMIT) v0 = ld_poll4(src);
        while (!ready4(v1) && ++it < SPIN_LIMIT) v1 = ld_poll4(src + 1);
        const int pc = tile_perm(ch);
        tile[pc] = make_uint4(~v0.x, ~v0.y, ~v0.z, ~v0.w);
        tile[640 + pc] = make_uint4(~v1.x, ~v1.y, ~v1.z, ~v1.w);
      }
    }
  } else {
    asm volatile("setmaxnreg.dec.sync.aligned.u32 56;");
    if (wtid == 32) {
      const uint32_t mb = smem_u32(&sm.mbar), mw = smem_u32(&sm.mbarw);
      asm volatile("mbarrier.arrive.expect_tx.shared.b64 _, [%0], %1;" ::"r"(mb), "r"(17 * D_ * 2) : "memory");
#pragma unroll 1
      for (int r = 0; r < 16; r++)
        asm volatile("cp.async.bulk.shared::cluster.global.mbarrier::complete_tx::bytes [%0], [%1], %2, [%3];" ::"r"(smem_u32(&sm.q[r][0])),
                     "l"(gq + (size_t)(cta * 16 + r) * D_), "r"(D_ * 2), "r"(mb) : "memory");
      asm volatile("cp.async.bulk.shared::cluster.global.mbarrier::complete_tx::bytes [%0], [%1], %2, [%3];" ::"r"(smem_u32(&sm.wr[0])),
                   "l"(gwr), "r"(D_ * 2), "r"(mb) : "memory");
      if (cta < N1) {
        asm volatile("mbarrier.arrive.expect_tx.shared.b64 _, [%0], %1;" ::"r"(mw), "r"(3840 * 16) : "memory");
#pragma unroll 1
        for (int i = 0; i < 4; i++) {
          asm volatile("cp.async.bulk.tensor.2d.shared::cluster.global.mbarrier::complete_tx::bytes [%0], [%1, {%3, %4}], [%2];" ::"r"(smem_u32(&sm.w[i * 480])),
                       "l"(&tmg), "r"(mw), "r"(cta * 24), "r"(i * 160) : "memory");
          asm volatile("cp.async.bulk.tensor.2d.shared::cluster.global.mbarrier::complete_tx::bytes [%0], [%1, {%3, %4}], [%2];" ::"r"(smem_u32(&sm.w[1920 + i * 480])),
                       "l"(&tmu), "r"(mw), "r"(cta * 24), "r"(i * 160) : "memory");
        }
      } else if (cta < N1 + N2) {
        asm volatile("mbarrier.arrive.expect_tx.shared.b64 _, [%0], %1;" ::"r"(mw), "r"(3072 * 16) : "memory");
#pragma unroll 1
        for (int i = 0; i < 6; i++)
          asm volatile("cp.async.bulk.tensor.2d.shared::cluster.global.mbarrier::complete_tx::bytes [%0], [%1, {%3, %4}], [%2];" ::"r"(smem_u32(&sm.w[i * 512])),
                       "l"(&tmd), "r"(mw), "r"((cta - N1) * 16), "r"(i * 256) : "memory");
      }
    }
    if (wtid == 0) wait_cleared(sm.target);
    const int rpb = wtid >> 1, re2 = wtid & 1;
    const int rsw = 3 * ((rpb >> 1) & 1);
    const int roff0 = 16 * rpb + 4 * ((2 * re2 + 0) ^ rsw);
    const int roff1 = 16 * rpb + 4 * ((2 * re2 + 1) ^ rsw);
    const uint32_t dvl = reinterpret_cast<const unsigned short*>(gD)[c0 + (lane < CPC ? lane : 0)];
#pragma unroll 1
    for (int c = 0; c < CPC; c++) {
      const int zg = c & 1;
      const uint32_t dvc = __shfl_sync(0xffffffffu, dvl, c);
      const bf162 d2 = u2b(dvc | (dvc << 16));
      bar_sync(3 + zg, 256);
#pragma unroll
      for (int half = 0; half < 2; half++) {
        const float* zb = sm.z[zg][0] + half * 1024;
        float4 x[4][2];
#pragma unroll
        for (int ww = 0; ww < 4; ww++) {
          x[ww][0] = *reinterpret_cast<const float4*>(zb + ww * ZPB * 16 + roff0);
          x[ww][1] = *reinterpret_cast<const float4*>(zb + ww * ZPB * 16 + roff1);
        }
        const int sidx = half * 1024 + wtid * 8;
        const uint4 kvv = *reinterpret_cast<const uint4*>(&sm.u[c][UPAD + sidx]);
        if (half == 1 && c + 2 < CPC) bar_arrive(5 + zg, 256);
        uint4 o;
        o.x = pack2((x[0][0].x + x[1][0].x) + (x[2][0].x + x[3][0].x), (x[0][0].y + x[1][0].y) + (x[2][0].y + x[3][0].y));
        o.y = pack2((x[0][0].z + x[1][0].z) + (x[2][0].z + x[3][0].z), (x[0][0].w + x[1][0].w) + (x[2][0].w + x[3][0].w));
        o.z = pack2((x[0][1].x + x[1][1].x) + (x[2][1].x + x[3][1].x), (x[0][1].y + x[1][1].y) + (x[2][1].y + x[3][1].y));
        o.w = pack2((x[0][1].z + x[1][1].z) + (x[2][1].z + x[3][1].z), (x[0][1].w + x[1][1].w) + (x[2][1].w + x[3][1].w));
        o.x = b2u(__hadd2_rn(u2b(o.x), __hmul2_rn(u2b(kvv.x), d2)));
        o.y = b2u(__hadd2_rn(u2b(o.y), __hmul2_rn(u2b(kvv.y), d2)));
        o.z = b2u(__hadd2_rn(u2b(o.z), __hmul2_rn(u2b(kvv.z), d2)));
        o.w = b2u(__hadd2_rn(u2b(o.w), __hmul2_rn(u2b(kvv.w), d2)));
        st_pub4(g_y2 + ((64 * half + rpb) * 640 + c0 + c) * 2 + re2, enc4(o));
      }
    }
    STAMP(4);
    asm volatile("setmaxnreg.inc.sync.aligned.u32 168;");
  }

  if (tid < 128 || tid >= 256) {
    const int t = tid < 128 ? tid : tid - 128;
    const int ch = (t >> 1) * 5 + 4, hh = t & 1;
    const uint4 v = poll4(g_y2 + cta * 1280 + ch * 2 + hh);
    tile[hh * 640 + tile_perm(ch)] = v;
  }
  __syncthreads();
  STAMP(5);

  const int g = lane >> 2, tq = lane & 3;
  const int hh = wid & 1, gqi = wid >> 1;
  const int row = hh * 8 + g;
  uint32_t hreg[16], hnreg[16];
  if (wid < 10) {
    float cs[4] = {0.f, 0.f, 0.f, 0.f};
#pragma unroll
    for (int k = 0; k < 4; k++) {
      const int base = 32 * (4 * gqi + k);
      const int lch = base + 8 * ((lane & 7) >> 1) + 2 * (lane >> 3) + (lane & 1);
      uint32_t y[4];
      asm volatile("ldmatrix.sync.aligned.m8n8.x4.trans.shared.b16 {%0,%1,%2,%3}, [%4];"
                   : "=r"(y[0]), "=r"(y[1]), "=r"(y[2]), "=r"(y[3]) : "r"(smem_u32(&tile[hh * 640 + tile_perm(lch)])) : "memory");
      const uint4 qv4 = *reinterpret_cast<const uint4*>(&sm.q[row][base + 8 * tq]);
      const uint4 qn4 = *reinterpret_cast<const uint4*>(qn_s + row * QSTR + base + 8 * tq);
      hreg[4 * k + 0] = b2u(__hadd2_rn(u2b(qv4.x), __hmul2_rn(u2b(qn4.x), u2b(y[0]))));
      hreg[4 * k + 1] = b2u(__hadd2_rn(u2b(qv4.y), __hmul2_rn(u2b(qn4.y), u2b(y[1]))));
      hreg[4 * k + 2] = b2u(__hadd2_rn(u2b(qv4.z), __hmul2_rn(u2b(qn4.z), u2b(y[2]))));
      hreg[4 * k + 3] = b2u(__hadd2_rn(u2b(qv4.w), __hmul2_rn(u2b(qn4.w), u2b(y[3]))));
      mma_bf16(cs, hreg[4 * k + 0], hreg[4 * k + 1], 0x3F803F80u, 0x3F803F80u);
      mma_bf16(cs, hreg[4 * k + 2], hreg[4 * k + 3], 0x3F803F80u, 0x3F803F80u);
    }
    const float mean = cs[0] * (1.f / 128.f);
    float m2a = 0.f, m2b = 0.f;
#pragma unroll
    for (int i = 0; i < 16; i++) {
      const float a = lo_f(hreg[i]) - mean, b = hi_f(hreg[i]) - mean;
      m2a = fmaf(a, a, m2a); m2b = fmaf(b, b, m2b);
    }
    float m2 = m2a + m2b;
    m2 += __shfl_xor_sync(0xffffffffu, m2, 1);
    m2 += __shfl_xor_sync(0xffffffffu, m2, 2);
    if (tq == 0) sm.st[row][gqi] = make_float2(mean, m2);
  }
  STAMP(13);
  __syncthreads();
  if (wid < 10) {
    float mean = 0.f, m2 = 0.f;
    float2 p[5];
#pragma unroll
    for (int i = 0; i < 5; i++) { p[i] = sm.st[row][i]; mean += p[i].x; }
    mean *= 0.2f;
#pragma unroll
    for (int i = 0; i < 5; i++) { const float dl = p[i].x - mean; m2 += p[i].y + 128.f * dl * dl; }
    const float hd = rbf(sqrtf(rbf(rbf(m2 * (1.f / D_)) + 1e-5f)));
    const float hr = 1.f / hd;
    const bf162 hm2 = __float2bfloat162_rn(mean);
    float cr[4] = {0.f, 0.f, 0.f, 0.f};
#pragma unroll
    for (int k = 0; k < 4; k++) {
      const uint4 w4 = sm.wr[4 * (4 * gqi + k) + tq];
#pragma unroll
      for (int i = 0; i < 4; i++) {
        const uint32_t d = b2u(__hsub2_rn(u2b(hreg[4 * k + i]), hm2));
        hnreg[4 * k + i] = pack2(fdivr(lo_f(d), hd, hr), fdivr(hi_f(d), hd, hr));
      }
      mma_bf16(cr, hnreg[4 * k + 0], hnreg[4 * k + 1], w4.x, w4.y);
      mma_bf16(cr, hnreg[4 * k + 2], hnreg[4 * k + 3], w4.z, w4.w);
    }
    if (tq == 0) sm.rp[row][gqi] = cr[0];
  }
  STAMP(14);
  __syncthreads();
  uint32_t best;
  {
    const int rr = lane & 15;
    const float r = ((sm.rp[rr][0] + sm.rp[rr][1]) + (sm.rp[rr][2] + sm.rp[rr][3])) + sm.rp[rr][4];
    const uint32_t bits = __bfloat16_as_ushort(__float2bfloat16_rn(r));
    const uint32_t ord = (bits & 0x8000u) ? (bits ^ 0xFFFFu) : (bits ^ 0x8000u);
    const uint32_t key = (ord << 16) | 0x8000u | (uint32_t)(2047 - (cta * 16 + rr));
    best = __reduce_max_sync(0xffffffffu, key);
  }
  if (tid == 352) asm volatile("st.relaxed.gpu.global.u32 [%0], %1;" ::"l"(&g_keys[cta]), "r"(best) : "memory");
  STAMP(15);
  const int brow = (2047 - (int)(best & 0x7FFu)) - cta * 16;
  uint4 outv[4];
  if (wid < 10) {
#pragma unroll
    for (int k = 0; k < 4; k++) {
      outv[k].x = b2u(__hadd2_rn(u2b(hreg[4 * k + 0]), u2b(hnreg[4 * k + 0])));
      outv[k].y = b2u(__hadd2_rn(u2b(hreg[4 * k + 1]), u2b(hnreg[4 * k + 1])));
      outv[k].z = b2u(__hadd2_rn(u2b(hreg[4 * k + 2]), u2b(hnreg[4 * k + 2])));
      outv[k].w = b2u(__hadd2_rn(u2b(hreg[4 * k + 3]), u2b(hnreg[4 * k + 3])));
      const int chunk = 4 * (4 * gqi + k) + tq;
      if (row == brow) {
        st_pub4(&g_cand[cta][0][chunk], enc4(make_uint4(hnreg[4 * k], hnreg[4 * k + 1], hnreg[4 * k + 2], hnreg[4 * k + 3])));
        st_pub4(&g_cand[cta][1][chunk], enc4(make_uint4(hreg[4 * k], hreg[4 * k + 1], hreg[4 * k + 2], hreg[4 * k + 3])));
      } else {
        *reinterpret_cast<uint4*>(gout + (size_t)(cta * 16 + row) * D_ + chunk * 8) = outv[k];
      }
    }
  }
  STAMP(6);
  if (wid == 11) {
    const uint4* kp = reinterpret_cast<const uint4*>(g_keys) + lane;
    uint4 v = ld_poll4(kp);
    int it = 0;
    while (!ready4(v) && ++it < SPIN_LIMIT) v = ld_poll4(kp);
    const uint32_t m = max(max(v.x, v.y), max(v.z, v.w));
    const uint32_t wk = __reduce_max_sync(0xffffffffu, m);
    if (lane == 0) sm.win = wk;
  }
  __syncthreads();
  const uint32_t win = sm.win;
  const int wrow = 2047 - (int)(win & 0x7FFu);
  const int wcta = wrow >> 4;
  if (wid < 10 && row == brow && wcta != cta) {
#pragma unroll
    for (int k = 0; k < 4; k++)
      *reinterpret_cast<uint4*>(gout + (size_t)(cta * 16 + row) * D_ + (4 * (4 * gqi + k) + tq) * 8) = outv[k];
  }
  STAMP(7);
  if (cta < N1 + N2) {
    const uint32_t mw = smem_u32(&sm.mbarw);
    uint32_t ok = 0;
    int it = 0;
    while (!ok && ++it < SPIN_LIMIT)
      asm volatile("{ .reg .pred p; mbarrier.try_wait.parity.shared.b64 p, [%1], 0; selp.u32 %0, 1, 0, p; }" : "=r"(ok) : "r"(mw) : "memory");
  }
  float* xs = &sm.z[0][0][0];
  float* part = xs + 2048;
  if (cta < N1) {
    if (tid < 80) {
      const uint4 v = poll4(&g_cand[wcta][0][tid]);
      float4* xp = reinterpret_cast<float4*>(xs + tid * 8);
      xp[0] = make_float4(lo_f(v.x), hi_f(v.x), lo_f(v.y), hi_f(v.y));
      xp[1] = make_float4(lo_f(v.z), hi_f(v.z), lo_f(v.w), hi_f(v.w));
    }
    __syncthreads();
    const int m = wid / 6, hc = (wid % 6) >> 1, rs = (wid & 1) * 32 + lane;
    float a[8];
#pragma unroll
    for (int j = 0; j < 8; j++) a[j] = 0.f;
#pragma unroll
    for (int it = 0; it < 10; it++) {
      const int r = rs + 64 * it;
      const uint4 wv = sm.w[m * 1920 + r * 3 + hc];
      const float x = xs[r];
      a[0] = fmaf(x, lo_f(wv.x), a[0]); a[1] = fmaf(x, hi_f(wv.x), a[1]);
      a[2] = fmaf(x, lo_f(wv.y), a[2]); a[3] = fmaf(x, hi_f(wv.y), a[3]);
      a[4] = fmaf(x, lo_f(wv.z), a[4]); a[5] = fmaf(x, hi_f(wv.z), a[5]);
      a[6] = fmaf(x, lo_f(wv.w), a[6]); a[7] = fmaf(x, hi_f(wv.w), a[7]);
    }
    {
      const bool up = lane & 16;
#pragma unroll
      for (int j = 0; j < 4; j++) {
        const float send = up ? a[j] : a[j + 4], keep = up ? a[j + 4] : a[j];
        a[j] = keep + __shfl_xor_sync(0xffffffffu, send, 16);
      }
      const bool up2 = lane & 8;
#pragma unroll
      for (int j = 0; j < 2; j++) {
        const float send = up2 ? a[j] : a[j + 2], keep = up2 ? a[j + 2] : a[j];
        a[j] = keep + __shfl_xor_sync(0xffffffffu, send, 8);
      }
      const bool up3 = lane & 4;
      const float send = up3 ? a[0] : a[1], keep = up3 ? a[1] : a[0];
      a[0] = keep + __shfl_xor_sync(0xffffffffu, send, 4);
      a[0] += __shfl_xor_sync(0xffffffffu, a[0], 2);
      a[0] += __shfl_xor_sync(0xffffffffu, a[0], 1);
      if ((lane & 3) == 0) part[wid * 8 + (lane >> 2)] = a[0];
    }
    __syncthreads();
    if (wid == 0) {
      uint32_t bits = 0;
      if (lane < 24) {
        const int hc2 = lane >> 3, j = lane & 7;
        const float gt = rbf(part[(2 * hc2) * 8 + j] + part[(2 * hc2 + 1) * 8 + j]);
        const float up = rbf(part[(6 + 2 * hc2) * 8 + j] + part[(6 + 2 * hc2 + 1) * 8 + j]);
        const float sg = rbf(gt / (1.f + __expf(-gt)));
        bits = __bfloat16_as_ushort(__float2bfloat16_rn(sg * up));
      }
      const uint32_t nb = __shfl_down_sync(0xffffffffu, bits, 1);
      const uint32_t pw = bits | (nb << 16);
      const uint32_t w1 = __shfl_down_sync(0xffffffffu, pw, 2), w2 = __shfl_down_sync(0xffffffffu, pw, 4), w3 = __shfl_down_sync(0xffffffffu, pw, 6);
      if (lane < 24 && (lane & 7) == 0) st_pub4(&g_act[cta * 3 + (lane >> 3)], enc4(make_uint4(pw, w1, w2, w3)));
    }
  } else if (cta < N1 + N2) {
    const int j2 = cta - N1;
    uint4 rowv = make_uint4(0, 0, 0, 0);
    if (tid < 192) {
      const uint4 v = poll4(&g_act[tid]);
      float4* xp = reinterpret_cast<float4*>(xs + tid * 8);
      xp[0] = make_float4(lo_f(v.x), hi_f(v.x), lo_f(v.y), hi_f(v.y));
      xp[1] = make_float4(lo_f(v.z), hi_f(v.z), lo_f(v.w), hi_f(v.w));
    } else if (tid < 196) {
      const int t = tid - 192;
      rowv = poll4(&g_cand[wcta][t >> 1][j2 * 2 + (t & 1)]);
      reinterpret_cast<uint4*>(part + 256)[t] = rowv;
    }
    __syncthreads();
    const int hc = lane & 1, rs = wid * 16 + (lane >> 1);
    float a[8];
#pragma unroll
    for (int j = 0; j < 8; j++) a[j] = 0.f;
#pragma unroll
    for (int it = 0; it < 8; it++) {
      const int r = rs + 192 * it;
      const uint4 wv = sm.w[r * 2 + hc];
      const float x = xs[r];
      a[0] = fmaf(x, lo_f(wv.x), a[0]); a[1] = fmaf(x, hi_f(wv.x), a[1]);
      a[2] = fmaf(x, lo_f(wv.y), a[2]); a[3] = fmaf(x, hi_f(wv.y), a[3]);
      a[4] = fmaf(x, lo_f(wv.z), a[4]); a[5] = fmaf(x, hi_f(wv.z), a[5]);
      a[6] = fmaf(x, lo_f(wv.w), a[6]); a[7] = fmaf(x, hi_f(wv.w), a[7]);
    }
    {
      const bool up = lane & 16;
#pragma unroll
      for (int j = 0; j < 4; j++) {
        const float send = up ? a[j] : a[j + 4], keep = up ? a[j + 4] : a[j];
        a[j] = keep + __shfl_xor_sync(0xffffffffu, send, 16);
      }
      const bool up2 = lane & 8;
#pragma unroll
      for (int j = 0; j < 2; j++) {
        const float send = up2 ? a[j] : a[j + 2], keep = up2 ? a[j + 2] : a[j];
        a[j] = keep + __shfl_xor_sync(0xffffffffu, send, 8);
      }
      const bool up3 = lane & 4;
      const float send = up3 ? a[0] : a[1], keep = up3 ? a[1] : a[0];
      a[0] = keep + __shfl_xor_sync(0xffffffffu, send, 4);
      a[0] += __shfl_xor_sync(0xffffffffu, a[0], 2);
      if ((lane & 2) == 0) part[wid * 16 + hc * 8 + (lane >> 2)] = a[0];
    }
    __syncthreads();
    if (tid < 16) {
      float y = 0.f;
#pragma unroll
      for (int i = 0; i < 12; i++) y += part[i * 16 + tid];
      const uint32_t ord = win >> 16;
      const uint32_t rb = (ord & 0x8000u) ? (ord ^ 0x8000u) : (ord ^ 0xFFFFu);
      const float r = __uint_as_float(rb << 16);
      const float sg = rbf(1.f / (1.f + __expf(-r)));
      const float yy = rbf(rbf(y) * sg);
      const unsigned short* rv = reinterpret_cast<const unsigned short*>(part + 256);
      const float hn = __uint_as_float((uint32_t)rv[tid] << 16), h = __uint_as_float((uint32_t)rv[16 + tid] << 16);
      gout[(size_t)wrow * D_ + j2 * 16 + tid] = __float2bfloat16_rn(h + rbf(hn + yy));
    }
  }
  STAMP(8);
}

}

typedef CUresult (*EncodeFn)(CUtensorMap*, CUtensorMapDataType, cuuint32_t, void*, const cuuint64_t*, const cuuint64_t*,
                             const cuuint32_t*, const cuuint32_t*, CUtensorMapInterleave, CUtensorMapSwizzle,
                             CUtensorMapL2promotion, CUtensorMapFloatOOBfill);

extern "C" void kernel_launch(void* const* d_in, const int* in_sizes, int n_in, void* d_out, int out_size) {
  (void)in_sizes; (void)n_in; (void)out_size;
  static EncodeFn encode = nullptr;
  static CUtensorMap tmg, tmu, tmd;
  static void* cached[3] = {nullptr, nullptr, nullptr};
  if (!encode) {
    cudaFuncSetAttribute(fused_kernel, cudaFuncAttributeMaxDynamicSharedMemorySize, (int)sizeof(Smem));
    void* fn = nullptr;
    cudaDriverEntryPointQueryResult qr;
    cudaGetDriverEntryPoint("cuTensorMapEncodeTiled", &fn, cudaEnableDefault, &qr);
    encode = (EncodeFn)fn;
  }
  if (cached[0] != d_in[8] || cached[1] != d_in[9] || cached[2] != d_in[10]) {
    const cuuint32_t es[2] = {1, 1};
    {
      const cuuint64_t dims[2] = {F_, D_}, strides[1] = {F_ * 2};
      const cuuint32_t box[2] = {24, 160};
      encode(&tmg, CU_TENSOR_MAP_DATA_TYPE_BFLOAT16, 2, d_in[8], dims, strides, box, es, CU_TENSOR_MAP_INTERLEAVE_NONE,
             CU_TENSOR_MAP_SWIZZLE_NONE, CU_TENSOR_MAP_L2_PROMOTION_NONE, CU_TENSOR_MAP_FLOAT_OOB_FILL_NONE);
      encode(&tmu, CU_TENSOR_MAP_DATA_TYPE_BFLOAT16, 2, d_in[9], dims, strides, box, es, CU_TENSOR_MAP_INTERLEAVE_NONE,
             CU_TENSOR_MAP_SWIZZLE_NONE, CU_TENSOR_MAP_L2_PROMOTION_NONE, CU_TENSOR_MAP_FLOAT_OOB_FILL_NONE);
    }
    {
      const cuuint64_t dims[2] = {D_, F_}, strides[1] = {D_ * 2};
      const cuuint32_t box[2] = {16, 256};
      encode(&tmd, CU_TENSOR_MAP_DATA_TYPE_BFLOAT16, 2, d_in[10], dims, strides, box, es, CU_TENSOR_MAP_INTERLEAVE_NONE,
             CU_TENSOR_MAP_SWIZZLE_NONE, CU_TENSOR_MAP_L2_PROMOTION_NONE, CU_TENSOR_MAP_FLOAT_OOB_FILL_NONE);
    }
    cached[0] = d_in[8]; cached[1] = d_in[9]; cached[2] = d_in[10];
  }
  fused_kernel<<<NCTA, NTHR, sizeof(Smem), cudaStreamPerThread>>>(
      tmg, tmu, tmd, (const bf16*)d_in[0], (const bf16*)d_in[1], (const bf16*)d_in[2], (const bf16*)d_in[3],
      (const bf16*)d_in[4], (const bf16*)d_in[5], (const bf16*)d_in[7], (bf16*)d_out);
}
```

```cpp
#include <cuda_runtime.h>
#include <cuda_bf16.h>
#include <cuda.h>
#include <stdint.h>

namespace {

typedef __nv_bfloat16 bf16;
typedef __nv_bfloat162 bf162;

constexpr int S_ = 2048, D_ = 640, F_ = 1536;
constexpr int NCTA = 128, CPC = 5, NTHR = 384;
constexpr int UPAD = 136, USTR = 2192;
constexpr int TABW = 1040;
constexpr int ZPB = 132;
constexpr int QSTR = 648;
constexpr int N1 = 64;
constexpr int N2 = 40;
constexpr int SPIN_LIMIT = 1 << 19;
#define POLL_NS 100
#define H_DELAY_NS 0

struct __align__(128) Smem {
  uint32_t tabA[3][2][TABW];
  uint32_t extra[1024];
  uint32_t tabB[2][2][TABW];
  bf16 u[CPC][USTR];
  float z[2][4][ZPB * 16];
  bf16 q[16][QSTR];
  alignas(128) uint4 w[3840];
  uint4 wr[80];
  float2 st[16][5];
  float rp[16][5];
  unsigned long long mbar;
  unsigned long long mbarw;
  uint32_t target;
  uint32_t target2;
  uint32_t best;
  uint32_t win;
};

__device__ uint4 g_kv[D_ * S_ / 8];
__device__ uint4 g_y2[D_ * S_ / 8];
__device__ uint32_t g_keys[NCTA];
__device__ uint4 g_cand[NCTA][2][80];
__device__ uint4 g_act[F_ / 8];
__device__ unsigned int g_ctr;
__device__ unsigned int g_ctr2;
#define STAMP(i)

__device__ __forceinline__ uint32_t smem_u32(const void* p) { return (uint32_t)__cvta_generic_to_shared(p); }
__device__ __forceinline__ void wg_fence() { asm volatile("wgmma.fence.sync.aligned;" ::: "memory"); }
__device__ __forceinline__ void wg_commit() { asm volatile("wgmma.commit_group.sync.aligned;" ::: "memory"); }
template <int N> __device__ __forceinline__ void wg_wait() { asm volatile("wgmma.wait_group.sync.aligned %0;" ::"n"(N) : "memory"); }
__device__ __forceinline__ void bar_sync(int id, int n) { asm volatile("bar.sync %0, %1;" ::"r"(id), "r"(n) : "memory"); }
__device__ __forceinline__ void bar_arrive(int id, int n) { asm volatile("bar.arrive %0, %1;" ::"r"(id), "r"(n) : "memory"); }
__device__ __forceinline__ bf162 u2b(uint32_t u) { return *reinterpret_cast<bf162*>(&u); }
__device__ __forceinline__ uint32_t b2u(bf162 b) { return *reinterpret_cast<uint32_t*>(&b); }
__device__ __forceinline__ float lo_f(uint32_t u) { return __uint_as_float(u << 16); }
__device__ __forceinline__ float hi_f(uint32_t u) { return __uint_as_float(u & 0xFFFF0000u); }
__device__ __forceinline__ float rbf(float x) { return __bfloat162float(__float2bfloat16_rn(x)); }
__device__ __forceinline__ uint32_t pack2(float a, float b) { return b2u(__floats2bfloat162_rn(a, b)); }
__device__ __forceinline__ uint32_t enc(uint32_t w) { return max(~w, 1u); }
__device__ __forceinline__ uint4 enc4(uint4 v) { return make_uint4(enc(v.x), enc(v.y), enc(v.z), enc(v.w)); }
__device__ __forceinline__ uint4 ld_poll4(const uint4* p) {
  uint4 v;
  asm volatile("ld.relaxed.gpu.global.v4.u32 {%0,%1,%2,%3}, [%4];" : "=r"(v.x), "=r"(v.y), "=r"(v.z), "=r"(v.w) : "l"(p) : "memory");
  return v;
}
__device__ __forceinline__ bool ready4(uint4 v) { return v.x != 0u && v.y != 0u && v.z != 0u && v.w != 0u; }
__device__ __forceinline__ uint4 poll4(const uint4* p) {
  uint4 v = ld_poll4(p);
  int it = 0;
  while (!ready4(v) && ++it < SPIN_LIMIT) v = ld_poll4(p);
  return make_uint4(~v.x, ~v.y, ~v.z, ~v.w);
}
__device__ __forceinline__ void st_pub4(uint4* p, uint4 v) {
  asm volatile("st.relaxed.gpu.global.v4.u32 [%0], {%1,%2,%3,%4};" ::"l"(p), "r"(v.x), "r"(v.y), "r"(v.z), "r"(v.w) : "memory");
}
__device__ __forceinline__ void st_pub2(uint2* p, uint32_t a, uint32_t b) {
  asm volatile("st.relaxed.gpu.global.v2.u32 [%0], {%1,%2};" ::"l"(p), "r"(a), "r"(b) : "memory");
}
__device__ __forceinline__ void mma_bf16(float (&c)[4], uint32_t a0, uint32_t a2, uint32_t b0, uint32_t b1) {
  asm volatile("mma.sync.aligned.m16n8k16.row.col.f32.bf16.bf16.f32 {%0,%1,%2,%3}, {%4,%5,%6,%5}, {%7,%8}, {%0,%1,%2,%3};"
               : "+f"(c[0]), "+f"(c[1]), "+f"(c[2]), "+f"(c[3]) : "r"(a0), "r"(0u), "r"(a2), "r"(b0), "r"(b1));
}
__device__ __forceinline__ float fdivr(float a, float d, float r) {
  float q = a * r;
  float e = fmaf(-q, d, a);
  return fmaf(e, r, q);
}

template <bool FIRST> __device__ __forceinline__ void wgmma32(float (&d)[16], const uint32_t* a, uint64_t desc) {
  if (FIRST) {
    asm volatile("wgmma.mma_async.sync.aligned.m64n32k16.f32.bf16.bf16 {%0,%1,%2,%3,%4,%5,%6,%7,%8,%9,%10,%11,%12,%13,%14,%15}, {%16,%17,%18,%19}, %20, 0, 1, 1, 0;"
                 : "+f"(d[0]), "+f"(d[1]), "+f"(d[2]), "+f"(d[3]), "+f"(d[4]), "+f"(d[5]), "+f"(d[6]), "+f"(d[7]),
                   "+f"(d[8]), "+f"(d[9]), "+f"(d[10]), "+f"(d[11]), "+f"(d[12]), "+f"(d[13]), "+f"(d[14]), "+f"(d[15])
                 : "r"(a[0]), "r"(a[1]), "r"(a[2]), "r"(a[3]), "l"(desc));
  } else {
    asm volatile("wgmma.mma_async.sync.aligned.m64n32k16.f32.bf16.bf16 {%0,%1,%2,%3,%4,%5,%6,%7,%8,%9,%10,%11,%12,%13,%14,%15}, {%16,%17,%18,%19}, %20, 1, 1, 1, 0;"
                 : "+f"(d[0]), "+f"(d[1]), "+f"(d[2]), "+f"(d[3]), "+f"(d[4]), "+f"(d[5]), "+f"(d[6]), "+f"(d[7]),
                   "+f"(d[8]), "+f"(d[9]), "+f"(d[10]), "+f"(d[11]), "+f"(d[12]), "+f"(d[13]), "+f"(d[14]), "+f"(d[15])
                 : "r"(a[0]), "r"(a[1]), "r"(a[2]), "r"(a[3]), "l"(desc));
  }
}

template <int G> __device__ __forceinline__ void load_a(uint32_t (&a)[8], const uint32_t* tp) {
#pragma unroll
  for (int q = 0; q < 2; q++) {
    const int e = 2 * G + q;
    a[4 * q + 0] = tp[-64 * e];
    a[4 * q + 1] = tp[-64 * e - 32];
    a[4 * q + 2] = tp[-64 * e + 4];
    a[4 * q + 3] = tp[-64 * e - 28];
  }
}
__device__ __forceinline__ void load_a_all(uint32_t (&a)[8][8], const uint32_t* tp) {
  load_a<0>(a[0], tp); load_a<1>(a[1], tp); load_a<2>(a[2], tp); load_a<3>(a[3], tp);
  load_a<4>(a[4], tp); load_a<5>(a[5], tp); load_a<6>(a[6], tp); load_a<7>(a[7], tp);
}
template <int G> __device__ __forceinline__ void issue_g(float (&acc)[8][16], uint32_t (&a)[8], uint64_t desc0) {
  wg_fence();
#pragma unroll
  for (int q = 0; q < 2; q++) {
#pragma unroll
    for (int b = G; b < 8; b++) {
      const int delta = 2 * b - (2 * G + q);
      if (G == 0 && q == 0) wgmma32<true>(acc[b], &a[4 * q], desc0 + (uint64_t)(int64_t)(16 * delta));
      else wgmma32<false>(acc[b], &a[4 * q], desc0 + (uint64_t)(int64_t)(16 * delta));
    }
  }
  wg_commit();
}
template <int B> __device__ __forceinline__ void fence_blk(float (&acc)[8][16]) {
#pragma unroll
  for (int i = 0; i < 16; i++) asm volatile("" : "+f"(acc[B][i])::"memory");
}
__device__ __forceinline__ void fence_a(uint32_t (&a)[8]) {
#pragma unroll
  for (int i = 0; i < 8; i++) asm volatile("" : "+r"(a[i])::"memory");
}
template <int B> __device__ __forceinline__ void sts_blk(float (&acc)[8][16], float* zw, int off_even, int off_odd) {
#pragma unroll
  for (int jj = 0; jj < 4; jj++) {
    const int j = 4 * B + jj;
    float p0 = acc[B][4 * jj + 0], p1 = acc[B][4 * jj + 1];
    if (jj > 0) { p0 += acc[B][4 * (jj - 1) + 2]; p1 += acc[B][4 * (jj - 1) + 3]; }
    else if (B > 0) { p0 += acc[B > 0 ? B - 1 : 0][14]; p1 += acc[B > 0 ? B - 1 : 0][15]; }
    zw[64 * j + off_even] = p0;
    zw[64 * j + off_odd] = p1;
  }
}
__device__ __forceinline__ int tab_off(int c) { return c == 4 ? 0 : (c + 1) * 2 * TABW + (c >= 2 ? 1024 : 0); }
__device__ __forceinline__ int tile_perm(int ch) { return ch ^ (((ch >> 3) & 3) << 1); }

__device__ __forceinline__ void wait_cleared(uint32_t target) {
  uint32_t v;
  int it = 0;
  do {
    asm volatile("ld.acquire.gpu.global.u32 %0, [%1];" : "=r"(v) : "l"(&g_ctr) : "memory");
  } while ((int)(v - target) < 0 && ++it < SPIN_LIMIT);
}

__global__ void __launch_bounds__(NTHR, 1)
fused_kernel(const __grid_constant__ CUtensorMap tmg, const __grid_constant__ CUtensorMap tmu,
             const __grid_constant__ CUtensorMap tmd, const bf16* __restrict__ gq, const bf16* __restrict__ gk, const bf16* __restrict__ gv,
             const bf16* __restrict__ gsk, const bf16* __restrict__ gh, const bf16* __restrict__ gD,
             const bf16* __restrict__ gwr, bf16* __restrict__ gout) {
  extern __shared__ __align__(128) unsigned char smraw[];
  Smem& sm = *reinterpret_cast<Smem*>(smraw);
  const int tid = threadIdx.x;
  const int cta = blockIdx.x;
  const int c0 = cta * CPC;
  const int lane = tid & 31;
  const int wid = tid >> 5;
  STAMP(0);

  {
    const int oc = tid >> 2;
    const int r0 = cta * 16 + (tid & 3) * 4;
    uint4 kk[7], vv[4], sk[4];
    if (tid < 320) {
      const uint4* kp = reinterpret_cast<const uint4*>(gk) + (size_t)r0 * 80 + oc;
      const uint4* vp = reinterpret_cast<const uint4*>(gv) + (size_t)r0 * 80 + oc;
#pragma unroll
      for (int i = 0; i < 7; i++) kk[i] = (i >= 3 || r0 > 0) ? __ldg(kp + (i - 3) * 80) : make_uint4(0, 0, 0, 0);
#pragma unroll
      for (int i = 0; i < 4; i++) vv[i] = __ldg(vp + i * 80);
#pragma unroll
      for (int i = 0; i < 4; i++) sk[i] = __ldg(reinterpret_cast<const uint4*>(gsk) + oc * 4 + i);
    }
    STAMP(9);
    if (tid < 320) {
#pragma unroll
      for (int p = 0; p < 4; p++) {
        const bf162 w0 = u2b(__byte_perm(sk[p].x, sk[p].z, 0x5410)), w1 = u2b(__byte_perm(sk[p].x, sk[p].z, 0x7632));
        const bf162 w2 = u2b(__byte_perm(sk[p].y, sk[p].w, 0x5410)), w3 = u2b(__byte_perm(sk[p].y, sk[p].w, 0x7632));
        uint32_t kv[4];
#pragma unroll
        for (int i = 0; i < 4; i++) {
          const uint32_t k0 = p == 0 ? kk[i].x : p == 1 ? kk[i].y : p == 2 ? kk[i].z : kk[i].w;
          const uint32_t k1 = p == 0 ? kk[i + 1].x : p == 1 ? kk[i + 1].y : p == 2 ? kk[i + 1].z : kk[i + 1].w;
          const uint32_t k2 = p == 0 ? kk[i + 2].x : p == 1 ? kk[i + 2].y : p == 2 ? kk[i + 2].z : kk[i + 2].w;
          const uint32_t k3 = p == 0 ? kk[i + 3].x : p == 1 ? kk[i + 3].y : p == 2 ? kk[i + 3].z : kk[i + 3].w;
          const uint32_t vx = p == 0 ? vv[i].x : p == 1 ? vv[i].y : p == 2 ? vv[i].z : vv[i].w;
          bf162 a = __hmul2_rn(u2b(k0), w3);
          a = __hadd2_rn(a, __hmul2_rn(u2b(k1), w2));
          a = __hadd2_rn(a, __hmul2_rn(u2b(k2), w1));
          a = __hadd2_rn(a, __hmul2_rn(u2b(k3), w0));
          kv[i] = b2u(__hmul2_rn(a, u2b(vx)));
        }
        uint2* dst = reinterpret_cast<uint2*>(g_kv) + (size_t)(oc * 8 + 2 * p) * 512 + (r0 >> 2);
        st_pub2(dst, enc(__byte_perm(kv[0], kv[1], 0x5410)), enc(__byte_perm(kv[2], kv[3], 0x5410)));
        st_pub2(dst + 512, enc(__byte_perm(kv[0], kv[1], 0x7632)), enc(__byte_perm(kv[2], kv[3], 0x7632)));
      }
      STAMP(10);
      if (wid == 0) bar_sync(6, 384); else bar_arrive(6, 384);
      if (tid == 0) {
        const unsigned old = atomicAdd(&g_ctr2, 1u);
        sm.target2 = (old / NCTA + 1u) * NCTA;
      }
    } else {
      const int t0 = tid - 320;
      const uint4 zz = make_uint4(0, 0, 0, 0);
#pragma unroll 4
      for (int i = 0; i < 20; i++) g_y2[cta * 1280 + t0 + 64 * i] = zz;
      (&g_cand[cta][0][0])[t0] = zz;
      (&g_cand[cta][0][0])[64 + t0] = zz;
      if (t0 < 32) (&g_cand[cta][0][0])[128 + t0] = zz;
      else if (t0 < 35) { if (cta < N1) g_act[cta * 3 + (t0 - 32)] = zz; }
      else if (t0 == 35) g_keys[cta] = 0u;
      for (int t = t0; t < CPC * 17; t += 64) *reinterpret_cast<uint4*>(&sm.u[t / 17][(t % 17) * 8]) = zz;
      if (t0 < 40) *reinterpret_cast<uint4*>(&sm.tabA[0][0][0] + tab_off(t0 >> 3) + ((t0 >> 2) & 1) * TABW + 1024 + 4 * (t0 & 3)) = zz;
      *reinterpret_cast<uint4*>(&sm.z[0][t0 >> 4][(t0 & 15) * 4]) = zz;
      *reinterpret_cast<uint4*>(&sm.z[1][t0 >> 4][(t0 & 15) * 4]) = zz;
      if (t0 == 0) {
        asm volatile("mbarrier.init.shared.b64 [%0], 1;" ::"r"(smem_u32(&sm.mbar)) : "memory");
        asm volatile("mbarrier.init.shared.b64 [%0], 1;" ::"r"(smem_u32(&sm.mbarw)) : "memory");
      }
      bar_sync(7, 64);
      bar_sync(6, 384);
      if (t0 == 0) {
        asm volatile("fence.proxy.async.shared::cta;" ::: "memory");
        const uint32_t mb = smem_u32(&sm.mbar);
      asm volatile("mbarrier.arrive.expect_tx.shared.b64 _, [%0], %1;" ::"r"(mb), "r"(17 * D_ * 2) : "memory");
#pragma unroll 1
      for (int r = 0; r < 16; r++)
        asm volatile("cp.async.bulk.shared::cluster.global.mbarrier::complete_tx::bytes [%0], [%1], %2, [%3];" ::"r"(smem_u32(&sm.q[r][0])),
                     "l"(gq + (size_t)(cta * 16 + r) * D_), "r"(D_ * 2), "r"(mb) : "memory");
      asm volatile("cp.async.bulk.shared::cluster.global.mbarrier::complete_tx::bytes [%0], [%1], %2, [%3];" ::"r"(smem_u32(&sm.wr[0])),
                   "l"(gwr), "r"(D_ * 2), "r"(mb) : "memory");
      }
      if (t0 == 32) {
        __threadfence();
        const unsigned old = atomicAdd(&g_ctr, 1u);
        sm.target = (old / NCTA + 1u) * NCTA;
      }
    }
    uint4 hv[4];
    uint32_t hp[4];
#pragma unroll
    for (int i = 0; i < 4; i++) {
      const int t = (NTHR - 1 - tid) + NTHR * i;
      hp[i] = 0;
      if (t < CPC * 256) {
        const bf16* p = gh + (size_t)c0 * S_ + t * 8;
        hv[i] = __ldg(reinterpret_cast<const uint4*>(p));
        if (t & 255) hp[i] = __ldg(reinterpret_cast<const unsigned short*>(p) - 1);
      }
    }
#pragma unroll
    for (int i = 0; i < 4; i++) {
      const int t = (NTHR - 1 - tid) + NTHR * i;
      if (t < CPC * 256) {
        uint32_t* tb = &sm.tabA[0][0][0] + tab_off(t >> 8) + (255 - (t & 255)) * 4;
        uint4 h = hv[i], r1, rr;
        r1.x = __byte_perm(h.w, 0, 0x1032); r1.y = __byte_perm(h.z, 0, 0x1032);
        r1.z = __byte_perm(h.y, 0, 0x1032); r1.w = __byte_perm(h.x, 0, 0x1032);
        rr.x = __byte_perm(h.w, h.z, 0x7610); rr.y = __byte_perm(h.z, h.y, 0x7610);
        rr.z = __byte_perm(h.y, h.x, 0x7610); rr.w = __byte_perm(h.x, hp[i], 0x5410);
        *reinterpret_cast<uint4*>(tb) = rr;
        *reinterpret_cast<uint4*>(tb + TABW) = r1;
      }
    }
    if (tid == 0) {
      const unsigned target = sm.target2;
      uint32_t v;
      int it = 0;
      do {
        asm volatile("ld.relaxed.gpu.global.u32 %0, [%1];" : "=r"(v) : "l"(&g_ctr2) : "memory");
      } while ((int)(v - target) < 0 && ++it < SPIN_LIMIT);
    }
    STAMP(12);
  }
  __syncthreads();
  {
    uint4 v[4];
    uint4* src = g_kv + c0 * 256 + tid;
#pragma unroll
    for (int i = 0; i < 4; i++) if (i < 3 || tid < 128) v[i] = ld_poll4(src + NTHR * i);
#pragma unroll
    for (int i = 0; i < 4; i++) {
      if (i < 3 || tid < 128) {
        int it = 0;
        while (!ready4(v[i]) && ++it < SPIN_LIMIT) { __nanosleep(POLL_NS); v[i] = ld_poll4(src + NTHR * i); }
        const int t = tid + NTHR * i;
        *reinterpret_cast<uint4*>(&sm.u[t >> 8][UPAD + (t & 255) * 8]) = make_uint4(~v[i].x, ~v[i].y, ~v[i].z, ~v[i].w);
        src[NTHR * i] = make_uint4(0, 0, 0, 0);
      }
    }
    STAMP(11);
    asm volatile("fence.proxy.async.shared::cta;" ::: "memory");
    __syncthreads();
  }
  STAMP(1);

  const int wg = __shfl_sync(0xffffffffu, tid >> 7, 0);
  const int wtid = tid & 127;
  uint4* tile = reinterpret_cast<uint4*>(&sm.tabB[0][0][0]);
  bf16* qn_s = reinterpret_cast<bf16*>(&sm.tabA[1][0][0]);
  if (wg < 2) {
    asm volatile("setmaxnreg.inc.sync.aligned.u32 224;");
    const int w = (tid >> 5) & 3, g = lane >> 2, tq = lane & 3;
    float* zw = sm.z[wg][w];
    const int sw = 3 * (((tq + w) >> 1) & 1);
    const int off_even = 16 * (tq + w) + 4 * ((0 + (g >> 2)) ^ sw) + (g & 3);
    const int off_odd = 16 * (tq + w) + 4 * ((2 + (g >> 2)) ^ sw) + (g & 3);
    uint32_t a[8][8];
    const uint32_t* tp0 = &sm.tabA[0][g & 1][1019 - 8 * w - (g >> 1) + tq];
    load_a_all(a, tp0 + tab_off(wg));
    if (wg == 0) bar_arrive(7, 256);
    else {
      {
        const uint32_t mb = smem_u32(&sm.mbar);
        uint32_t ok = 0;
        int it = 0;
        while (!ok && ++it < SPIN_LIMIT)
          asm volatile("{ .reg .pred p; mbarrier.try_wait.parity.shared.b64 p, [%1], 0; selp.u32 %0, 1, 0, p; }" : "=r"(ok) : "r"(mb) : "memory");
        bar_sync(7, 256);
        uint32_t qv[4][10];
        float sv[4];
#pragma unroll
        for (int rr = 0; rr < 4; rr++) {
          const uint32_t* qp = reinterpret_cast<const uint32_t*>(&sm.q[w * 4 + rr][0]);
          float s = 0.f;
#pragma unroll
          for (int i = 0; i < 10; i++) { qv[rr][i] = qp[lane + 32 * i]; s += lo_f(qv[rr][i]) + hi_f(qv[rr][i]); }
          sv[rr] = s;
        }
#pragma unroll
        for (int o = 16; o > 0; o >>= 1)
#pragma unroll
          for (int rr = 0; rr < 4; rr++) sv[rr] += __shfl_xor_sync(0xffffffffu, sv[rr], o);
        float m2[4];
#pragma unroll
        for (int rr = 0; rr < 4; rr++) {
          sv[rr] *= (1.f / D_);
          float t = 0.f;
#pragma unroll
          for (int i = 0; i < 10; i++) { const float x = lo_f(qv[rr][i]) - sv[rr], y = hi_f(qv[rr][i]) - sv[rr]; t = fmaf(x, x, fmaf(y, y, t)); }
          m2[rr] = t;
        }
#pragma unroll
        for (int o = 16; o > 0; o >>= 1)
#pragma unroll
          for (int rr = 0; rr < 4; rr++) m2[rr] += __shfl_xor_sync(0xffffffffu, m2[rr], o);
#pragma unroll
        for (int rr = 0; rr < 4; rr++) {
          const float qd = rbf(sqrtf(rbf(rbf(m2[rr] * (1.f / D_)) + 1e-5f)));
          const float qr = 1.f / qd;
          const bf162 qm2 = __float2bfloat162_rn(sv[rr]);
          uint32_t* np = reinterpret_cast<uint32_t*>(qn_s + (w * 4 + rr) * QSTR);
#pragma unroll
          for (int i = 0; i < 10; i++) {
            const uint32_t d = b2u(__hsub2_rn(u2b(qv[rr][i]), qm2));
            np[lane + 32 * i] = pack2(fdivr(lo_f(d), qd, qr), fdivr(hi_f(d), qd, qr));
          }
        }
      }
    }
    float acc[8][16];
#pragma unroll
    for (int b = 0; b < 8; b++)
#pragma unroll
      for (int i = 0; i < 16; i++) acc[b][i] = 0.f;
#pragma unroll 1
    for (int c = wg; c < CPC; c += 2) {
      const uint64_t desc = (uint64_t)((smem_u32(&sm.u[c][UPAD - 8]) & 0x3FFFF) >> 4) | ((uint64_t)1 << 16) | ((uint64_t)8 << 32);
      if (c > 0) bar_sync(1 + wg, 256);
      issue_g<0>(acc, a[0], desc);
      issue_g<1>(acc, a[1], desc);
      issue_g<2>(acc, a[2], desc);
      issue_g<3>(acc, a[3], desc);
      issue_g<4>(acc, a[4], desc);
      issue_g<5>(acc, a[5], desc);
      if (c + 1 < CPC) bar_arrive(1 + (wg ^ 1), 256);
      issue_g<6>(acc, a[6], desc);
      issue_g<7>(acc, a[7], desc);
      if (c >= 2) bar_sync(5 + wg, 256);
      wg_wait<4>();
      fence_blk<0>(acc); fence_blk<1>(acc); fence_blk<2>(acc); fence_blk<3>(acc);
      sts_blk<0>(acc, zw, off_even, off_odd);
      sts_blk<1>(acc, zw, off_even, off_odd);
      sts_blk<2>(acc, zw, off_even, off_odd);
      sts_blk<3>(acc, zw, off_even, off_odd);
      wg_wait<0>();
      fence_blk<4>(acc); fence_blk<5>(acc); fence_blk<6>(acc); fence_blk<7>(acc);
#pragma unroll
      for (int i = 0; i < 8; i++) fence_a(a[i]);
      sts_blk<4>(acc, zw, off_even, off_odd);
      sts_blk<5>(acc, zw, off_even, off_odd);
      sts_blk<6>(acc, zw, off_even, off_odd);
      sts_blk<7>(acc, zw, off_even, off_odd);
      bar_arrive(3 + wg, 256);
      if (c + 2 < CPC) load_a_all(a, tp0 + tab_off(c + 2));
    }
    STAMP(2 + wg);
    asm volatile("setmaxnreg.dec.sync.aligned.u32 168;");
    if (wg == 1) {
#pragma unroll 1
      for (int cc = 0; cc < 4; cc++) {
        const int ch = wtid * 5 + cc;
        const uint4* src = g_y2 + cta * 1280 + ch * 2;
        uint4 v0 = ld_poll4(src), v1 = ld_poll4(src + 1);
        int it = 0;
        while (!ready4(v0) && ++it < SPIN_LIMIT) v0 = ld_poll4(src);
        while (!ready4(v1) && ++it < SPIN_LIMIT) v1 = ld_poll4(src + 1);
        const int pc = tile_perm(ch);
        tile[pc] = make_uint4(~v0.x, ~v0.y, ~v0.z, ~v0.w);
        tile[640 + pc] = make_uint4(~v1.x, ~v1.y, ~v1.z, ~v1.w);
      }
    }
  } else {
    asm volatile("setmaxnreg.dec.sync.aligned.u32 56;");
    if (wtid == 32) {
      const uint32_t mw = smem_u32(&sm.mbarw);
      if (cta < N1) {
        asm volatile("mbarrier.arrive.expect_tx.shared.b64 _, [%0], %1;" ::"r"(mw), "r"(3840 * 16) : "memory");
#pragma unroll 1
        for (int i = 0; i < 4; i++) {
          asm volatile("cp.async.bulk.tensor.2d.shared::cluster.global.mbarrier::complete_tx::bytes [%0], [%1, {%3, %4}], [%2];" ::"r"(smem_u32(&sm.w[i * 480])),
                       "l"(&tmg), "r"(mw), "r"(cta * 24), "r"(i * 160) : "memory");
          asm volatile("cp.async.bulk.tensor.2d.shared::cluster.global.mbarrier::complete_tx::bytes [%0], [%1, {%3, %4}], [%2];" ::"r"(smem_u32(&sm.w[1920 + i * 480])),
                       "l"(&tmu), "r"(mw), "r"(cta * 24), "r"(i * 160) : "memory");
        }
      } else if (cta < N1 + N2) {
        asm volatile("mbarrier.arrive.expect_tx.shared.b64 _, [%0], %1;" ::"r"(mw), "r"(3072 * 16) : "memory");
#pragma unroll 1
        for (int i = 0; i < 6; i++)
          asm volatile("cp.async.bulk.tensor.2d.shared::cluster.global.mbarrier::complete_tx::bytes [%0], [%1, {%3, %4}], [%2];" ::"r"(smem_u32(&sm.w[i * 512])),
                       "l"(&tmd), "r"(mw), "r"((cta - N1) * 16), "r"(i * 256) : "memory");
      }
    }
    if (wtid == 0) wait_cleared(sm.target);
    const int rpb = wtid >> 1, re2 = wtid & 1;
    const int rsw = 3 * ((rpb >> 1) & 1);
    const int roff0 = 16 * rpb + 4 * ((2 * re2 + 0) ^ rsw);
    const int roff1 = 16 * rpb + 4 * ((2 * re2 + 1) ^ rsw);
    const uint32_t dvl = reinterpret_cast<const unsigned short*>(gD)[c0 + (lane < CPC ? lane : 0)];
#pragma unroll 1
    for (int c = 0; c < CPC; c++) {
      const int zg = c & 1;
      const uint32_t dvc = __shfl_sync(0xffffffffu, dvl, c);
      const bf162 d2 = u2b(dvc | (dvc << 16));
      bar_sync(3 + zg, 256);
#pragma unroll
      for (int half = 0; half < 2; half++) {
        const float* zb = sm.z[zg][0] + half * 1024;
        float4 x[4][2];
#pragma unroll
        for (int ww = 0; ww < 4; ww++) {
          x[ww][0] = *reinterpret_cast<const float4*>(zb + ww * ZPB * 16 + roff0);
          x[ww][1] = *reinterpret_cast<const float4*>(zb + ww * ZPB * 16 + roff1);
        }
        const int sidx = half * 1024 + wtid * 8;
        const uint4 kvv = *reinterpret_cast<const uint4*>(&sm.u[c][UPAD + sidx]);
        if (half == 1 && c + 2 < CPC) bar_arrive(5 + zg, 256);
        uint4 o;
        o.x = pack2((x[0][0].x + x[1][0].x) + (x[2][0].x + x[3][0].x), (x[0][0].y + x[1][0].y) + (x[2][0].y + x[3][0].y));
        o.y = pack2((x[0][0].z + x[1][0].z) + (x[2][0].z + x[3][0].z), (x[0][0].w + x[1][0].w) + (x[2][0].w + x[3][0].w));
        o.z = pack2((x[0][1].x + x[1][1].x) + (x[2][1].x + x[3][1].x), (x[0][1].y + x[1][1].y) + (x[2][1].y + x[3][1].y));
        o.w = pack2((x[0][1].z + x[1][1].z) + (x[2][1].z + x[3][1].z), (x[0][1].w + x[1][1].w) + (x[2][1].w + x[3][1].w));
        o.x = b2u(__hadd2_rn(u2b(o.x), __hmul2_rn(u2b(kvv.x), d2)));
        o.y = b2u(__hadd2_rn(u2b(o.y), __hmul2_rn(u2b(kvv.y), d2)));
        o.z = b2u(__hadd2_rn(u2b(o.z), __hmul2_rn(u2b(kvv.z), d2)));
        o.w = b2u(__hadd2_rn(u2b(o.w), __hmul2_rn(u2b(kvv.w), d2)));
        st_pub4(g_y2 + ((64 * half + rpb) * 640 + c0 + c) * 2 + re2, enc4(o));
      }
    }
    STAMP(4);
    asm volatile("setmaxnreg.inc.sync.aligned.u32 168;");
  }

  if (tid < 128 || tid >= 256) {
    const int t = tid < 128 ? tid : tid - 128;
    const int ch = (t >> 1) * 5 + 4, hh = t & 1;
    const uint4 v = poll4(g_y2 + cta * 1280 + ch * 2 + hh);
    tile[hh * 640 + tile_perm(ch)] = v;
  }
  __syncthreads();
  STAMP(5);

  const int g = lane >> 2, tq = lane & 3;
  const int hh = wid & 1, gqi = wid >> 1;
  const int row = hh * 8 + g;
  uint32_t hreg[16], hnreg[16];
  if (wid < 10) {
    float cs[4] = {0.f, 0.f, 0.f, 0.f};
#pragma unroll
    for (int k = 0; k < 4; k++) {
      const int base = 32 * (4 * gqi + k);
      const int lch = base + 8 * ((lane & 7) >> 1) + 2 * (lane >> 3) + (lane & 1);
      uint32_t y[4];
      asm volatile("ldmatrix.sync.aligned.m8n8.x4.trans.shared.b16 {%0,%1,%2,%3}, [%4];"
                   : "=r"(y[0]), "=r"(y[1]), "=r"(y[2]), "=r"(y[3]) : "r"(smem_u32(&tile[hh * 640 + tile_perm(lch)])) : "memory");
      const uint4 qv4 = *reinterpret_cast<const uint4*>(&sm.q[row][base + 8 * tq]);
      const uint4 qn4 = *reinterpret_cast<const uint4*>(qn_s + row * QSTR + base + 8 * tq);
      hreg[4 * k + 0] = b2u(__hadd2_rn(u2b(qv4.x), __hmul2_rn(u2b(qn4.x), u2b(y[0]))));
      hreg[4 * k + 1] = b2u(__hadd2_rn(u2b(qv4.y), __hmul2_rn(u2b(qn4.y), u2b(y[1]))));
      hreg[4 * k + 2] = b2u(__hadd2_rn(u2b(qv4.z), __hmul2_rn(u2b(qn4.z), u2b(y[2]))));
      hreg[4 * k + 3] = b2u(__hadd2_rn(u2b(qv4.w), __hmul2_rn(u2b(qn4.w), u2b(y[3]))));
      mma_bf16(cs, hreg[4 * k + 0], hreg[4 * k + 1], 0x3F803F80u, 0x3F803F80u);
      mma_bf16(cs, hreg[4 * k + 2], hreg[4 * k + 3], 0x3F803F80u, 0x3F803F80u);
    }
    const float mean = cs[0] * (1.f / 128.f);
    float m2a = 0.f, m2b = 0.f;
#pragma unroll
    for (int i = 0; i < 16; i++) {
      const float a = lo_f(hreg[i]) - mean, b = hi_f(hreg[i]) - mean;
      m2a = fmaf(a, a, m2a); m2b = fmaf(b, b, m2b);
    }
    float m2 = m2a + m2b;
    m2 += __shfl_xor_sync(0xffffffffu, m2, 1);
    m2 += __shfl_xor_sync(0xffffffffu, m2, 2);
    if (tq == 0) sm.st[row][gqi] = make_float2(mean, m2);
  }
  STAMP(13);
  __syncthreads();
  if (wid < 10) {
    float mean = 0.f, m2 = 0.f;
    float2 p[5];
#pragma unroll
    for (int i = 0; i < 5; i++) { p[i] = sm.st[row][i]; mean += p[i].x; }
    mean *= 0.2f;
#pragma unroll
    for (int i = 0; i < 5; i++) { const float dl = p[i].x - mean; m2 += p[i].y + 128.f * dl * dl; }
    const float hd = rbf(sqrtf(rbf(rbf(m2 * (1.f / D_)) + 1e-5f)));
    const float hr = 1.f / hd;
    const bf162 hm2 = __float2bfloat162_rn(mean);
    float cr[4] = {0.f, 0.f, 0.f, 0.f};
#pragma unroll
    for (int k = 0; k < 4; k++) {
      const uint4 w4 = sm.wr[4 * (4 * gqi + k) + tq];
#pragma unroll
      for (int i = 0; i < 4; i++) {
        const uint32_t d = b2u(__hsub2_rn(u2b(hreg[4 * k + i]), hm2));
        hnreg[4 * k + i] = pack2(fdivr(lo_f(d), hd, hr), fdivr(hi_f(d), hd, hr));
      }
      mma_bf16(cr, hnreg[4 * k + 0], hnreg[4 * k + 1], w4.x, w4.y);
      mma_bf16(cr, hnreg[4 * k + 2], hnreg[4 * k + 3], w4.z, w4.w);
    }
    if (tq == 0) sm.rp[row][gqi] = cr[0];
  }
  STAMP(14);
  __syncthreads();
  uint32_t best;
  {
    const int rr = lane & 15;
    const float r = ((sm.rp[rr][0] + sm.rp[rr][1]) + (sm.rp[rr][2] + sm.rp[rr][3])) + sm.rp[rr][4];
    const uint32_t bits = __bfloat16_as_ushort(__float2bfloat16_rn(r));
    const uint32_t ord = (bits & 0x8000u) ? (bits ^ 0xFFFFu) : (bits ^ 0x8000u);
    const uint32_t key = (ord << 16) | 0x8000u | (uint32_t)(2047 - (cta * 16 + rr));
    best = __reduce_max_sync(0xffffffffu, key);
  }
  if (tid == 352) asm volatile("st.relaxed.gpu.global.u32 [%0], %1;" ::"l"(&g_keys[cta]), "r"(best) : "memory");
  STAMP(15);
  const int brow = (2047 - (int)(best & 0x7FFu)) - cta * 16;
  uint4 outv[4];
  if (wid < 10) {
#pragma unroll
    for (int k = 0; k < 4; k++) {
      outv[k].x = b2u(__hadd2_rn(u2b(hreg[4 * k + 0]), u2b(hnreg[4 * k + 0])));
      outv[k].y = b2u(__hadd2_rn(u2b(hreg[4 * k + 1]), u2b(hnreg[4 * k + 1])));
      outv[k].z = b2u(__hadd2_rn(u2b(hreg[4 * k + 2]), u2b(hnreg[4 * k + 2])));
      outv[k].w = b2u(__hadd2_rn(u2b(hreg[4 * k + 3]), u2b(hnreg[4 * k + 3])));
      const int chunk = 4 * (4 * gqi + k) + tq;
      if (row == brow) {
        st_pub4(&g_cand[cta][0][chunk], enc4(make_uint4(hnreg[4 * k], hnreg[4 * k + 1], hnreg[4 * k + 2], hnreg[4 * k + 3])));
        st_pub4(&g_cand[cta][1][chunk], enc4(make_uint4(hreg[4 * k], hreg[4 * k + 1], hreg[4 * k + 2], hreg[4 * k + 3])));
      } else {
        *reinterpret_cast<uint4*>(gout + (size_t)(cta * 16 + row) * D_ + chunk * 8) = outv[k];
      }
    }
  }
  STAMP(6);
  if (wid == 11) {
    const uint4* kp = reinterpret_cast<const uint4*>(g_keys) + lane;
    uint4 v = ld_poll4(kp);
    int it = 0;
    while (!ready4(v) && ++it < SPIN_LIMIT) v = ld_poll4(kp);
    const uint32_t m = max(max(v.x, v.y), max(v.z, v.w));
    const uint32_t wk = __reduce_max_sync(0xffffffffu, m);
    if (lane == 0) sm.win = wk;
  }
  __syncthreads();
  const uint32_t win = sm.win;
  const int wrow = 2047 - (int)(win & 0x7FFu);
  const int wcta = wrow >> 4;
  if (wid < 10 && row == brow && wcta != cta) {
#pragma unroll
    for (int k = 0; k < 4; k++)
      *reinterpret_cast<uint4*>(gout + (size_t)(cta * 16 + row) * D_ + (4 * (4 * gqi + k) + tq) * 8) = outv[k];
  }
  STAMP(7);
  if (cta < N1 + N2) {
    const uint32_t mw = smem_u32(&sm.mbarw);
    uint32_t ok = 0;
    int it = 0;
    while (!ok && ++it < SPIN_LIMIT)
      asm volatile("{ .reg .pred p; mbarrier.try_wait.parity.shared.b64 p, [%1], 0; selp.u32 %0, 1, 0, p; }" : "=r"(ok) : "r"(mw) : "memory");
  }
  float* xs = &sm.z[0][0][0];
  float* part = xs + 2048;
  if (cta < N1) {
    if (tid < 80) {
      const uint4 v = poll4(&g_cand[wcta][0][tid]);
      float4* xp = reinterpret_cast<float4*>(xs + tid * 8);
      xp[0] = make_float4(lo_f(v.x), hi_f(v.x), lo_f(v.y), hi_f(v.y));
      xp[1] = make_float4(lo_f(v.z), hi_f(v.z), lo_f(v.w), hi_f(v.w));
    }
    __syncthreads();
    const int m = wid / 6, hc = (wid % 6) >> 1, rs = (wid & 1) * 32 + lane;
    float a[8];
#pragma unroll
    for (int j = 0; j < 8; j++) a[j] = 0.f;
#pragma unroll
    for (int it = 0; it < 10; it++) {
      const int r = rs + 64 * it;
      const uint4 wv = sm.w[m * 1920 + r * 3 + hc];
      const float x = xs[r];
      a[0] = fmaf(x, lo_f(wv.x), a[0]); a[1] = fmaf(x, hi_f(wv.x), a[1]);
      a[2] = fmaf(x, lo_f(wv.y), a[2]); a[3] = fmaf(x, hi_f(wv.y), a[3]);
      a[4] = fmaf(x, lo_f(wv.z), a[4]); a[5] = fmaf(x, hi_f(wv.z), a[5]);
      a[6] = fmaf(x, lo_f(wv.w), a[6]); a[7] = fmaf(x, hi_f(wv.w), a[7]);
    }
    {
      const bool up = lane & 16;
#pragma unroll
      for (int j = 0; j < 4; j++) {
        const float send = up ? a[j] : a[j + 4], keep = up ? a[j + 4] : a[j];
        a[j] = keep + __shfl_xor_sync(0xffffffffu, send, 16);
      }
      const bool up2 = lane & 8;
#pragma unroll
      for (int j = 0; j < 2; j++) {
        const float send = up2 ? a[j] : a[j + 2], keep = up2 ? a[j + 2] : a[j];
        a[j] = keep + __shfl_xor_sync(0xffffffffu, send, 8);
      }
      const bool up3 = lane & 4;
      const float send = up3 ? a[0] : a[1], keep = up3 ? a[1] : a[0];
      a[0] = keep + __shfl_xor_sync(0xffffffffu, send, 4);
      a[0] += __shfl_xor_sync(0xffffffffu, a[0], 2);
      a[0] += __shfl_xor_sync(0xffffffffu, a[0], 1);
      if ((lane & 3) == 0) part[wid * 8 + (lane >> 2)] = a[0];
    }
    __syncthreads();
    if (wid == 0) {
      uint32_t bits = 0;
      if (lane < 24) {
        const int hc2 = lane >> 3, j = lane & 7;
        const float gt = rbf(part[(2 * hc2) * 8 + j] + part[(2 * hc2 + 1) * 8 + j]);
        const float up = rbf(part[(6 + 2 * hc2) * 8 + j] + part[(6 + 2 * hc2 + 1) * 8 + j]);
        const float sg = rbf(gt / (1.f + __expf(-gt)));
        bits = __bfloat16_as_ushort(__float2bfloat16_rn(sg * up));
      }
      const uint32_t nb = __shfl_down_sync(0xffffffffu, bits, 1);
      const uint32_t pw = bits | (nb << 16);
      const uint32_t w1 = __shfl_down_sync(0xffffffffu, pw, 2), w2 = __shfl_down_sync(0xffffffffu, pw, 4), w3 = __shfl_down_sync(0xffffffffu, pw, 6);
      if (lane < 24 && (lane & 7) == 0) st_pub4(&g_act[cta * 3 + (lane >> 3)], enc4(make_uint4(pw, w1, w2, w3)));
    }
  } else if (cta < N1 + N2) {
    const int j2 = cta - N1;
    uint4 rowv = make_uint4(0, 0, 0, 0);
    if (tid < 192) {
      const uint4 v = poll4(&g_act[tid]);
      float4* xp = reinterpret_cast<float4*>(xs + tid * 8);
      xp[0] = make_float4(lo_f(v.x), hi_f(v.x), lo_f(v.y), hi_f(v.y));
      xp[1] = make_float4(lo_f(v.z), hi_f(v.z), lo_f(v.w), hi_f(v.w));
    } else if (tid < 196) {
      const int t = tid - 192;
      rowv = poll4(&g_cand[wcta][t >> 1][j2 * 2 + (t & 1)]);
      reinterpret_cast<uint4*>(part + 256)[t] = rowv;
    }
    __syncthreads();
    const int hc = lane & 1, rs = wid * 16 + (lane >> 1);
    float a[8];
#pragma unroll
    for (int j = 0; j < 8; j++) a[j] = 0.f;
#pragma unroll
    for (int it = 0; it < 8; it++) {
      const int r = rs + 192 * it;
      const uint4 wv = sm.w[r * 2 + hc];
      const float x = xs[r];
      a[0] = fmaf(x, lo_f(wv.x), a[0]); a[1] = fmaf(x, hi_f(wv.x), a[1]);
      a[2] = fmaf(x, lo_f(wv.y), a[2]); a[3] = fmaf(x, hi_f(wv.y), a[3]);
      a[4] = fmaf(x, lo_f(wv.z), a[4]); a[5] = fmaf(x, hi_f(wv.z), a[5]);
      a[6] = fmaf(x, lo_f(wv.w), a[6]); a[7] = fmaf(x, hi_f(wv.w), a[7]);
    }
    {
      const bool up = lane & 16;
#pragma unroll
      for (int j = 0; j < 4; j++) {
        const float send = up ? a[j] : a[j + 4], keep = up ? a[j + 4] : a[j];
        a[j] = keep + __shfl_xor_sync(0xffffffffu, send, 16);
      }
      const bool up2 = lane & 8;
#pragma unroll
      for (int j = 0; j < 2; j++) {
        const float send = up2 ? a[j] : a[j + 2], keep = up2 ? a[j + 2] : a[j];
        a[j] = keep + __shfl_xor_sync(0xffffffffu, send, 8);
      }
      const bool up3 = lane & 4;
      const float send = up3 ? a[0] : a[1], keep = up3 ? a[1] : a[0];
      a[0] = keep + __shfl_xor_sync(0xffffffffu, send, 4);
      a[0] += __shfl_xor_sync(0xffffffffu, a[0], 2);
      if ((lane & 2) == 0) part[wid * 16 + hc * 8 + (lane >> 2)] = a[0];
    }
    __syncthreads();
    if (tid < 16) {
      float y = 0.f;
#pragma unroll
      for (int i = 0; i < 12; i++) y += part[i * 16 + tid];
      const uint32_t ord = win >> 16;
      const uint32_t rb = (ord & 0x8000u) ? (ord ^ 0x8000u) : (ord ^ 0xFFFFu);
      const float r = __uint_as_float(rb << 16);
      const float sg = rbf(1.f / (1.f + __expf(-r)));
      const float yy = rbf(rbf(y) * sg);
      const unsigned short* rv = reinterpret_cast<const unsigned short*>(part + 256);
      const float hn = __uint_as_float((uint32_t)rv[tid] << 16), h = __uint_as_float((uint32_t)rv[16 + tid] << 16);
      gout[(size_t)wrow * D_ + j2 * 16 + tid] = __float2bfloat16_rn(h + rbf(hn + yy));
    }
  }
  STAMP(8);
}

}

typedef CUresult (*EncodeFn)(CUtensorMap*, CUtensorMapDataType, cuuint32_t, void*, const cuuint64_t*, const cuuint64_t*,
                             const cuuint32_t*, const cuuint32_t*, CUtensorMapInterleave, CUtensorMapSwizzle,
                             CUtensorMapL2promotion, CUtensorMapFloatOOBfill);

extern "C" void kernel_launch(void* const* d_in, const int* in_sizes, int n_in, void* d_out, int out_size) {
  (void)in_sizes; (void)n_in; (void)out_size;
  static EncodeFn encode = nullptr;
  static CUtensorMap tmg, tmu, tmd;
  static void* cached[3] = {nullptr, nullptr, nullptr};
  if (!encode) {
    cudaFuncSetAttribute(fused_kernel, cudaFuncAttributeMaxDynamicSharedMemorySize, (int)sizeof(Smem));
    void* fn = nullptr;
    cudaDriverEntryPointQueryResult qr;
    cudaGetDriverEntryPoint("cuTensorMapEncodeTiled", &fn, cudaEnableDefault, &qr);
    encode = (EncodeFn)fn;
  }
  if (cached[0] != d_in[8] || cached[1] != d_in[9] || cached[2] != d_in[10]) {
    const cuuint32_t es[2] = {1, 1};
    {
      const cuuint64_t dims[2] = {F_, D_}, strides[1] = {F_ * 2};
      const cuuint32_t box[2] = {24, 160};
      encode(&tmg, CU_TENSOR_MAP_DATA_TYPE_BFLOAT16, 2, d_in[8], dims, strides, box, es, CU_TENSOR_MAP_INTERLEAVE_NONE,
             CU_TENSOR_MAP_SWIZZLE_NONE, CU_TENSOR_MAP_L2_PROMOTION_NONE, CU_TENSOR_MAP_FLOAT_OOB_FILL_NONE);
      encode(&tmu, CU_TENSOR_MAP_DATA_TYPE_BFLOAT16, 2, d_in[9], dims, strides, box, es, CU_TENSOR_MAP_INTERLEAVE_NONE,
             CU_TENSOR_MAP_SWIZZLE_NONE, CU_TENSOR_MAP_L2_PROMOTION_NONE, CU_TENSOR_MAP_FLOAT_OOB_FILL_NONE);
    }
    {
      const cuuint64_t dims[2] = {D_, F_}, strides[1] = {D_ * 2};
      const cuuint32_t box[2] = {16, 256};
      encode(&tmd, CU_TENSOR_MAP_DATA_TYPE_BFLOAT16, 2, d_in[10], dims, strides, box, es, CU_TENSOR_MAP_INTERLEAVE_NONE,
             CU_TENSOR_MAP_SWIZZLE_NONE, CU_TENSOR_MAP_L2_PROMOTION_NONE, CU_TENSOR_MAP_FLOAT_OOB_FILL_NONE);
    }
    cached[0] = d_in[8]; cached[1] = d_in[9]; cached[2] = d_in[10];
  }
  fused_kernel<<<NCTA, NTHR, sizeof(Smem), cudaStreamPerThread>>>(
      tmg, tmu, tmd, (const bf16*)d_in[0], (const bf16*)d_in[1], (const bf16*)d_in[2], (const bf16*)d_in[3],
      (const bf16*)d_in[4], (const bf16*)d_in[5], (const bf16*)d_in[7], (bf16*)d_out);
}
```

```cpp
#include <cuda_runtime.h>
#include <cuda_bf16.h>
#include <cuda.h>
#include <stdint.h>

namespace {

typedef __nv_bfloat16 bf16;
typedef __nv_bfloat162 bf162;

constexpr int S_ = 2048, D_ = 640, F_ = 1536;
constexpr int NCTA = 128, CPC = 5, NTHR = 384;
constexpr int UPAD = 136, USTR = 2192;
constexpr int TABW = 1040;
constexpr int ZPB = 132;
constexpr int QSTR = 648;
constexpr int N1 = 64;
constexpr int N2 = 40;
constexpr int SPIN_LIMIT = 1 << 19;
#define POLL_NS 100
#define H_DELAY_NS 0

struct __align__(128) Smem {
  uint32_t tabA[3][2][TABW];
  uint32_t extra[1024];
  uint32_t tabB[2][2][TABW];
  bf16 u[CPC][USTR];
  float z[2][4][ZPB * 16];
  bf16 q[16][QSTR];
  alignas(128) uint4 w[3840];
  uint4 wr[80];
  float2 st[16][5];
  float rp[16][5];
  unsigned long long mbar;
  unsigned long long mbarw;
  unsigned long long mbarkv;
  unsigned long long mbarh;
  uint32_t target;
  uint32_t target2;
  uint32_t best;
  uint32_t win;
};

__device__ uint4 g_kv[D_ * S_ / 8];
__device__ uint4 g_y2[D_ * S_ / 8];
__device__ uint32_t g_keys[NCTA];
__device__ uint4 g_cand[NCTA][2][80];
__device__ uint4 g_act[F_ / 8];
__device__ unsigned int g_ctr;
__device__ unsigned int g_ctr2;
#define STAMP(i)

__device__ __forceinline__ uint32_t smem_u32(const void* p) { return (uint32_t)__cvta_generic_to_shared(p); }
__device__ __forceinline__ void wg_fence() { asm volatile("wgmma.fence.sync.aligned;" ::: "memory"); }
__device__ __forceinline__ void wg_commit() { asm volatile("wgmma.commit_group.sync.aligned;" ::: "memory"); }
template <int N> __device__ __forceinline__ void wg_wait() { asm volatile("wgmma.wait_group.sync.aligned %0;" ::"n"(N) : "memory"); }
__device__ __forceinline__ void bar_sync(int id, int n) { asm volatile("bar.sync %0, %1;" ::"r"(id), "r"(n) : "memory"); }
__device__ __forceinline__ void bar_arrive(int id, int n) { asm volatile("bar.arrive %0, %1;" ::"r"(id), "r"(n) : "memory"); }
__device__ __forceinline__ bf162 u2b(uint32_t u) { return *reinterpret_cast<bf162*>(&u); }
__device__ __forceinline__ uint32_t b2u(bf162 b) { return *reinterpret_cast<uint32_t*>(&b); }
__device__ __forceinline__ float lo_f(uint32_t u) { return __uint_as_float(u << 16); }
__device__ __forceinline__ float hi_f(uint32_t u) { return __uint_as_float(u & 0xFFFF0000u); }
__device__ __forceinline__ float rbf(float x) { return __bfloat162float(__float2bfloat16_rn(x)); }
__device__ __forceinline__ uint32_t pack2(float a, float b) { return b2u(__floats2bfloat162_rn(a, b)); }
__device__ __forceinline__ uint32_t enc(uint32_t w) { return max(~w, 1u); }
__device__ __forceinline__ uint4 enc4(uint4 v) { return make_uint4(enc(v.x), enc(v.y), enc(v.z), enc(v.w)); }
__device__ __forceinline__ uint4 ld_poll4(const uint4* p) {
  uint4 v;
  asm volatile("ld.relaxed.gpu.global.v4.u32 {%0,%1,%2,%3}, [%4];" : "=r"(v.x), "=r"(v.y), "=r"(v.z), "=r"(v.w) : "l"(p) : "memory");
  return v;
}
__device__ __forceinline__ bool ready4(uint4 v) { return v.x != 0u && v.y != 0u && v.z != 0u && v.w != 0u; }
__device__ __forceinline__ uint4 poll4(const uint4* p) {
  uint4 v = ld_poll4(p);
  int it = 0;
  while (!ready4(v) && ++it < SPIN_LIMIT) v = ld_poll4(p);
  return make_uint4(~v.x, ~v.y, ~v.z, ~v.w);
}
__device__ __forceinline__ void st_pub4(uint4* p, uint4 v) {
  asm volatile("st.relaxed.gpu.global.v4.u32 [%0], {%1,%2,%3,%4};" ::"l"(p), "r"(v.x), "r"(v.y), "r"(v.z), "r"(v.w) : "memory");
}
__device__ __forceinline__ void st_pub2(uint2* p, uint32_t a, uint32_t b) {
  asm volatile("st.relaxed.gpu.global.v2.u32 [%0], {%1,%2};" ::"l"(p), "r"(a), "r"(b) : "memory");
}
__device__ __forceinline__ void mma_bf16(float (&c)[4], uint32_t a0, uint32_t a2, uint32_t b0, uint32_t b1) {
  asm volatile("mma.sync.aligned.m16n8k16.row.col.f32.bf16.bf16.f32 {%0,%1,%2,%3}, {%4,%5,%6,%5}, {%7,%8}, {%0,%1,%2,%3};"
               : "+f"(c[0]), "+f"(c[1]), "+f"(c[2]), "+f"(c[3]) : "r"(a0), "r"(0u), "r"(a2), "r"(b0), "r"(b1));
}
__device__ __forceinline__ void mbar_wait(const unsigned long long* bar) {
  const uint32_t mb = smem_u32(bar);
  uint32_t ok = 0;
  int it = 0;
  while (!ok && ++it < SPIN_LIMIT)
    asm volatile("{ .reg .pred p; mbarrier.try_wait.parity.shared.b64 p, [%1], 0; selp.u32 %0, 1, 0, p; }" : "=r"(ok) : "r"(mb) : "memory");
}
__device__ __forceinline__ void bulk_g2s(void* dst, const void* src, uint32_t bytes, const unsigned long long* bar) {
  asm volatile("cp.async.bulk.shared::cluster.global.mbarrier::complete_tx::bytes [%0], [%1], %2, [%3];" ::"r"(smem_u32(dst)),
               "l"(src), "r"(bytes), "r"(smem_u32(bar)) : "memory");
}
__device__ __forceinline__ void mbar_expect(const unsigned long long* bar, uint32_t bytes) {
  asm volatile("mbarrier.arrive.expect_tx.shared.b64 _, [%0], %1;" ::"r"(smem_u32(bar)), "r"(bytes) : "memory");
}
__device__ __forceinline__ float fdivr(float a, float d, float r) {
  float q = a * r;
  float e = fmaf(-q, d, a);
  return fmaf(e, r, q);
}

template <bool FIRST> __device__ __forceinline__ void wgmma32(float (&d)[16], const uint32_t* a, uint64_t desc) {
  if (FIRST) {
    asm volatile("wgmma.mma_async.sync.aligned.m64n32k16.f32.bf16.bf16 {%0,%1,%2,%3,%4,%5,%6,%7,%8,%9,%10,%11,%12,%13,%14,%15}, {%16,%17,%18,%19}, %20, 0, 1, 1, 0;"
                 : "+f"(d[0]), "+f"(d[1]), "+f"(d[2]), "+f"(d[3]), "+f"(d[4]), "+f"(d[5]), "+f"(d[6]), "+f"(d[7]),
                   "+f"(d[8]), "+f"(d[9]), "+f"(d[10]), "+f"(d[11]), "+f"(d[12]), "+f"(d[13]), "+f"(d[14]), "+f"(d[15])
                 : "r"(a[0]), "r"(a[1]), "r"(a[2]), "r"(a[3]), "l"(desc));
  } else {
    asm volatile("wgmma.mma_async.sync.aligned.m64n32k16.f32.bf16.bf16 {%0,%1,%2,%3,%4,%5,%6,%7,%8,%9,%10,%11,%12,%13,%14,%15}, {%16,%17,%18,%19}, %20, 1, 1, 1, 0;"
                 : "+f"(d[0]), "+f"(d[1]), "+f"(d[2]), "+f"(d[3]), "+f"(d[4]), "+f"(d[5]), "+f"(d[6]), "+f"(d[7]),
                   "+f"(d[8]), "+f"(d[9]), "+f"(d[10]), "+f"(d[11]), "+f"(d[12]), "+f"(d[13]), "+f"(d[14]), "+f"(d[15])
                 : "r"(a[0]), "r"(a[1]), "r"(a[2]), "r"(a[3]), "l"(desc));
  }
}

template <int G> __device__ __forceinline__ void load_a(uint32_t (&a)[8], const uint32_t* tp) {
#pragma unroll
  for (int q = 0; q < 2; q++) {
    const int e = 2 * G + q;
    a[4 * q + 0] = tp[-64 * e];
    a[4 * q + 1] = tp[-64 * e - 32];
    a[4 * q + 2] = tp[-64 * e + 4];
    a[4 * q + 3] = tp[-64 * e - 28];
  }
}
__device__ __forceinline__ void load_a_all(uint32_t (&a)[8][8], const uint32_t* tp) {
  load_a<0>(a[0], tp); load_a<1>(a[1], tp); load_a<2>(a[2], tp); load_a<3>(a[3], tp);
  load_a<4>(a[4], tp); load_a<5>(a[5], tp); load_a<6>(a[6], tp); load_a<7>(a[7], tp);
}
template <int G> __device__ __forceinline__ void issue_g(float (&acc)[8][16], uint32_t (&a)[8], uint64_t desc0) {
  wg_fence();
#pragma unroll
  for (int q = 0; q < 2; q++) {
#pragma unroll
    for (int b = G; b < 8; b++) {
      const int delta = 2 * b - (2 * G + q);
      if (G == 0 && q == 0) wgmma32<true>(acc[b], &a[4 * q], desc0 + (uint64_t)(int64_t)(16 * delta));
      else wgmma32<false>(acc[b], &a[4 * q], desc0 + (uint64_t)(int64_t)(16 * delta));
    }
  }
  wg_commit();
}
template <int B> __device__ __forceinline__ void fence_blk(float (&acc)[8][16]) {
#pragma unroll
  for (int i = 0; i < 16; i++) asm volatile("" : "+f"(acc[B][i])::"memory");
}
__device__ __forceinline__ void fence_a(uint32_t (&a)[8]) {
#pragma unroll
  for (int i = 0; i < 8; i++) asm volatile("" : "+r"(a[i])::"memory");
}
template <int B> __device__ __forceinline__ void sts_blk(float (&acc)[8][16], float* zw, int off_even, int off_odd) {
#pragma unroll
  for (int jj = 0; jj < 4; jj++) {
    const int j = 4 * B + jj;
    float p0 = acc[B][4 * jj + 0], p1 = acc[B][4 * jj + 1];
    if (jj > 0) { p0 += acc[B][4 * (jj - 1) + 2]; p1 += acc[B][4 * (jj - 1) + 3]; }
    else if (B > 0) { p0 += acc[B > 0 ? B - 1 : 0][14]; p1 += acc[B > 0 ? B - 1 : 0][15]; }
    zw[64 * j + off_even] = p0;
    zw[64 * j + off_odd] = p1;
  }
}
__device__ __forceinline__ int tab_off(int c) { return c == 4 ? 0 : (c + 1) * 2 * TABW + (c >= 2 ? 1024 : 0); }
__device__ __forceinline__ int tile_perm(int ch) { return ch ^ (((ch >> 3) & 3) << 1); }

__device__ __forceinline__ void wait_cleared(uint32_t target) {
  uint32_t v;
  int it = 0;
  do {
    asm volatile("ld.acquire.gpu.global.u32 %0, [%1];" : "=r"(v) : "l"(&g_ctr) : "memory");
  } while ((int)(v - target) < 0 && ++it < SPIN_LIMIT);
}

__global__ void __launch_bounds__(NTHR, 1)
fused_kernel(const __grid_constant__ CUtensorMap tmg, const __grid_constant__ CUtensorMap tmu,
             const __grid_constant__ CUtensorMap tmd, const bf16* __restrict__ gq, const bf16* __restrict__ gk, const bf16* __restrict__ gv,
             const bf16* __restrict__ gsk, const bf16* __restrict__ gh, const bf16* __restrict__ gD,
             const bf16* __restrict__ gwr, bf16* __restrict__ gout) {
  extern __shared__ __align__(128) unsigned char smraw[];
  Smem& sm = *reinterpret_cast<Smem*>(smraw);
  const int tid = threadIdx.x;
  const int cta = blockIdx.x;
  const int c0 = cta * CPC;
  const int lane = tid & 31;
  const int wid = tid >> 5;
  STAMP(0);

  {
    uint32_t* ks = reinterpret_cast<uint32_t*>(&sm.z[0][0][0]);
    uint32_t* vs = ks + 19 * 320;
    uint4* hs = reinterpret_cast<uint4*>(vs + 16 * 320);
    if (tid == 0) {
      asm volatile("mbarrier.init.shared.b64 [%0], 1;" ::"r"(smem_u32(&sm.mbarkv)) : "memory");
      asm volatile("mbarrier.init.shared.b64 [%0], 1;" ::"r"(smem_u32(&sm.mbarh)) : "memory");
      asm volatile("mbarrier.init.shared.b64 [%0], 1;" ::"r"(smem_u32(&sm.mbar)) : "memory");
      asm volatile("mbarrier.init.shared.b64 [%0], 1;" ::"r"(smem_u32(&sm.mbarw)) : "memory");
      asm volatile("fence.proxy.async.shared::cta;" ::: "memory");
      const int skip = cta == 0 ? 3 : 0;
      mbar_expect(&sm.mbarkv, (35 - skip) * 1280);
      bulk_g2s(ks + skip * 320, gk + (size_t)(cta * 16 - 3 + skip) * D_, (19 - skip) * 1280, &sm.mbarkv);
      bulk_g2s(vs, gv + (size_t)cta * 16 * D_, 16 * 1280, &sm.mbarkv);
      mbar_expect(&sm.mbarh, CPC * S_ * 2);
      bulk_g2s(hs, gh + (size_t)c0 * S_, CPC * S_ * 2, &sm.mbarh);
      mbar_expect(&sm.mbar, 17 * D_ * 2);
#pragma unroll 1
      for (int r = 0; r < 16; r++) bulk_g2s(&sm.q[r][0], gq + (size_t)(cta * 16 + r) * D_, D_ * 2, &sm.mbar);
      bulk_g2s(&sm.wr[0], gwr, D_ * 2, &sm.mbar);
    }
    uint4 sk = make_uint4(0, 0, 0, 0);
    if (tid < 320) {
      sk = __ldg(reinterpret_cast<const uint4*>(gsk) + tid);
      if (cta == 0) { ks[tid] = 0u; ks[320 + tid] = 0u; ks[640 + tid] = 0u; }
    } else {
      const int t0 = tid - 320;
      const uint4 zz = make_uint4(0, 0, 0, 0);
#pragma unroll 4
      for (int i = 0; i < 20; i++) g_y2[cta * 1280 + t0 + 64 * i] = zz;
      (&g_cand[cta][0][0])[t0] = zz;
      (&g_cand[cta][0][0])[64 + t0] = zz;
      if (t0 < 32) (&g_cand[cta][0][0])[128 + t0] = zz;
      else if (t0 < 35) { if (cta < N1) g_act[cta * 3 + (t0 - 32)] = zz; }
      else if (t0 == 35) g_keys[cta] = 0u;
      for (int t = t0; t < CPC * 17; t += 64) *reinterpret_cast<uint4*>(&sm.u[t / 17][(t % 17) * 8]) = zz;
      if (t0 < 40) *reinterpret_cast<uint4*>(&sm.tabA[0][0][0] + tab_off(t0 >> 3) + ((t0 >> 2) & 1) * TABW + 1024 + 4 * (t0 & 3)) = zz;
    }
    __syncthreads();
    STAMP(9);
    if (tid < 320) {
      mbar_wait(&sm.mbarkv);
      const bf162 w0 = u2b(__byte_perm(sk.x, sk.z, 0x5410)), w1 = u2b(__byte_perm(sk.x, sk.z, 0x7632));
      const bf162 w2 = u2b(__byte_perm(sk.y, sk.w, 0x5410)), w3 = u2b(__byte_perm(sk.y, sk.w, 0x7632));
      uint32_t kk[19], kv[16];
#pragma unroll
      for (int i = 0; i < 19; i++) kk[i] = ks[i * 320 + tid];
#pragma unroll
      for (int i = 0; i < 16; i++) {
        bf162 a = __hmul2_rn(u2b(kk[i]), w3);
        a = __hadd2_rn(a, __hmul2_rn(u2b(kk[i + 1]), w2));
        a = __hadd2_rn(a, __hmul2_rn(u2b(kk[i + 2]), w1));
        a = __hadd2_rn(a, __hmul2_rn(u2b(kk[i + 3]), w0));
        kv[i] = b2u(__hmul2_rn(a, u2b(vs[i * 320 + tid])));
      }
      uint4* dst = g_kv + (size_t)(2 * tid) * 256 + cta * 2;
#pragma unroll
      for (int e = 0; e < 2; e++) {
        const uint32_t sel = e ? 0x7632u : 0x5410u;
#pragma unroll
        for (int hb = 0; hb < 2; hb++)
          st_pub4(dst + e * 256 + hb, make_uint4(enc(__byte_perm(kv[8 * hb + 0], kv[8 * hb + 1], sel)), enc(__byte_perm(kv[8 * hb + 2], kv[8 * hb + 3], sel)),
                                                 enc(__byte_perm(kv[8 * hb + 4], kv[8 * hb + 5], sel)), enc(__byte_perm(kv[8 * hb + 6], kv[8 * hb + 7], sel))));
      }
      STAMP(10);
      if (wid == 0) bar_sync(6, 320); else bar_arrive(6, 320);
      if (tid == 0) {
        const unsigned old = atomicAdd(&g_ctr2, 1u);
        sm.target2 = (old / NCTA + 1u) * NCTA;
      }
    } else if (tid == 352) {
      __threadfence();
      const unsigned old = atomicAdd(&g_ctr, 1u);
      sm.target = (old / NCTA + 1u) * NCTA;
    }
    mbar_wait(&sm.mbarh);
#pragma unroll
    for (int i = 0; i < 4; i++) {
      const int t = (NTHR - 1 - tid) + NTHR * i;
      if (t < CPC * 256) {
        uint32_t* tb = &sm.tabA[0][0][0] + tab_off(t >> 8) + (255 - (t & 255)) * 4;
        const uint4 h = hs[t];
        const uint32_t hp = (t & 255) ? reinterpret_cast<const uint32_t*>(hs)[4 * t - 1] : 0u;
        uint4 r1, rr;
        r1.x = __byte_perm(h.w, 0, 0x1032); r1.y = __byte_perm(h.z, 0, 0x1032);
        r1.z = __byte_perm(h.y, 0, 0x1032); r1.w = __byte_perm(h.x, 0, 0x1032);
        rr.x = __byte_perm(h.w, h.z, 0x7610); rr.y = __byte_perm(h.z, h.y, 0x7610);
        rr.z = __byte_perm(h.y, h.x, 0x7610); rr.w = __byte_perm(h.x, hp, 0x7610);
        *reinterpret_cast<uint4*>(tb) = rr;
        *reinterpret_cast<uint4*>(tb + TABW) = r1;
      }
    }
    if (tid == 0) {
      const unsigned target = sm.target2;
      uint32_t v;
      int it = 0;
      do {
        asm volatile("ld.relaxed.gpu.global.u32 %0, [%1];" : "=r"(v) : "l"(&g_ctr2) : "memory");
      } while ((int)(v - target) < 0 && ++it < SPIN_LIMIT);
    }
    STAMP(12);
  }
  __syncthreads();
  {
    uint4 v[4];
    uint4* src = g_kv + c0 * 256 + tid;
#pragma unroll
    for (int i = 0; i < 4; i++) if (i < 3 || tid < 128) v[i] = ld_poll4(src + NTHR * i);
    if (tid >= 256) {
      const int t0 = tid - 256;
      *reinterpret_cast<uint4*>(&sm.z[t0 >> 6][(t0 >> 4) & 3][(t0 & 15) * 4]) = make_uint4(0, 0, 0, 0);
    }
#pragma unroll
    for (int i = 0; i < 4; i++) {
      if (i < 3 || tid < 128) {
        int it = 0;
        while (!ready4(v[i]) && ++it < SPIN_LIMIT) { __nanosleep(POLL_NS); v[i] = ld_poll4(src + NTHR * i); }
        const int t = tid + NTHR * i;
        *reinterpret_cast<uint4*>(&sm.u[t >> 8][UPAD + (t & 255) * 8]) = make_uint4(~v[i].x, ~v[i].y, ~v[i].z, ~v[i].w);
      }
    }
    STAMP(11);
    asm volatile("fence.proxy.async.shared::cta;" ::: "memory");
    __syncthreads();
#pragma unroll
    for (int i = 0; i < 4; i++) if (i < 3 || tid < 128) src[NTHR * i] = make_uint4(0, 0, 0, 0);
  }
  STAMP(1);

  const int wg = __shfl_sync(0xffffffffu, tid >> 7, 0);
  const int wtid = tid & 127;
  uint4* tile = reinterpret_cast<uint4*>(&sm.tabB[0][0][0]);
  bf16* qn_s = reinterpret_cast<bf16*>(&sm.tabA[1][0][0]);
  if (wg < 2) {
    asm volatile("setmaxnreg.inc.sync.aligned.u32 224;");
    const int w = (tid >> 5) & 3, g = lane >> 2, tq = lane & 3;
    float* zw = sm.z[wg][w];
    const int sw = 3 * (((tq + w) >> 1) & 1);
    const int off_even = 16 * (tq + w) + 4 * ((0 + (g >> 2)) ^ sw) + (g & 3);
    const int off_odd = 16 * (tq + w) + 4 * ((2 + (g >> 2)) ^ sw) + (g & 3);
    uint32_t a[8][8];
    const uint32_t* tp0 = &sm.tabA[0][g & 1][1019 - 8 * w - (g >> 1) + tq];
    load_a_all(a, tp0 + tab_off(wg));
    bar_arrive(7, 384);
    float acc[8][16];
#pragma unroll
    for (int b = 0; b < 8; b++)
#pragma unroll
      for (int i = 0; i < 16; i++) acc[b][i] = 0.f;
#pragma unroll 1
    for (int c = wg; c < CPC; c += 2) {
      const uint64_t desc = (uint64_t)((smem_u32(&sm.u[c][UPAD - 8]) & 0x3FFFF) >> 4) | ((uint64_t)1 << 16) | ((uint64_t)8 << 32);
      if (c > 0) bar_sync(1 + wg, 256);
      issue_g<0>(acc, a[0], desc);
      issue_g<1>(acc, a[1], desc);
      issue_g<2>(acc, a[2], desc);
      issue_g<3>(acc, a[3], desc);
      issue_g<4>(acc, a[4], desc);
      issue_g<5>(acc, a[5], desc);
      if (c + 1 < CPC) bar_arrive(1 + (wg ^ 1), 256);
      issue_g<6>(acc, a[6], desc);
      issue_g<7>(acc, a[7], desc);
      if (c >= 2) bar_sync(5 + wg, 256);
      wg_wait<4>();
      fence_blk<0>(acc); fence_blk<1>(acc); fence_blk<2>(acc); fence_blk<3>(acc);
      sts_blk<0>(acc, zw, off_even, off_odd);
      sts_blk<1>(acc, zw, off_even, off_odd);
      sts_blk<2>(acc, zw, off_even, off_odd);
      sts_blk<3>(acc, zw, off_even, off_odd);
      wg_wait<0>();
      fence_blk<4>(acc); fence_blk<5>(acc); fence_blk<6>(acc); fence_blk<7>(acc);
#pragma unroll
      for (int i = 0; i < 8; i++) fence_a(a[i]);
      sts_blk<4>(acc, zw, off_even, off_odd);
      sts_blk<5>(acc, zw, off_even, off_odd);
      sts_blk<6>(acc, zw, off_even, off_odd);
      sts_blk<7>(acc, zw, off_even, off_odd);
      bar_arrive(3 + wg, 256);
      if (c + 2 < CPC) load_a_all(a, tp0 + tab_off(c + 2));
    }
    STAMP(2 + wg);
    asm volatile("setmaxnreg.dec.sync.aligned.u32 168;");
    if (wg == 1) {
#pragma unroll 1
      for (int cc = 0; cc < 4; cc++) {
        const int ch = wtid * 5 + cc;
        const uint4* src = g_y2 + cta * 1280 + ch * 2;
        uint4 v0 = ld_poll4(src), v1 = ld_poll4(src + 1);
        int it = 0;
        while (!ready4(v0) && ++it < SPIN_LIMIT) v0 = ld_poll4(src);
        while (!ready4(v1) && ++it < SPIN_LIMIT) v1 = ld_poll4(src + 1);
        const int pc = tile_perm(ch);
        tile[pc] = make_uint4(~v0.x, ~v0.y, ~v0.z, ~v0.w);
        tile[640 + pc] = make_uint4(~v1.x, ~v1.y, ~v1.z, ~v1.w);
      }
    }
  } else {
    asm volatile("setmaxnreg.dec.sync.aligned.u32 56;");
    if (wtid == 32) {
      const uint32_t mw = smem_u32(&sm.mbarw);
      if (cta < N1) {
        asm volatile("mbarrier.arrive.expect_tx.shared.b64 _, [%0], %1;" ::"r"(mw), "r"(3840 * 16) : "memory");
#pragma unroll 1
        for (int i = 0; i < 4; i++) {
          asm volatile("cp.async.bulk.tensor.2d.shared::cluster.global.mbarrier::complete_tx::bytes [%0], [%1, {%3, %4}], [%2];" ::"r"(smem_u32(&sm.w[i * 480])),
                       "l"(&tmg), "r"(mw), "r"(cta * 24), "r"(i * 160) : "memory");
          asm volatile("cp.async.bulk.tensor.2d.shared::cluster.global.mbarrier::complete_tx::bytes [%0], [%1, {%3, %4}], [%2];" ::"r"(smem_u32(&sm.w[1920 + i * 480])),
                       "l"(&tmu), "r"(mw), "r"(cta * 24), "r"(i * 160) : "memory");
        }
      } else if (cta < N1 + N2) {
        asm volatile("mbarrier.arrive.expect_tx.shared.b64 _, [%0], %1;" ::"r"(mw), "r"(3072 * 16) : "memory");
#pragma unroll 1
        for (int i = 0; i < 6; i++)
          asm volatile("cp.async.bulk.tensor.2d.shared::cluster.global.mbarrier::complete_tx::bytes [%0], [%1, {%3, %4}], [%2];" ::"r"(smem_u32(&sm.w[i * 512])),
                       "l"(&tmd), "r"(mw), "r"((cta - N1) * 16), "r"(i * 256) : "memory");
      }
    }
    mbar_wait(&sm.mbar);
    bar_sync(7, 384);
#pragma unroll 1
    for (int rr = 0; rr < 4; rr += 2) {
      const int row = (wid - 8) * 4 + rr;
      const uint32_t* qp = reinterpret_cast<const uint32_t*>(&sm.q[row][0]);
      uint32_t qa[10], qb[10];
      float sa = 0.f, sb = 0.f;
#pragma unroll
      for (int i = 0; i < 10; i++) {
        qa[i] = qp[lane + 32 * i]; qb[i] = qp[QSTR / 2 + lane + 32 * i];
        sa += lo_f(qa[i]) + hi_f(qa[i]); sb += lo_f(qb[i]) + hi_f(qb[i]);
      }
#pragma unroll
      for (int o = 16; o > 0; o >>= 1) { sa += __shfl_xor_sync(0xffffffffu, sa, o); sb += __shfl_xor_sync(0xffffffffu, sb, o); }
      sa *= (1.f / D_); sb *= (1.f / D_);
      float ma = 0.f, mb2 = 0.f;
#pragma unroll
      for (int i = 0; i < 10; i++) {
        const float x = lo_f(qa[i]) - sa, y = hi_f(qa[i]) - sa, z = lo_f(qb[i]) - sb, t = hi_f(qb[i]) - sb;
        ma = fmaf(x, x, fmaf(y, y, ma)); mb2 = fmaf(z, z, fmaf(t, t, mb2));
      }
#pragma unroll
      for (int o = 16; o > 0; o >>= 1) { ma += __shfl_xor_sync(0xffffffffu, ma, o); mb2 += __shfl_xor_sync(0xffffffffu, mb2, o); }
      const float da = rbf(sqrtf(rbf(rbf(ma * (1.f / D_)) + 1e-5f))), db = rbf(sqrtf(rbf(rbf(mb2 * (1.f / D_)) + 1e-5f)));
      const float ra = 1.f / da, rb = 1.f / db;
      const bf162 ma2 = __float2bfloat162_rn(sa), mb3 = __float2bfloat162_rn(sb);
      uint32_t* np = reinterpret_cast<uint32_t*>(qn_s + row * QSTR);
#pragma unroll
      for (int i = 0; i < 10; i++) {
        const uint32_t d = b2u(__hsub2_rn(u2b(qa[i]), ma2)), e = b2u(__hsub2_rn(u2b(qb[i]), mb3));
        np[lane + 32 * i] = pack2(fdivr(lo_f(d), da, ra), fdivr(hi_f(d), da, ra));
        np[QSTR / 2 + lane + 32 * i] = pack2(fdivr(lo_f(e), db, rb), fdivr(hi_f(e), db, rb));
      }
    }
    if (wtid == 0) wait_cleared(sm.target);
    const int rpb = wtid >> 1, re2 = wtid & 1;
    const int rsw = 3 * ((rpb >> 1) & 1);
    const int roff0 = 16 * rpb + 4 * ((2 * re2 + 0) ^ rsw);
    const int roff1 = 16 * rpb + 4 * ((2 * re2 + 1) ^ rsw);
    const uint32_t dvl = reinterpret_cast<const unsigned short*>(gD)[c0 + (lane < CPC ? lane : 0)];
#pragma unroll 1
    for (int c = 0; c < CPC; c++) {
      const int zg = c & 1;
      const uint32_t dvc = __shfl_sync(0xffffffffu, dvl, c);
      const bf162 d2 = u2b(dvc | (dvc << 16));
      bar_sync(3 + zg, 256);
#pragma unroll
      for (int half = 0; half < 2; half++) {
        const float* zb = sm.z[zg][0] + half * 1024;
        float4 x[4][2];
#pragma unroll
        for (int ww = 0; ww < 4; ww++) {
          x[ww][0] = *reinterpret_cast<const float4*>(zb + ww * ZPB * 16 + roff0);
          x[ww][1] = *reinterpret_cast<const float4*>(zb + ww * ZPB * 16 + roff1);
        }
        const int sidx = half * 1024 + wtid * 8;
        const uint4 kvv = *reinterpret_cast<const uint4*>(&sm.u[c][UPAD + sidx]);
        if (half == 1 && c + 2 < CPC) bar_arrive(5 + zg, 256);
        uint4 o;
        o.x = pack2((x[0][0].x + x[1][0].x) + (x[2][0].x + x[3][0].x), (x[0][0].y + x[1][0].y) + (x[2][0].y + x[3][0].y));
        o.y = pack2((x[0][0].z + x[1][0].z) + (x[2][0].z + x[3][0].z), (x[0][0].w + x[1][0].w) + (x[2][0].w + x[3][0].w));
        o.z = pack2((x[0][1].x + x[1][1].x) + (x[2][1].x + x[3][1].x), (x[0][1].y + x[1][1].y) + (x[2][1].y + x[3][1].y));
        o.w = pack2((x[0][1].z + x[1][1].z) + (x[2][1].z + x[3][1].z), (x[0][1].w + x[1][1].w) + (x[2][1].w + x[3][1].w));
        o.x = b2u(__hadd2_rn(u2b(o.x), __hmul2_rn(u2b(kvv.x), d2)));
        o.y = b2u(__hadd2_rn(u2b(o.y), __hmul2_rn(u2b(kvv.y), d2)));
        o.z = b2u(__hadd2_rn(u2b(o.z), __hmul2_rn(u2b(kvv.z), d2)));
        o.w = b2u(__hadd2_rn(u2b(o.w), __hmul2_rn(u2b(kvv.w), d2)));
        st_pub4(g_y2 + ((64 * half + rpb) * 640 + c0 + c) * 2 + re2, enc4(o));
      }
    }
    STAMP(4);
    asm volatile("setmaxnreg.inc.sync.aligned.u32 168;");
  }

  if (tid < 128 || tid >= 256) {
    const int t = tid < 128 ? tid : tid - 128;
    const int ch = (t >> 1) * 5 + 4, hh = t & 1;
    const uint4 v = poll4(g_y2 + cta * 1280 + ch * 2 + hh);
    tile[hh * 640 + tile_perm(ch)] = v;
  }
  __syncthreads();
  STAMP(5);

  const int g = lane >> 2, tq = lane & 3;
  const int hh = wid & 1, gqi = wid >> 1;
  const int row = hh * 8 + g;
  uint32_t hreg[16], hnreg[16];
  if (wid < 10) {
    float cs[4] = {0.f, 0.f, 0.f, 0.f};
#pragma unroll
    for (int k = 0; k < 4; k++) {
      const int base = 32 * (4 * gqi + k);
      const int lch = base + 8 * ((lane & 7) >> 1) + 2 * (lane >> 3) + (lane & 1);
      uint32_t y[4];
      asm volatile("ldmatrix.sync.aligned.m8n8.x4.trans.shared.b16 {%0,%1,%2,%3}, [%4];"
                   : "=r"(y[0]), "=r"(y[1]), "=r"(y[2]), "=r"(y[3]) : "r"(smem_u32(&tile[hh * 640 + tile_perm(lch)])) : "memory");
      const uint4 qv4 = *reinterpret_cast<const uint4*>(&sm.q[row][base + 8 * tq]);
      const uint4 qn4 = *reinterpret_cast<const uint4*>(qn_s + row * QSTR + base + 8 * tq);
      hreg[4 * k + 0] = b2u(__hadd2_rn(u2b(qv4.x), __hmul2_rn(u2b(qn4.x), u2b(y[0]))));
      hreg[4 * k + 1] = b2u(__hadd2_rn(u2b(qv4.y), __hmul2_rn(u2b(qn4.y), u2b(y[1]))));
      hreg[4 * k + 2] = b2u(__hadd2_rn(u2b(qv4.z), __hmul2_rn(u2b(qn4.z), u2b(y[2]))));
      hreg[4 * k + 3] = b2u(__hadd2_rn(u2b(qv4.w), __hmul2_rn(u2b(qn4.w), u2b(y[3]))));
      mma_bf16(cs, hreg[4 * k + 0], hreg[4 * k + 1], 0x3F803F80u, 0x3F803F80u);
      mma_bf16(cs, hreg[4 * k + 2], hreg[4 * k + 3], 0x3F803F80u, 0x3F803F80u);
    }
    const float mean = cs[0] * (1.f / 128.f);
    float m2a = 0.f, m2b = 0.f;
#pragma unroll
    for (int i = 0; i < 16; i++) {
      const float a = lo_f(hreg[i]) - mean, b = hi_f(hreg[i]) - mean;
      m2a = fmaf(a, a, m2a); m2b = fmaf(b, b, m2b);
    }
    float m2 = m2a + m2b;
    m2 += __shfl_xor_sync(0xffffffffu, m2, 1);
    m2 += __shfl_xor_sync(0xffffffffu, m2, 2);
    if (tq == 0) sm.st[row][gqi] = make_float2(mean, m2);
  }
  STAMP(13);
  __syncthreads();
  if (wid < 10) {
    float mean = 0.f, m2 = 0.f;
    float2 p[5];
#pragma unroll
    for (int i = 0; i < 5; i++) { p[i] = sm.st[row][i]; mean += p[i].x; }
    mean *= 0.2f;
#pragma unroll
    for (int i = 0; i < 5; i++) { const float dl = p[i].x - mean; m2 += p[i].y + 128.f * dl * dl; }
    const float hd = rbf(sqrtf(rbf(rbf(m2 * (1.f / D_)) + 1e-5f)));
    const float hr = 1.f / hd;
    const bf162 hm2 = __float2bfloat162_rn(mean);
    float cr[4] = {0.f, 0.f, 0.f, 0.f};
#pragma unroll
    for (int k = 0; k < 4; k++) {
      const uint4 w4 = sm.wr[4 * (4 * gqi + k) + tq];
#pragma unroll
      for (int i = 0; i < 4; i++) {
        const uint32_t d = b2u(__hsub2_rn(u2b(hreg[4 * k + i]), hm2));
        hnreg[4 * k + i] = pack2(fdivr(lo_f(d), hd, hr), fdivr(hi_f(d), hd, hr));
      }
      mma_bf16(cr, hnreg[4 * k + 0], hnreg[4 * k + 1], w4.x, w4.y);
      mma_bf16(cr, hnreg[4 * k + 2], hnreg[4 * k + 3], w4.z, w4.w);
    }
    if (tq == 0) sm.rp[row][gqi] = cr[0];
  }
  STAMP(14);
  __syncthreads();
  uint32_t best;
  {
    const int rr = lane & 15;
    const float r = ((sm.rp[rr][0] + sm.rp[rr][1]) + (sm.rp[rr][2] + sm.rp[rr][3])) + sm.rp[rr][4];
    const uint32_t bits = __bfloat16_as_ushort(__float2bfloat16_rn(r));
    const uint32_t ord = (bits & 0x8000u) ? (bits ^ 0xFFFFu) : (bits ^ 0x8000u);
    const uint32_t key = (ord << 16) | 0x8000u | (uint32_t)(2047 - (cta * 16 + rr));
    best = __reduce_max_sync(0xffffffffu, key);
  }
  if (tid == 352) asm volatile("st.relaxed.gpu.global.u32 [%0], %1;" ::"l"(&g_keys[cta]), "r"(best) : "memory");
  STAMP(15);
  const int brow = (2047 - (int)(best & 0x7FFu)) - cta * 16;
  uint4 outv[4];
  if (wid < 10) {
#pragma unroll
    for (int k = 0; k < 4; k++) {
      outv[k].x = b2u(__hadd2_rn(u2b(hreg[4 * k + 0]), u2b(hnreg[4 * k + 0])));
      outv[k].y = b2u(__hadd2_rn(u2b(hreg[4 * k + 1]), u2b(hnreg[4 * k + 1])));
      outv[k].z = b2u(__hadd2_rn(u2b(hreg[4 * k + 2]), u2b(hnreg[4 * k + 2])));
      outv[k].w = b2u(__hadd2_rn(u2b(hreg[4 * k + 3]), u2b(hnreg[4 * k + 3])));
      const int chunk = 4 * (4 * gqi + k) + tq;
      if (row == brow) {
        st_pub4(&g_cand[cta][0][chunk], enc4(make_uint4(hnreg[4 * k], hnreg[4 * k + 1], hnreg[4 * k + 2], hnreg[4 * k + 3])));
        st_pub4(&g_cand[cta][1][chunk], enc4(make_uint4(hreg[4 * k], hreg[4 * k + 1], hreg[4 * k + 2], hreg[4 * k + 3])));
      } else {
        *reinterpret_cast<uint4*>(gout + (size_t)(cta * 16 + row) * D_ + chunk * 8) = outv[k];
      }
    }
  }
  STAMP(6);
  if (wid == 11) {
    const uint4* kp = reinterpret_cast<const uint4*>(g_keys) + lane;
    uint4 v = ld_poll4(kp);
    int it = 0;
    while (!ready4(v) && ++it < SPIN_LIMIT) v = ld_poll4(kp);
    const uint32_t m = max(max(v.x, v.y), max(v.z, v.w));
    const uint32_t wk = __reduce_max_sync(0xffffffffu, m);
    if (lane == 0) sm.win = wk;
  }
  __syncthreads();
  const uint32_t win = sm.win;
  const int wrow = 2047 - (int)(win & 0x7FFu);
  const int wcta = wrow >> 4;
  if (wid < 10 && row == brow && wcta != cta) {
#pragma unroll
    for (int k = 0; k < 4; k++)
      *reinterpret_cast<uint4*>(gout + (size_t)(cta * 16 + row) * D_ + (4 * (4 * gqi + k) + tq) * 8) = outv[k];
  }
  STAMP(7);
  if (cta < N1 + N2) mbar_wait(&sm.mbarw);
  float* xs = &sm.z[0][0][0];
  float* part = xs + 2048;
  if (cta < N1) {
    if (tid < 80) {
      const uint4 v = poll4(&g_cand[wcta][0][tid]);
      float4* xp = reinterpret_cast<float4*>(xs + tid * 8);
      xp[0] = make_float4(lo_f(v.x), hi_f(v.x), lo_f(v.y), hi_f(v.y));
      xp[1] = make_float4(lo_f(v.z), hi_f(v.z), lo_f(v.w), hi_f(v.w));
    }
    __syncthreads();
    const int m = wid / 6, hc = (wid % 6) >> 1, rs = (wid & 1) * 32 + lane;
    float a[8];
#pragma unroll
    for (int j = 0; j < 8; j++) a[j] = 0.f;
#pragma unroll
    for (int it = 0; it < 10; it++) {
      const int r = rs + 64 * it;
      const uint4 wv = sm.w[m * 1920 + r * 3 + hc];
      const float x = xs[r];
      a[0] = fmaf(x, lo_f(wv.x), a[0]); a[1] = fmaf(x, hi_f(wv.x), a[1]);
      a[2] = fmaf(x, lo_f(wv.y), a[2]); a[3] = fmaf(x, hi_f(wv.y), a[3]);
      a[4] = fmaf(x, lo_f(wv.z), a[4]); a[5] = fmaf(x, hi_f(wv.z), a[5]);
      a[6] = fmaf(x, lo_f(wv.w), a[6]); a[7] = fmaf(x, hi_f(wv.w), a[7]);
    }
    {
      const bool up = lane & 16;
#pragma unroll
      for (int j = 0; j < 4; j++) {
        const float send = up ? a[j] : a[j + 4], keep = up ? a[j + 4] : a[j];
        a[j] = keep + __shfl_xor_sync(0xffffffffu, send, 16);
      }
      const bool up2 = lane & 8;
#pragma unroll
      for (int j = 0; j < 2; j++) {
        const float send = up2 ? a[j] : a[j + 2], keep = up2 ? a[j + 2] : a[j];
        a[j] = keep + __shfl_xor_sync(0xffffffffu, send, 8);
      }
      const bool up3 = lane & 4;
      const float send = up3 ? a[0] : a[1], keep = up3 ? a[1] : a[0];
      a[0] = keep + __shfl_xor_sync(0xffffffffu, send, 4);
      a[0] += __shfl_xor_sync(0xffffffffu, a[0], 2);
      a[0] += __shfl_xor_sync(0xffffffffu, a[0], 1);
      if ((lane & 3) == 0) part[wid * 8 + (lane >> 2)] = a[0];
    }
    __syncthreads();
    if (wid == 0) {
      uint32_t bits = 0;
      if (lane < 24) {
        const int hc2 = lane >> 3, j = lane & 7;
        const float gt = rbf(part[(2 * hc2) * 8 + j] + part[(2 * hc2 + 1) * 8 + j]);
        const float up = rbf(part[(6 + 2 * hc2) * 8 + j] + part[(6 + 2 * hc2 + 1) * 8 + j]);
        const float sg = rbf(gt / (1.f + __expf(-gt)));
        bits = __bfloat16_as_ushort(__float2bfloat16_rn(sg * up));
      }
      const uint32_t nb = __shfl_down_sync(0xffffffffu, bits, 1);
      const uint32_t pw = bits | (nb << 16);
      const uint32_t w1 = __shfl_down_sync(0xffffffffu, pw, 2), w2 = __shfl_down_sync(0xffffffffu, pw, 4), w3 = __shfl_down_sync(0xffffffffu, pw, 6);
      if (lane < 24 && (lane & 7) == 0) st_pub4(&g_act[cta * 3 + (lane >> 3)], enc4(make_uint4(pw, w1, w2, w3)));
    }
  } else if (cta < N1 + N2) {
    const int j2 = cta - N1;
    uint4 rowv = make_uint4(0, 0, 0, 0);
    if (tid < 192) {
      const uint4 v = poll4(&g_act[tid]);
      float4* xp = reinterpret_cast<float4*>(xs + tid * 8);
      xp[0] = make_float4(lo_f(v.x), hi_f(v.x), lo_f(v.y), hi_f(v.y));
      xp[1] = make_float4(lo_f(v.z), hi_f(v.z), lo_f(v.w), hi_f(v.w));
    } else if (tid < 196) {
      const int t = tid - 192;
      rowv = poll4(&g_cand[wcta][t >> 1][j2 * 2 + (t & 1)]);
      reinterpret_cast<uint4*>(part + 256)[t] = rowv;
    }
    __syncthreads();
    const int hc = lane & 1, rs = wid * 16 + (lane >> 1);
    float a[8];
#pragma unroll
    for (int j = 0; j < 8; j++) a[j] = 0.f;
#pragma unroll
    for (int it = 0; it < 8; it++) {
      const int r = rs + 192 * it;
      const uint4 wv = sm.w[r * 2 + hc];
      const float x = xs[r];
      a[0] = fmaf(x, lo_f(wv.x), a[0]); a[1] = fmaf(x, hi_f(wv.x), a[1]);
      a[2] = fmaf(x, lo_f(wv.y), a[2]); a[3] = fmaf(x, hi_f(wv.y), a[3]);
      a[4] = fmaf(x, lo_f(wv.z), a[4]); a[5] = fmaf(x, hi_f(wv.z), a[5]);
      a[6] = fmaf(x, lo_f(wv.w), a[6]); a[7] = fmaf(x, hi_f(wv.w), a[7]);
    }
    {
      const bool up = lane & 16;
#pragma unroll
      for (int j = 0; j < 4; j++) {
        const float send = up ? a[j] : a[j + 4], keep = up ? a[j + 4] : a[j];
        a[j] = keep + __shfl_xor_sync(0xffffffffu, send, 16);
      }
      const bool up2 = lane & 8;
#pragma unroll
      for (int j = 0; j < 2; j++) {
        const float send = up2 ? a[j] : a[j + 2], keep = up2 ? a[j + 2] : a[j];
        a[j] = keep + __shfl_xor_sync(0xffffffffu, send, 8);
      }
      const bool up3 = lane & 4;
      const float send = up3 ? a[0] : a[1], keep = up3 ? a[1] : a[0];
      a[0] = keep + __shfl_xor_sync(0xffffffffu, send, 4);
      a[0] += __shfl_xor_sync(0xffffffffu, a[0], 2);
      if ((lane & 2) == 0) part[wid * 16 + hc * 8 + (lane >> 2)] = a[0];
    }
    __syncthreads();
    if (tid < 16) {
      float y = 0.f;
#pragma unroll
      for (int i = 0; i < 12; i++) y += part[i * 16 + tid];
      const uint32_t ord = win >> 16;
      const uint32_t rb = (ord & 0x8000u) ? (ord ^ 0x8000u) : (ord ^ 0xFFFFu);
      const float r = __uint_as_float(rb << 16);
      const float sg = rbf(1.f / (1.f + __expf(-r)));
      const float yy = rbf(rbf(y) * sg);
      const unsigned short* rv = reinterpret_cast<const unsigned short*>(part + 256);
      const float hn = __uint_as_float((uint32_t)rv[tid] << 16), h = __uint_as_float((uint32_t)rv[16 + tid] << 16);
      gout[(size_t)wrow * D_ + j2 * 16 + tid] = __float2bfloat16_rn(h + rbf(hn + yy));
    }
  }
  STAMP(8);
}

}

typedef CUresult (*EncodeFn)(CUtensorMap*, CUtensorMapDataType, cuuint32_t, void*, const cuuint64_t*, const cuuint64_t*,
                             const cuuint32_t*, const cuuint32_t*, CUtensorMapInterleave, CUtensorMapSwizzle,
                             CUtensorMapL2promotion, CUtensorMapFloatOOBfill);

extern "C" void kernel_launch(void* const* d_in, const int* in_sizes, int n_in, void* d_out, int out_size) {
  (void)in_sizes; (void)n_in; (void)out_size;
  static EncodeFn encode = nullptr;
  static CUtensorMap tmg, tmu, tmd;
  static void* cached[3] = {nullptr, nullptr, nullptr};
  if (!encode) {
    cudaFuncSetAttribute(fused_kernel, cudaFuncAttributeMaxDynamicSharedMemorySize, (int)sizeof(Smem));
    void* fn = nullptr;
    cudaDriverEntryPointQueryResult qr;
    cudaGetDriverEntryPoint("cuTensorMapEncodeTiled", &fn, cudaEnableDefault, &qr);
    encode = (EncodeFn)fn;
  }
  if (cached[0] != d_in[8] || cached[1] != d_in[9] || cached[2] != d_in[10]) {
    const cuuint32_t es[2] = {1, 1};
    {
      const cuuint64_t dims[2] = {F_, D_}, strides[1] = {F_ * 2};
      const cuuint32_t box[2] = {24, 160};
      encode(&tmg, CU_TENSOR_MAP_DATA_TYPE_BFLOAT16, 2, d_in[8], dims, strides, box, es, CU_TENSOR_MAP_INTERLEAVE_NONE,
             CU_TENSOR_MAP_SWIZZLE_NONE, CU_TENSOR_MAP_L2_PROMOTION_NONE, CU_TENSOR_MAP_FLOAT_OOB_FILL_NONE);
      encode(&tmu, CU_TENSOR_MAP_DATA_TYPE_BFLOAT16, 2, d_in[9], dims, strides, box, es, CU_TENSOR_MAP_INTERLEAVE_NONE,
             CU_TENSOR_MAP_SWIZZLE_NONE, CU_TENSOR_MAP_L2_PROMOTION_NONE, CU_TENSOR_MAP_FLOAT_OOB_FILL_NONE);
    }
    {
      const cuuint64_t dims[2] = {D_, F_}, strides[1] = {D_ * 2};
      const cuuint32_t box[2] = {16, 256};
      encode(&tmd, CU_TENSOR_MAP_DATA_TYPE_BFLOAT16, 2, d_in[10], dims, strides, box, es, CU_TENSOR_MAP_INTERLEAVE_NONE,
             CU_TENSOR_MAP_SWIZZLE_NONE, CU_TENSOR_MAP_L2_PROMOTION_NONE, CU_TENSOR_MAP_FLOAT_OOB_FILL_NONE);
    }
    cached[0] = d_in[8]; cached[1] = d_in[9]; cached[2] = d_in[10];
  }
  fused_kernel<<<NCTA, NTHR, sizeof(Smem), cudaStreamPerThread>>>(
      tmg, tmu, tmd, (const bf16*)d_in[0], (const bf16*)d_in[1], (const bf16*)d_in[2], (const bf16*)d_in[3],
      (const bf16*)d_in[4], (const bf16*)d_in[5], (const bf16*)d_in[7], (bf16*)d_out);
}
```

```cpp
#include <cuda_runtime.h>
#include <cuda_bf16.h>
#include <cuda.h>
#include <stdint.h>

namespace {

typedef __nv_bfloat16 bf16;
typedef __nv_bfloat162 bf162;

constexpr int S_ = 2048, D_ = 640, F_ = 1536;
constexpr int NCTA = 128, CPC = 5, NTHR = 384;
constexpr int UPAD = 136, USTR = 2192;
constexpr int TABW = 1040;
constexpr int ZPB = 132;
constexpr int QSTR = 648;
constexpr int N1 = 64;
constexpr int N2 = 40;
constexpr int SPIN_LIMIT = 1 << 19;
#define POLL_NS 100
#define H_DELAY 2000
#define Q_DELAY 4500

struct __align__(128) Smem {
  uint32_t tabA[3][2][TABW];
  uint32_t extra[1024];
  uint32_t tabB[2][2][TABW];
  bf16 u[CPC][USTR];
  float z[2][4][ZPB * 16];
  bf16 q[16][QSTR];
  alignas(128) uint4 w[3840];
  uint4 wr[80];
  float2 st[16][5];
  float rp[16][5];
  unsigned long long mbar;
  unsigned long long mbarw;
  unsigned long long mbarkv;
  unsigned long long mbarh;
  uint32_t target;
  uint32_t target2;
  uint32_t best;
  uint32_t win;
};

__device__ uint4 g_kv[D_ * S_ / 8];
__device__ uint4 g_y2[D_ * S_ / 8];
__device__ uint32_t g_keys[NCTA];
__device__ uint4 g_cand[NCTA][2][80];
__device__ uint4 g_act[F_ / 8];
__device__ unsigned int g_ctr;
__device__ unsigned int g_ctr2;
#define STAMP(i)

__device__ __forceinline__ uint32_t smem_u32(const void* p) { return (uint32_t)__cvta_generic_to_shared(p); }
__device__ __forceinline__ void wg_fence() { asm volatile("wgmma.fence.sync.aligned;" ::: "memory"); }
__device__ __forceinline__ void wg_commit() { asm volatile("wgmma.commit_group.sync.aligned;" ::: "memory"); }
template <int N> __device__ __forceinline__ void wg_wait() { asm volatile("wgmma.wait_group.sync.aligned %0;" ::"n"(N) : "memory"); }
__device__ __forceinline__ void bar_sync(int id, int n) { asm volatile("bar.sync %0, %1;" ::"r"(id), "r"(n) : "memory"); }
__device__ __forceinline__ void bar_arrive(int id, int n) { asm volatile("bar.arrive %0, %1;" ::"r"(id), "r"(n) : "memory"); }
__device__ __forceinline__ bf162 u2b(uint32_t u) { return *reinterpret_cast<bf162*>(&u); }
__device__ __forceinline__ uint32_t b2u(bf162 b) { return *reinterpret_cast<uint32_t*>(&b); }
__device__ __forceinline__ float lo_f(uint32_t u) { return __uint_as_float(u << 16); }
__device__ __forceinline__ float hi_f(uint32_t u) { return __uint_as_float(u & 0xFFFF0000u); }
__device__ __forceinline__ float rbf(float x) { return __bfloat162float(__float2bfloat16_rn(x)); }
__device__ __forceinline__ uint32_t pack2(float a, float b) { return b2u(__floats2bfloat162_rn(a, b)); }
__device__ __forceinline__ uint32_t enc(uint32_t w) { return max(~w, 1u); }
__device__ __forceinline__ uint4 enc4(uint4 v) { return make_uint4(enc(v.x), enc(v.y), enc(v.z), enc(v.w)); }
__device__ __forceinline__ uint4 ld_poll4(const uint4* p) {
  uint4 v;
  asm volatile("ld.relaxed.gpu.global.v4.u32 {%0,%1,%2,%3}, [%4];" : "=r"(v.x), "=r"(v.y), "=r"(v.z), "=r"(v.w) : "l"(p) : "memory");
  return v;
}
__device__ __forceinline__ bool ready4(uint4 v) { return v.x != 0u && v.y != 0u && v.z != 0u && v.w != 0u; }
__device__ __forceinline__ uint4 poll4(const uint4* p) {
  uint4 v = ld_poll4(p);
  int it = 0;
  while (!ready4(v) && ++it < SPIN_LIMIT) v = ld_poll4(p);
  return make_uint4(~v.x, ~v.y, ~v.z, ~v.w);
}
__device__ __forceinline__ void st_pub4(uint4* p, uint4 v) {
  asm volatile("st.relaxed.gpu.global.v4.u32 [%0], {%1,%2,%3,%4};" ::"l"(p), "r"(v.x), "r"(v.y), "r"(v.z), "r"(v.w) : "memory");
}
__device__ __forceinline__ void st_pub2(uint2* p, uint32_t a, uint32_t b) {
  asm volatile("st.relaxed.gpu.global.v2.u32 [%0], {%1,%2};" ::"l"(p), "r"(a), "r"(b) : "memory");
}
__device__ __forceinline__ void mma_bf16(float (&c)[4], uint32_t a0, uint32_t a2, uint32_t b0, uint32_t b1) {
  asm volatile("mma.sync.aligned.m16n8k16.row.col.f32.bf16.bf16.f32 {%0,%1,%2,%3}, {%4,%5,%6,%5}, {%7,%8}, {%0,%1,%2,%3};"
               : "+f"(c[0]), "+f"(c[1]), "+f"(c[2]), "+f"(c[3]) : "r"(a0), "r"(0u), "r"(a2), "r"(b0), "r"(b1));
}
__device__ __forceinline__ void mbar_wait(const unsigned long long* bar) {
  const uint32_t mb = smem_u32(bar);
  uint32_t ok = 0;
  int it = 0;
  while (!ok && ++it < SPIN_LIMIT)
    asm volatile("{ .reg .pred p; mbarrier.try_wait.parity.shared.b64 p, [%1], 0; selp.u32 %0, 1, 0, p; }" : "=r"(ok) : "r"(mb) : "memory");
}
__device__ __forceinline__ void bulk_g2s(void* dst, const void* src, uint32_t bytes, const unsigned long long* bar) {
  asm volatile("cp.async.bulk.shared::cluster.global.mbarrier::complete_tx::bytes [%0], [%1], %2, [%3];" ::"r"(smem_u32(dst)),
               "l"(src), "r"(bytes), "r"(smem_u32(bar)) : "memory");
}
__device__ __forceinline__ void mbar_expect(const unsigned long long* bar, uint32_t bytes) {
  asm volatile("mbarrier.arrive.expect_tx.shared.b64 _, [%0], %1;" ::"r"(smem_u32(bar)), "r"(bytes) : "memory");
}
__device__ __forceinline__ float fdivr(float a, float d, float r) {
  float q = a * r;
  float e = fmaf(-q, d, a);
  return fmaf(e, r, q);
}

template <bool FIRST> __device__ __forceinline__ void wgmma32(float (&d)[16], const uint32_t* a, uint64_t desc) {
  if (FIRST) {
    asm volatile("wgmma.mma_async.sync.aligned.m64n32k16.f32.bf16.bf16 {%0,%1,%2,%3,%4,%5,%6,%7,%8,%9,%10,%11,%12,%13,%14,%15}, {%16,%17,%18,%19}, %20, 0, 1, 1, 0;"
                 : "+f"(d[0]), "+f"(d[1]), "+f"(d[2]), "+f"(d[3]), "+f"(d[4]), "+f"(d[5]), "+f"(d[6]), "+f"(d[7]),
                   "+f"(d[8]), "+f"(d[9]), "+f"(d[10]), "+f"(d[11]), "+f"(d[12]), "+f"(d[13]), "+f"(d[14]), "+f"(d[15])
                 : "r"(a[0]), "r"(a[1]), "r"(a[2]), "r"(a[3]), "l"(desc));
  } else {
    asm volatile("wgmma.mma_async.sync.aligned.m64n32k16.f32.bf16.bf16 {%0,%1,%2,%3,%4,%5,%6,%7,%8,%9,%10,%11,%12,%13,%14,%15}, {%16,%17,%18,%19}, %20, 1, 1, 1, 0;"
                 : "+f"(d[0]), "+f"(d[1]), "+f"(d[2]), "+f"(d[3]), "+f"(d[4]), "+f"(d[5]), "+f"(d[6]), "+f"(d[7]),
                   "+f"(d[8]), "+f"(d[9]), "+f"(d[10]), "+f"(d[11]), "+f"(d[12]), "+f"(d[13]), "+f"(d[14]), "+f"(d[15])
                 : "r"(a[0]), "r"(a[1]), "r"(a[2]), "r"(a[3]), "l"(desc));
  }
}

template <int G> __device__ __forceinline__ void load_a(uint32_t (&a)[8], const uint32_t* tp) {
#pragma unroll
  for (int q = 0; q < 2; q++) {
    const int e = 2 * G + q;
    a[4 * q + 0] = tp[-64 * e];
    a[4 * q + 1] = tp[-64 * e - 32];
    a[4 * q + 2] = tp[-64 * e + 4];
    a[4 * q + 3] = tp[-64 * e - 28];
  }
}
__device__ __forceinline__ void load_a_all(uint32_t (&a)[8][8], const uint32_t* tp) {
  load_a<0>(a[0], tp); load_a<1>(a[1], tp); load_a<2>(a[2], tp); load_a<3>(a[3], tp);
  load_a<4>(a[4], tp); load_a<5>(a[5], tp); load_a<6>(a[6], tp); load_a<7>(a[7], tp);
}
template <int G> __device__ __forceinline__ void issue_g(float (&acc)[8][16], uint32_t (&a)[8], uint64_t desc0) {
  wg_fence();
#pragma unroll
  for (int q = 0; q < 2; q++) {
#pragma unroll
    for (int b = G; b < 8; b++) {
      const int delta = 2 * b - (2 * G + q);
      if (G == 0 && q == 0) wgmma32<true>(acc[b], &a[4 * q], desc0 + (uint64_t)(int64_t)(16 * delta));
      else wgmma32<false>(acc[b], &a[4 * q], desc0 + (uint64_t)(int64_t)(16 * delta));
    }
  }
  wg_commit();
}
template <int B> __device__ __forceinline__ void fence_blk(float (&acc)[8][16]) {
#pragma unroll
  for (int i = 0; i < 16; i++) asm volatile("" : "+f"(acc[B][i])::"memory");
}
__device__ __forceinline__ void fence_a(uint32_t (&a)[8]) {
#pragma unroll
  for (int i = 0; i < 8; i++) asm volatile("" : "+r"(a[i])::"memory");
}
template <int B> __device__ __forceinline__ void sts_blk(float (&acc)[8][16], float* zw, int off_even, int off_odd) {
#pragma unroll
  for (int jj = 0; jj < 4; jj++) {
    const int j = 4 * B + jj;
    float p0 = acc[B][4 * jj + 0], p1 = acc[B][4 * jj + 1];
    if (jj > 0) { p0 += acc[B][4 * (jj - 1) + 2]; p1 += acc[B][4 * (jj - 1) + 3]; }
    else if (B > 0) { p0 += acc[B > 0 ? B - 1 : 0][14]; p1 += acc[B > 0 ? B - 1 : 0][15]; }
    zw[64 * j + off_even] = p0;
    zw[64 * j + off_odd] = p1;
  }
}
__device__ __forceinline__ int tab_off(int c) { return c == 4 ? 0 : (c + 1) * 2 * TABW + (c >= 2 ? 1024 : 0); }
__device__ __forceinline__ int tile_perm(int ch) { return ch ^ (((ch >> 3) & 3) << 1); }

__device__ __forceinline__ void wait_cleared(uint32_t target) {
  uint32_t v;
  int it = 0;
  do {
    asm volatile("ld.acquire.gpu.global.u32 %0, [%1];" : "=r"(v) : "l"(&g_ctr) : "memory");
  } while ((int)(v - target) < 0 && ++it < SPIN_LIMIT);
}

__device__ __forceinline__ void ln_q_rows(Smem& sm, bf16* qn_s, int row, int lane) {
      const uint32_t* qp = reinterpret_cast<const uint32_t*>(&sm.q[row][0]);
      uint32_t qa[10], qb[10];
      float sa = 0.f, sb = 0.f;
#pragma unroll
      for (int i = 0; i < 10; i++) {
        qa[i] = qp[lane + 32 * i]; qb[i] = qp[QSTR / 2 + lane + 32 * i];
        sa += lo_f(qa[i]) + hi_f(qa[i]); sb += lo_f(qb[i]) + hi_f(qb[i]);
      }
#pragma unroll
      for (int o = 16; o > 0; o >>= 1) { sa += __shfl_xor_sync(0xffffffffu, sa, o); sb += __shfl_xor_sync(0xffffffffu, sb, o); }
      sa *= (1.f / D_); sb *= (1.f / D_);
      float ma = 0.f, mb2 = 0.f;
#pragma unroll
      for (int i = 0; i < 10; i++) {
        const float x = lo_f(qa[i]) - sa, y = hi_f(qa[i]) - sa, z = lo_f(qb[i]) - sb, t = hi_f(qb[i]) - sb;
        ma = fmaf(x, x, fmaf(y, y, ma)); mb2 = fmaf(z, z, fmaf(t, t, mb2));
      }
#pragma unroll
      for (int o = 16; o > 0; o >>= 1) { ma += __shfl_xor_sync(0xffffffffu, ma, o); mb2 += __shfl_xor_sync(0xffffffffu, mb2, o); }
      const float da = rbf(sqrtf(rbf(rbf(ma * (1.f / D_)) + 1e-5f))), db = rbf(sqrtf(rbf(rbf(mb2 * (1.f / D_)) + 1e-5f)));
      const float ra = 1.f / da, rb = 1.f / db;
      const bf162 ma2 = __float2bfloat162_rn(sa), mb3 = __float2bfloat162_rn(sb);
      uint32_t* np = reinterpret_cast<uint32_t*>(qn_s + row * QSTR);
#pragma unroll
      for (int i = 0; i < 10; i++) {
        const uint32_t d = b2u(__hsub2_rn(u2b(qa[i]), ma2)), e = b2u(__hsub2_rn(u2b(qb[i]), mb3));
        np[lane + 32 * i] = pack2(fdivr(lo_f(d), da, ra), fdivr(hi_f(d), da, ra));
        np[QSTR / 2 + lane + 32 * i] = pack2(fdivr(lo_f(e), db, rb), fdivr(hi_f(e), db, rb));
      }
}

__global__ void __launch_bounds__(NTHR, 1)
fused_kernel(const __grid_constant__ CUtensorMap tmg, const __grid_constant__ CUtensorMap tmu,
             const __grid_constant__ CUtensorMap tmd, const bf16* __restrict__ gq, const bf16* __restrict__ gk, const bf16* __restrict__ gv,
             const bf16* __restrict__ gsk, const bf16* __restrict__ gh, const bf16* __restrict__ gD,
             const bf16* __restrict__ gwr, bf16* __restrict__ gout) {
  extern __shared__ __align__(128) unsigned char smraw[];
  Smem& sm = *reinterpret_cast<Smem*>(smraw);
  const int tid = threadIdx.x;
  const int cta = blockIdx.x;
  const int c0 = cta * CPC;
  const int lane = tid & 31;
  const int wid = tid >> 5;
  STAMP(0);
  const long long tstart = clock64();

  {
    uint4* hs = reinterpret_cast<uint4*>(&sm.z[0][0][0]);
    if (tid < 320) {
      const int oc = tid >> 2;
      const int r0 = cta * 16 + (tid & 3) * 4;
      uint4 kk[7], vv[4], sk[4];
      const uint4* kp = reinterpret_cast<const uint4*>(gk) + (size_t)r0 * 80 + oc;
      const uint4* vp = reinterpret_cast<const uint4*>(gv) + (size_t)r0 * 80 + oc;
#pragma unroll
      for (int i = 0; i < 7; i++) kk[i] = (i >= 3 || r0 > 0) ? __ldg(kp + (i - 3) * 80) : make_uint4(0, 0, 0, 0);
#pragma unroll
      for (int i = 0; i < 4; i++) vv[i] = __ldg(vp + i * 80);
#pragma unroll
      for (int i = 0; i < 4; i++) sk[i] = __ldg(reinterpret_cast<const uint4*>(gsk) + oc * 4 + i);
      STAMP(9);
#pragma unroll
      for (int p = 0; p < 4; p++) {
        const bf162 w0 = u2b(__byte_perm(sk[p].x, sk[p].z, 0x5410)), w1 = u2b(__byte_perm(sk[p].x, sk[p].z, 0x7632));
        const bf162 w2 = u2b(__byte_perm(sk[p].y, sk[p].w, 0x5410)), w3 = u2b(__byte_perm(sk[p].y, sk[p].w, 0x7632));
        uint32_t kv[4];
#pragma unroll
        for (int i = 0; i < 4; i++) {
          const uint32_t k0 = p == 0 ? kk[i].x : p == 1 ? kk[i].y : p == 2 ? kk[i].z : kk[i].w;
          const uint32_t k1 = p == 0 ? kk[i + 1].x : p == 1 ? kk[i + 1].y : p == 2 ? kk[i + 1].z : kk[i + 1].w;
          const uint32_t k2 = p == 0 ? kk[i + 2].x : p == 1 ? kk[i + 2].y : p == 2 ? kk[i + 2].z : kk[i + 2].w;
          const uint32_t k3 = p == 0 ? kk[i + 3].x : p == 1 ? kk[i + 3].y : p == 2 ? kk[i + 3].z : kk[i + 3].w;
          const uint32_t vx = p == 0 ? vv[i].x : p == 1 ? vv[i].y : p == 2 ? vv[i].z : vv[i].w;
          bf162 a = __hmul2_rn(u2b(k0), w3);
          a = __hadd2_rn(a, __hmul2_rn(u2b(k1), w2));
          a = __hadd2_rn(a, __hmul2_rn(u2b(k2), w1));
          a = __hadd2_rn(a, __hmul2_rn(u2b(k3), w0));
          kv[i] = b2u(__hmul2_rn(a, u2b(vx)));
        }
        uint2* dst = reinterpret_cast<uint2*>(g_kv) + (size_t)(oc * 8 + 2 * p) * 512 + (r0 >> 2);
        st_pub2(dst, enc(__byte_perm(kv[0], kv[1], 0x5410)), enc(__byte_perm(kv[2], kv[3], 0x5410)));
        st_pub2(dst + 512, enc(__byte_perm(kv[0], kv[1], 0x7632)), enc(__byte_perm(kv[2], kv[3], 0x7632)));
      }
      STAMP(10);
      bar_sync(6, 384);
      if (tid == 0) {
        const unsigned old = atomicAdd(&g_ctr2, 1u);
        sm.target2 = (old / NCTA + 1u) * NCTA;
      }
    } else {
      if (tid == 352) {
        asm volatile("mbarrier.init.shared.b64 [%0], 1;" ::"r"(smem_u32(&sm.mbarh)) : "memory");
        asm volatile("mbarrier.init.shared.b64 [%0], 1;" ::"r"(smem_u32(&sm.mbar)) : "memory");
        asm volatile("mbarrier.init.shared.b64 [%0], 1;" ::"r"(smem_u32(&sm.mbarw)) : "memory");
        asm volatile("fence.proxy.async.shared::cta;" ::: "memory");
        while (clock64() - tstart < H_DELAY) {}
        mbar_expect(&sm.mbarh, CPC * S_ * 2);
        bulk_g2s(hs, gh + (size_t)c0 * S_, CPC * S_ * 2, &sm.mbarh);
      }
      __syncwarp();
      const int t0 = tid - 320;
      const uint4 zz = make_uint4(0, 0, 0, 0);
#pragma unroll 4
      for (int i = 0; i < 20; i++) g_y2[cta * 1280 + t0 + 64 * i] = zz;
      (&g_cand[cta][0][0])[t0] = zz;
      (&g_cand[cta][0][0])[64 + t0] = zz;
      if (t0 < 32) (&g_cand[cta][0][0])[128 + t0] = zz;
      else if (t0 < 35) { if (cta < N1) g_act[cta * 3 + (t0 - 32)] = zz; }
      else if (t0 == 35) g_keys[cta] = 0u;
      for (int t = t0; t < CPC * 17; t += 64) *reinterpret_cast<uint4*>(&sm.u[t / 17][(t % 17) * 8]) = zz;
      if (t0 < 40) *reinterpret_cast<uint4*>(&sm.tabA[0][0][0] + tab_off(t0 >> 3) + ((t0 >> 2) & 1) * TABW + 1024 + 4 * (t0 & 3)) = zz;
      bar_sync(5, 64);
      bar_arrive(6, 384);
      if (tid == 352) {
        __threadfence();
        const unsigned old = atomicAdd(&g_ctr, 1u);
        sm.target = (old / NCTA + 1u) * NCTA;
        while (clock64() - tstart < Q_DELAY) {}
        mbar_expect(&sm.mbar, 17 * D_ * 2);
#pragma unroll 1
        for (int r = 0; r < 16; r++) bulk_g2s(&sm.q[r][0], gq + (size_t)(cta * 16 + r) * D_, D_ * 2, &sm.mbar);
        bulk_g2s(&sm.wr[0], gwr, D_ * 2, &sm.mbar);
      }
      __syncwarp();
    }
    mbar_wait(&sm.mbarh);
#pragma unroll
    for (int i = 0; i < 4; i++) {
      const int t = (NTHR - 1 - tid) + NTHR * i;
      if (t < CPC * 256) {
        uint32_t* tb = &sm.tabA[0][0][0] + tab_off(t >> 8) + (255 - (t & 255)) * 4;
        const uint4 h = hs[t];
        const uint32_t hp = (t & 255) ? reinterpret_cast<const uint32_t*>(hs)[4 * t - 1] : 0u;
        uint4 r1, rr;
        r1.x = __byte_perm(h.w, 0, 0x1032); r1.y = __byte_perm(h.z, 0, 0x1032);
        r1.z = __byte_perm(h.y, 0, 0x1032); r1.w = __byte_perm(h.x, 0, 0x1032);
        rr.x = __byte_perm(h.w, h.z, 0x7610); rr.y = __byte_perm(h.z, h.y, 0x7610);
        rr.z = __byte_perm(h.y, h.x, 0x7610); rr.w = __byte_perm(h.x, hp, 0x7610);
        *reinterpret_cast<uint4*>(tb) = rr;
        *reinterpret_cast<uint4*>(tb + TABW) = r1;
      }
    }
    if (tid == 0) {
      const unsigned target = sm.target2;
      uint32_t v;
      int it = 0;
      do {
        asm volatile("ld.relaxed.gpu.global.u32 %0, [%1];" : "=r"(v) : "l"(&g_ctr2) : "memory");
      } while ((int)(v - target) < 0 && ++it < SPIN_LIMIT);
    }
    STAMP(12);
  }
  __syncthreads();
  {
    uint4 v[4];
    uint4* src = g_kv + c0 * 256 + tid;
#pragma unroll
    for (int i = 0; i < 4; i++) if (i < 3 || tid < 128) v[i] = ld_poll4(src + NTHR * i);
    if (tid >= 256) {
      const int t0 = tid - 256;
      *reinterpret_cast<uint4*>(&sm.z[t0 >> 6][(t0 >> 4) & 3][(t0 & 15) * 4]) = make_uint4(0, 0, 0, 0);
    }
#pragma unroll
    for (int i = 0; i < 4; i++) {
      if (i < 3 || tid < 128) {
        int it = 0;
        while (!ready4(v[i]) && ++it < SPIN_LIMIT) { __nanosleep(POLL_NS); v[i] = ld_poll4(src + NTHR * i); }
        const int t = tid + NTHR * i;
        *reinterpret_cast<uint4*>(&sm.u[t >> 8][UPAD + (t & 255) * 8]) = make_uint4(~v[i].x, ~v[i].y, ~v[i].z, ~v[i].w);
      }
    }
    STAMP(11);
    asm volatile("fence.proxy.async.shared::cta;" ::: "memory");
    __syncthreads();
#pragma unroll
    for (int i = 0; i < 4; i++) if (i < 3 || tid < 128) src[NTHR * i] = make_uint4(0, 0, 0, 0);
  }
  STAMP(1);

  const int wg = __shfl_sync(0xffffffffu, tid >> 7, 0);
  const int wtid = tid & 127;
  uint4* tile = reinterpret_cast<uint4*>(&sm.tabB[0][0][0]);
  bf16* qn_s = reinterpret_cast<bf16*>(&sm.tabA[1][0][0]);
  if (wg < 2) {
    asm volatile("setmaxnreg.inc.sync.aligned.u32 224;");
    const int w = (tid >> 5) & 3, g = lane >> 2, tq = lane & 3;
    float* zw = sm.z[wg][w];
    const int sw = 3 * (((tq + w) >> 1) & 1);
    const int off_even = 16 * (tq + w) + 4 * ((0 + (g >> 2)) ^ sw) + (g & 3);
    const int off_odd = 16 * (tq + w) + 4 * ((2 + (g >> 2)) ^ sw) + (g & 3);
    uint32_t a[8][8];
    const uint32_t* tp0 = &sm.tabA[0][g & 1][1019 - 8 * w - (g >> 1) + tq];
    load_a_all(a, tp0 + tab_off(wg));
    if (wg == 0) bar_arrive(7, 384);
    else {
      mbar_wait(&sm.mbar);
      bar_sync(7, 384);
      ln_q_rows(sm, qn_s, w * 2, lane);
    }
    float acc[8][16];
#pragma unroll
    for (int b = 0; b < 8; b++)
#pragma unroll
      for (int i = 0; i < 16; i++) acc[b][i] = 0.f;
#pragma unroll 1
    for (int c = wg; c < CPC; c += 2) {
      const uint64_t desc = (uint64_t)((smem_u32(&sm.u[c][UPAD - 8]) & 0x3FFFF) >> 4) | ((uint64_t)1 << 16) | ((uint64_t)8 << 32);
      if (c > 0) bar_sync(1 + wg, 256);
      issue_g<0>(acc, a[0], desc);
      issue_g<1>(acc, a[1], desc);
      issue_g<2>(acc, a[2], desc);
      issue_g<3>(acc, a[3], desc);
      issue_g<4>(acc, a[4], desc);
      issue_g<5>(acc, a[5], desc);
      if (c + 1 < CPC) bar_arrive(1 + (wg ^ 1), 256);
      issue_g<6>(acc, a[6], desc);
      issue_g<7>(acc, a[7], desc);
      if (c >= 2) bar_sync(5 + wg, 256);
      wg_wait<4>();
      fence_blk<0>(acc); fence_blk<1>(acc); fence_blk<2>(acc); fence_blk<3>(acc);
      sts_blk<0>(acc, zw, off_even, off_odd);
      sts_blk<1>(acc, zw, off_even, off_odd);
      sts_blk<2>(acc, zw, off_even, off_odd);
      sts_blk<3>(acc, zw, off_even, off_odd);
      wg_wait<0>();
      fence_blk<4>(acc); fence_blk<5>(acc); fence_blk<6>(acc); fence_blk<7>(acc);
#pragma unroll
      for (int i = 0; i < 8; i++) fence_a(a[i]);
      sts_blk<4>(acc, zw, off_even, off_odd);
      sts_blk<5>(acc, zw, off_even, off_odd);
      sts_blk<6>(acc, zw, off_even, off_odd);
      sts_blk<7>(acc, zw, off_even, off_odd);
      bar_arrive(3 + wg, 256);
      if (c + 2 < CPC) load_a_all(a, tp0 + tab_off(c + 2));
    }
    STAMP(2 + wg);
    asm volatile("setmaxnreg.dec.sync.aligned.u32 168;");
    if (wg == 1) {
#pragma unroll 1
      for (int cc = 0; cc < 4; cc++) {
        const int ch = wtid * 5 + cc;
        const uint4* src = g_y2 + cta * 1280 + ch * 2;
        uint4 v0 = ld_poll4(src), v1 = ld_poll4(src + 1);
        int it = 0;
        while (!ready4(v0) && ++it < SPIN_LIMIT) v0 = ld_poll4(src);
        while (!ready4(v1) && ++it < SPIN_LIMIT) v1 = ld_poll4(src + 1);
        const int pc = tile_perm(ch);
        tile[pc] = make_uint4(~v0.x, ~v0.y, ~v0.z, ~v0.w);
        tile[640 + pc] = make_uint4(~v1.x, ~v1.y, ~v1.z, ~v1.w);
      }
    }
  } else {
    asm volatile("setmaxnreg.dec.sync.aligned.u32 56;");
    if (wtid == 32) {
      const uint32_t mw = smem_u32(&sm.mbarw);
      if (cta < N1) {
        asm volatile("mbarrier.arrive.expect_tx.shared.b64 _, [%0], %1;" ::"r"(mw), "r"(3840 * 16) : "memory");
#pragma unroll 1
        for (int i = 0; i < 4; i++) {
          asm volatile("cp.async.bulk.tensor.2d.shared::cluster.global.mbarrier::complete_tx::bytes [%0], [%1, {%3, %4}], [%2];" ::"r"(smem_u32(&sm.w[i * 480])),
                       "l"(&tmg), "r"(mw), "r"(cta * 24), "r"(i * 160) : "memory");
          asm volatile("cp.async.bulk.tensor.2d.shared::cluster.global.mbarrier::complete_tx::bytes [%0], [%1, {%3, %4}], [%2];" ::"r"(smem_u32(&sm.w[1920 + i * 480])),
                       "l"(&tmu), "r"(mw), "r"(cta * 24), "r"(i * 160) : "memory");
        }
      } else if (cta < N1 + N2) {
        asm volatile("mbarrier.arrive.expect_tx.shared.b64 _, [%0], %1;" ::"r"(mw), "r"(3072 * 16) : "memory");
#pragma unroll 1
        for (int i = 0; i < 6; i++)
          asm volatile("cp.async.bulk.tensor.2d.shared::cluster.global.mbarrier::complete_tx::bytes [%0], [%1, {%3, %4}], [%2];" ::"r"(smem_u32(&sm.w[i * 512])),
                       "l"(&tmd), "r"(mw), "r"((cta - N1) * 16), "r"(i * 256) : "memory");
      }
    }
    mbar_wait(&sm.mbar);
    bar_sync(7, 384);
    ln_q_rows(sm, qn_s, 8 + (wid - 8) * 2, lane);
    if (wtid == 0) wait_cleared(sm.target);
    const int rpb = wtid >> 1, re2 = wtid & 1;
    const int rsw = 3 * ((rpb >> 1) & 1);
    const int roff0 = 16 * rpb + 4 * ((2 * re2 + 0) ^ rsw);
    const int roff1 = 16 * rpb + 4 * ((2 * re2 + 1) ^ rsw);
    const uint32_t dvl = reinterpret_cast<const unsigned short*>(gD)[c0 + (lane < CPC ? lane : 0)];
#pragma unroll 1
    for (int c = 0; c < CPC; c++) {
      const int zg = c & 1;
      const uint32_t dvc = __shfl_sync(0xffffffffu, dvl, c);
      const bf162 d2 = u2b(dvc | (dvc << 16));
      bar_sync(3 + zg, 256);
#pragma unroll
      for (int half = 0; half < 2; half++) {
        const float* zb = sm.z[zg][0] + half * 1024;
        float4 x[4][2];
#pragma unroll
        for (int ww = 0; ww < 4; ww++) {
          x[ww][0] = *reinterpret_cast<const float4*>(zb + ww * ZPB * 16 + roff0);
          x[ww][1] = *reinterpret_cast<const float4*>(zb + ww * ZPB * 16 + roff1);
        }
        const int sidx = half * 1024 + wtid * 8;
        const uint4 kvv = *reinterpret_cast<const uint4*>(&sm.u[c][UPAD + sidx]);
        if (half == 1 && c + 2 < CPC) bar_arrive(5 + zg, 256);
        uint4 o;
        o.x = pack2((x[0][0].x + x[1][0].x) + (x[2][0].x + x[3][0].x), (x[0][0].y + x[1][0].y) + (x[2][0].y + x[3][0].y));
        o.y = pack2((x[0][0].z + x[1][0].z) + (x[2][0].z + x[3][0].z), (x[0][0].w + x[1][0].w) + (x[2][0].w + x[3][0].w));
        o.z = pack2((x[0][1].x + x[1][1].x) + (x[2][1].x + x[3][1].x), (x[0][1].y + x[1][1].y) + (x[2][1].y + x[3][1].y));
        o.w = pack2((x[0][1].z + x[1][1].z) + (x[2][1].z + x[3][1].z), (x[0][1].w + x[1][1].w) + (x[2][1].w + x[3][1].w));
        o.x = b2u(__hadd2_rn(u2b(o.x), __hmul2_rn(u2b(kvv.x), d2)));
        o.y = b2u(__hadd2_rn(u2b(o.y), __hmul2_rn(u2b(kvv.y), d2)));
        o.z = b2u(__hadd2_rn(u2b(o.z), __hmul2_rn(u2b(kvv.z), d2)));
        o.w = b2u(__hadd2_rn(u2b(o.w), __hmul2_rn(u2b(kvv.w), d2)));
        st_pub4(g_y2 + ((64 * half + rpb) * 640 + c0 + c) * 2 + re2, enc4(o));
      }
    }
    STAMP(4);
    asm volatile("setmaxnreg.inc.sync.aligned.u32 168;");
  }

  if (tid < 128 || tid >= 256) {
    const int t = tid < 128 ? tid : tid - 128;
    const int ch = (t >> 1) * 5 + 4, hh = t & 1;
    const uint4 v = poll4(g_y2 + cta * 1280 + ch * 2 + hh);
    tile[hh * 640 + tile_perm(ch)] = v;
  }
  __syncthreads();
  STAMP(5);

  const int g = lane >> 2, tq = lane & 3;
  const int hh = wid & 1, gqi = wid >> 1;
  const int row = hh * 8 + g;
  uint32_t hreg[16], hnreg[16];
  if (wid < 10) {
    float cs[4] = {0.f, 0.f, 0.f, 0.f};
#pragma unroll
    for (int k = 0; k < 4; k++) {
      const int base = 32 * (4 * gqi + k);
      const int lch = base + 8 * ((lane & 7) >> 1) + 2 * (lane >> 3) + (lane & 1);
      uint32_t y[4];
      asm volatile("ldmatrix.sync.aligned.m8n8.x4.trans.shared.b16 {%0,%1,%2,%3}, [%4];"
                   : "=r"(y[0]), "=r"(y[1]), "=r"(y[2]), "=r"(y[3]) : "r"(smem_u32(&tile[hh * 640 + tile_perm(lch)])) : "memory");
      const uint4 qv4 = *reinterpret_cast<const uint4*>(&sm.q[row][base + 8 * tq]);
      const uint4 qn4 = *reinterpret_cast<const uint4*>(qn_s + row * QSTR + base + 8 * tq);
      hreg[4 * k + 0] = b2u(__hadd2_rn(u2b(qv4.x), __hmul2_rn(u2b(qn4.x), u2b(y[0]))));
      hreg[4 * k + 1] = b2u(__hadd2_rn(u2b(qv4.y), __hmul2_rn(u2b(qn4.y), u2b(y[1]))));
      hreg[4 * k + 2] = b2u(__hadd2_rn(u2b(qv4.z), __hmul2_rn(u2b(qn4.z), u2b(y[2]))));
      hreg[4 * k + 3] = b2u(__hadd2_rn(u2b(qv4.w), __hmul2_rn(u2b(qn4.w), u2b(y[3]))));
      mma_bf16(cs, hreg[4 * k + 0], hreg[4 * k + 1], 0x3F803F80u, 0x3F803F80u);
      mma_bf16(cs, hreg[4 * k + 2], hreg[4 * k + 3], 0x3F803F80u, 0x3F803F80u);
    }
    const float mean = cs[0] * (1.f / 128.f);
    float m2a = 0.f, m2b = 0.f;
#pragma unroll
    for (int i = 0; i < 16; i++) {
      const float a = lo_f(hreg[i]) - mean, b = hi_f(hreg[i]) - mean;
      m2a = fmaf(a, a, m2a); m2b = fmaf(b, b, m2b);
    }
    float m2 = m2a + m2b;
    m2 += __shfl_xor_sync(0xffffffffu, m2, 1);
    m2 += __shfl_xor_sync(0xffffffffu, m2, 2);
    if (tq == 0) sm.st[row][gqi] = make_float2(mean, m2);
  }
  STAMP(13);
  __syncthreads();
  if (wid < 10) {
    float mean = 0.f, m2 = 0.f;
    float2 p[5];
#pragma unroll
    for (int i = 0; i < 5; i++) { p[i] = sm.st[row][i]; mean += p[i].x; }
    mean *= 0.2f;
#pragma unroll
    for (int i = 0; i < 5; i++) { const float dl = p[i].x - mean; m2 += p[i].y + 128.f * dl * dl; }
    const float hd = rbf(sqrtf(rbf(rbf(m2 * (1.f / D_)) + 1e-5f)));
    const float hr = 1.f / hd;
    const bf162 hm2 = __float2bfloat162_rn(mean);
    float cr[4] = {0.f, 0.f, 0.f, 0.f};
#pragma unroll
    for (int k = 0; k < 4; k++) {
      const uint4 w4 = sm.wr[4 * (4 * gqi + k) + tq];
#pragma unroll
      for (int i = 0; i < 4; i++) {
        const uint32_t d = b2u(__hsub2_rn(u2b(hreg[4 * k + i]), hm2));
        hnreg[4 * k + i] = pack2(fdivr(lo_f(d), hd, hr), fdivr(hi_f(d), hd, hr));
      }
      mma_bf16(cr, hnreg[4 * k + 0], hnreg[4 * k + 1], w4.x, w4.y);
      mma_bf16(cr, hnreg[4 * k + 2], hnreg[4 * k + 3], w4.z, w4.w);
    }
    if (tq == 0) sm.rp[row][gqi] = cr[0];
  }
  STAMP(14);
  __syncthreads();
  uint32_t best;
  {
    const int rr = lane & 15;
    const float r = ((sm.rp[rr][0] + sm.rp[rr][1]) + (sm.rp[rr][2] + sm.rp[rr][3])) + sm.rp[rr][4];
    const uint32_t bits = __bfloat16_as_ushort(__float2bfloat16_rn(r));
    const uint32_t ord = (bits & 0x8000u) ? (bits ^ 0xFFFFu) : (bits ^ 0x8000u);
    const uint32_t key = (ord << 16) | 0x8000u | (uint32_t)(2047 - (cta * 16 + rr));
    best = __reduce_max_sync(0xffffffffu, key);
  }
  if (tid == 352) asm volatile("st.relaxed.gpu.global.u32 [%0], %1;" ::"l"(&g_keys[cta]), "r"(best) : "memory");
  STAMP(15);
  const int brow = (2047 - (int)(best & 0x7FFu)) - cta * 16;
  uint4 outv[4];
  if (wid < 10) {
#pragma unroll
    for (int k = 0; k < 4; k++) {
      outv[k].x = b2u(__hadd2_rn(u2b(hreg[4 * k + 0]), u2b(hnreg[4 * k + 0])));
      outv[k].y = b2u(__hadd2_rn(u2b(hreg[4 * k + 1]), u2b(hnreg[4 * k + 1])));
      outv[k].z = b2u(__hadd2_rn(u2b(hreg[4 * k + 2]), u2b(hnreg[4 * k + 2])));
      outv[k].w = b2u(__hadd2_rn(u2b(hreg[4 * k + 3]), u2b(hnreg[4 * k + 3])));
      const int chunk = 4 * (4 * gqi + k) + tq;
      if (row == brow) {
        st_pub4(&g_cand[cta][0][chunk], enc4(make_uint4(hnreg[4 * k], hnreg[4 * k + 1], hnreg[4 * k + 2], hnreg[4 * k + 3])));
        st_pub4(&g_cand[cta][1][chunk], enc4(make_uint4(hreg[4 * k], hreg[4 * k + 1], hreg[4 * k + 2], hreg[4 * k + 3])));
      } else {
        *reinterpret_cast<uint4*>(gout + (size_t)(cta * 16 + row) * D_ + chunk * 8) = outv[k];
      }
    }
  }
  STAMP(6);
  if (wid == 11) {
    const uint4* kp = reinterpret_cast<const uint4*>(g_keys) + lane;
    uint4 v = ld_poll4(kp);
    int it = 0;
    while (!ready4(v) && ++it < SPIN_LIMIT) v = ld_poll4(kp);
    const uint32_t m = max(max(v.x, v.y), max(v.z, v.w));
    const uint32_t wk = __reduce_max_sync(0xffffffffu, m);
    if (lane == 0) sm.win = wk;
  }
  __syncthreads();
  const uint32_t win = sm.win;
  const int wrow = 2047 - (int)(win & 0x7FFu);
  const int wcta = wrow >> 4;
  if (wid < 10 && row == brow && wcta != cta) {
#pragma unroll
    for (int k = 0; k < 4; k++)
      *reinterpret_cast<uint4*>(gout + (size_t)(cta * 16 + row) * D_ + (4 * (4 * gqi + k) + tq) * 8) = outv[k];
  }
  STAMP(7);
  if (cta < N1 + N2) mbar_wait(&sm.mbarw);
  float* xs = &sm.z[0][0][0];
  float* part = xs + 2048;
  if (cta < N1) {
    if (tid < 80) {
      const uint4 v = poll4(&g_cand[wcta][0][tid]);
      float4* xp = reinterpret_cast<float4*>(xs + tid * 8);
      xp[0] = make_float4(lo_f(v.x), hi_f(v.x), lo_f(v.y), hi_f(v.y));
      xp[1] = make_float4(lo_f(v.z), hi_f(v.z), lo_f(v.w), hi_f(v.w));
    }
    __syncthreads();
    const int m = wid / 6, hc = (wid % 6) >> 1, rs = (wid & 1) * 32 + lane;
    float a[8];
#pragma unroll
    for (int j = 0; j < 8; j++) a[j] = 0.f;
#pragma unroll
    for (int it = 0; it < 10; it++) {
      const int r = rs + 64 * it;
      const uint4 wv = sm.w[m * 1920 + r * 3 + hc];
      const float x = xs[r];
      a[0] = fmaf(x, lo_f(wv.x), a[0]); a[1] = fmaf(x, hi_f(wv.x), a[1]);
      a[2] = fmaf(x, lo_f(wv.y), a[2]); a[3] = fmaf(x, hi_f(wv.y), a[3]);
      a[4] = fmaf(x, lo_f(wv.z), a[4]); a[5] = fmaf(x, hi_f(wv.z), a[5]);
      a[6] = fmaf(x, lo_f(wv.w), a[6]); a[7] = fmaf(x, hi_f(wv.w), a[7]);
    }
    {
      const bool up = lane & 16;
#pragma unroll
      for (int j = 0; j < 4; j++) {
        const float send = up ? a[j] : a[j + 4], keep = up ? a[j + 4] : a[j];
        a[j] = keep + __shfl_xor_sync(0xffffffffu, send, 16);
      }
      const bool up2 = lane & 8;
#pragma unroll
      for (int j = 0; j < 2; j++) {
        const float send = up2 ? a[j] : a[j + 2], keep = up2 ? a[j + 2] : a[j];
        a[j] = keep + __shfl_xor_sync(0xffffffffu, send, 8);
      }
      const bool up3 = lane & 4;
      const float send = up3 ? a[0] : a[1], keep = up3 ? a[1] : a[0];
      a[0] = keep + __shfl_xor_sync(0xffffffffu, send, 4);
      a[0] += __shfl_xor_sync(0xffffffffu, a[0], 2);
      a[0] += __shfl_xor_sync(0xffffffffu, a[0], 1);
      if ((lane & 3) == 0) part[wid * 8 + (lane >> 2)] = a[0];
    }
    __syncthreads();
    if (wid == 0) {
      uint32_t bits = 0;
      if (lane < 24) {
        const int hc2 = lane >> 3, j = lane & 7;
        const float gt = rbf(part[(2 * hc2) * 8 + j] + part[(2 * hc2 + 1) * 8 + j]);
        const float up = rbf(part[(6 + 2 * hc2) * 8 + j] + part[(6 + 2 * hc2 + 1) * 8 + j]);
        const float sg = rbf(gt / (1.f + __expf(-gt)));
        bits = __bfloat16_as_ushort(__float2bfloat16_rn(sg * up));
      }
      const uint32_t nb = __shfl_down_sync(0xffffffffu, bits, 1);
      const uint32_t pw = bits | (nb << 16);
      const uint32_t w1 = __shfl_down_sync(0xffffffffu, pw, 2), w2 = __shfl_down_sync(0xffffffffu, pw, 4), w3 = __shfl_down_sync(0xffffffffu, pw, 6);
      if (lane < 24 && (lane & 7) == 0) st_pub4(&g_act[cta * 3 + (lane >> 3)], enc4(make_uint4(pw, w1, w2, w3)));
    }
  } else if (cta < N1 + N2) {
    const int j2 = cta - N1;
    uint4 rowv = make_uint4(0, 0, 0, 0);
    if (tid < 192) {
      const uint4 v = poll4(&g_act[tid]);
      float4* xp = reinterpret_cast<float4*>(xs + tid * 8);
      xp[0] = make_float4(lo_f(v.x), hi_f(v.x), lo_f(v.y), hi_f(v.y));
      xp[1] = make_float4(lo_f(v.z), hi_f(v.z), lo_f(v.w), hi_f(v.w));
    } else if (tid < 196) {
      const int t = tid - 192;
      rowv = poll4(&g_cand[wcta][t >> 1][j2 * 2 + (t & 1)]);
      reinterpret_cast<uint4*>(part + 256)[t] = rowv;
    }
    __syncthreads();
    const int hc = lane & 1, rs = wid * 16 + (lane >> 1);
    float a[8];
#pragma unroll
    for (int j = 0; j < 8; j++) a[j] = 0.f;
#pragma unroll
    for (int it = 0; it < 8; it++) {
      const int r = rs + 192 * it;
      const uint4 wv = sm.w[r * 2 + hc];
      const float x = xs[r];
      a[0] = fmaf(x, lo_f(wv.x), a[0]); a[1] = fmaf(x, hi_f(wv.x), a[1]);
      a[2] = fmaf(x, lo_f(wv.y), a[2]); a[3] = fmaf(x, hi_f(wv.y), a[3]);
      a[4] = fmaf(x, lo_f(wv.z), a[4]); a[5] = fmaf(x, hi_f(wv.z), a[5]);
      a[6] = fmaf(x, lo_f(wv.w), a[6]); a[7] = fmaf(x, hi_f(wv.w), a[7]);
    }
    {
      const bool up = lane & 16;
#pragma unroll
      for (int j = 0; j < 4; j++) {
        const float send = up ? a[j] : a[j + 4], keep = up ? a[j + 4] : a[j];
        a[j] = keep + __shfl_xor_sync(0xffffffffu, send, 16);
      }
      const bool up2 = lane & 8;
#pragma unroll
      for (int j = 0; j < 2; j++) {
        const float send = up2 ? a[j] : a[j + 2], keep = up2 ? a[j + 2] : a[j];
        a[j] = keep + __shfl_xor_sync(0xffffffffu, send, 8);
      }
      const bool up3 = lane & 4;
      const float send = up3 ? a[0] : a[1], keep = up3 ? a[1] : a[0];
      a[0] = keep + __shfl_xor_sync(0xffffffffu, send, 4);
      a[0] += __shfl_xor_sync(0xffffffffu, a[0], 2);
      if ((lane & 2) == 0) part[wid * 16 + hc * 8 + (lane >> 2)] = a[0];
    }
    __syncthreads();
    if (tid < 16) {
      float y = 0.f;
#pragma unroll
      for (int i = 0; i < 12; i++) y += part[i * 16 + tid];
      const uint32_t ord = win >> 16;
      const uint32_t rb = (ord & 0x8000u) ? (ord ^ 0x8000u) : (ord ^ 0xFFFFu);
      const float r = __uint_as_float(rb << 16);
      const float sg = rbf(1.f / (1.f + __expf(-r)));
      const float yy = rbf(rbf(y) * sg);
      const unsigned short* rv = reinterpret_cast<const unsigned short*>(part + 256);
      const float hn = __uint_as_float((uint32_t)rv[tid] << 16), h = __uint_as_float((uint32_t)rv[16 + tid] << 16);
      gout[(size_t)wrow * D_ + j2 * 16 + tid] = __float2bfloat16_rn(h + rbf(hn + yy));
    }
  }
  STAMP(8);
}

}

typedef CUresult (*EncodeFn)(CUtensorMap*, CUtensorMapDataType, cuuint32_t, void*, const cuuint64_t*, const cuuint64_t*,
                             const cuuint32_t*, const cuuint32_t*, CUtensorMapInterleave, CUtensorMapSwizzle,
                             CUtensorMapL2promotion, CUtensorMapFloatOOBfill);

extern "C" void kernel_launch(void* const* d_in, const int* in_sizes, int n_in, void* d_out, int out_size) {
  (void)in_sizes; (void)n_in; (void)out_size;
  static EncodeFn encode = nullptr;
  static CUtensorMap tmg, tmu, tmd;
  static void* cached[3] = {nullptr, nullptr, nullptr};
  if (!encode) {
    cudaFuncSetAttribute(fused_kernel, cudaFuncAttributeMaxDynamicSharedMemorySize, (int)sizeof(Smem));
    void* fn = nullptr;
    cudaDriverEntryPointQueryResult qr;
    cudaGetDriverEntryPoint("cuTensorMapEncodeTiled", &fn, cudaEnableDefault, &qr);
    encode = (EncodeFn)fn;
  }
  if (cached[0] != d_in[8] || cached[1] != d_in[9] || cached[2] != d_in[10]) {
    const cuuint32_t es[2] = {1, 1};
    {
      const cuuint64_t dims[2] = {F_, D_}, strides[1] = {F_ * 2};
      const cuuint32_t box[2] = {24, 160};
      encode(&tmg, CU_TENSOR_MAP_DATA_TYPE_BFLOAT16, 2, d_in[8], dims, strides, box, es, CU_TENSOR_MAP_INTERLEAVE_NONE,
             CU_TENSOR_MAP_SWIZZLE_NONE, CU_TENSOR_MAP_L2_PROMOTION_NONE, CU_TENSOR_MAP_FLOAT_OOB_FILL_NONE);
      encode(&tmu, CU_TENSOR_MAP_DATA_TYPE_BFLOAT16, 2, d_in[9], dims, strides, box, es, CU_TENSOR_MAP_INTERLEAVE_NONE,
             CU_TENSOR_MAP_SWIZZLE_NONE, CU_TENSOR_MAP_L2_PROMOTION_NONE, CU_TENSOR_MAP_FLOAT_OOB_FILL_NONE);
    }
    {
      const cuuint64_t dims[2] = {D_, F_}, strides[1] = {D_ * 2};
      const cuuint32_t box[2] = {16, 256};
      encode(&tmd, CU_TENSOR_MAP_DATA_TYPE_BFLOAT16, 2, d_in[10], dims, strides, box, es, CU_TENSOR_MAP_INTERLEAVE_NONE,
             CU_TENSOR_MAP_SWIZZLE_NONE, CU_TENSOR_MAP_L2_PROMOTION_NONE, CU_TENSOR_MAP_FLOAT_OOB_FILL_NONE);
    }
    cached[0] = d_in[8]; cached[1] = d_in[9]; cached[2] = d_in[10];
  }
  fused_kernel<<<NCTA, NTHR, sizeof(Smem), cudaStreamPerThread>>>(
      tmg, tmu, tmd, (const bf16*)d_in[0], (const bf16*)d_in[1], (const bf16*)d_in[2], (const bf16*)d_in[3],
      (const bf16*)d_in[4], (const bf16*)d_in[5], (const bf16*)d_in[7], (bf16*)d_out);
}
```

```cpp
#include <cuda_runtime.h>
#include <cuda_bf16.h>
#include <cuda.h>
#include <stdint.h>

namespace {

typedef __nv_bfloat16 bf16;
typedef __nv_bfloat162 bf162;

constexpr int S_ = 2048, D_ = 640, F_ = 1536;
constexpr int NCTA = 128, CPC = 5, NTHR = 384;
constexpr int UPAD = 136, USTR = 2192;
constexpr int TABW = 1040;
constexpr int ZPB = 132;
constexpr int QSTR = 648;
constexpr int N1 = 64;
constexpr int N2 = 40;
constexpr int SPIN_LIMIT = 1 << 19;
#define POLL_NS 100
#define H_DELAY 2000
#define Q_DELAY 4500

struct __align__(128) Smem {
  uint32_t tabA[3][2][TABW];
  uint32_t extra[1024];
  uint32_t tabB[2][2][TABW];
  bf16 u[CPC][USTR];
  float z[2][4][ZPB * 16];
  bf16 q[16][QSTR];
  alignas(128) uint4 w[3840];
  uint4 wr[80];
  float2 st[16][5];
  float rp[16][5];
  unsigned long long mbar;
  unsigned long long mbarw;
  unsigned long long mbarc;
  unsigned long long mbarh;
  uint32_t target;
  uint32_t best;
  uint32_t win;
};

__device__ uint4 g_kv[D_ * S_ / 8];
__device__ uint4 g_y2[D_ * S_ / 8];
__device__ uint32_t g_keys[NCTA];
__device__ uint4 g_cand[NCTA][2][80];
__device__ uint4 g_act[F_ / 8];
__device__ unsigned int g_ctr;
__device__ unsigned int g_ctr2;
#define STAMP(i)

__device__ __forceinline__ uint32_t smem_u32(const void* p) { return (uint32_t)__cvta_generic_to_shared(p); }
__device__ __forceinline__ void wg_fence() { asm volatile("wgmma.fence.sync.aligned;" ::: "memory"); }
__device__ __forceinline__ void wg_commit() { asm volatile("wgmma.commit_group.sync.aligned;" ::: "memory"); }
template <int N> __device__ __forceinline__ void wg_wait() { asm volatile("wgmma.wait_group.sync.aligned %0;" ::"n"(N) : "memory"); }
__device__ __forceinline__ void bar_sync(int id, int n) { asm volatile("bar.sync %0, %1;" ::"r"(id), "r"(n) : "memory"); }
__device__ __forceinline__ void bar_arrive(int id, int n) { asm volatile("bar.arrive %0, %1;" ::"r"(id), "r"(n) : "memory"); }
__device__ __forceinline__ bf162 u2b(uint32_t u) { return *reinterpret_cast<bf162*>(&u); }
__device__ __forceinline__ uint32_t b2u(bf162 b) { return *reinterpret_cast<uint32_t*>(&b); }
__device__ __forceinline__ float lo_f(uint32_t u) { return __uint_as_float(u << 16); }
__device__ __forceinline__ float hi_f(uint32_t u) { return __uint_as_float(u & 0xFFFF0000u); }
__device__ __forceinline__ float rbf(float x) { return __bfloat162float(__float2bfloat16_rn(x)); }
__device__ __forceinline__ uint32_t pack2(float a, float b) { return b2u(__floats2bfloat162_rn(a, b)); }
__device__ __forceinline__ uint32_t enc(uint32_t w) { return max(~w, 1u); }
__device__ __forceinline__ uint4 enc4(uint4 v) { return make_uint4(enc(v.x), enc(v.y), enc(v.z), enc(v.w)); }
__device__ __forceinline__ uint4 ld_poll4(const uint4* p) {
  uint4 v;
  asm volatile("ld.relaxed.gpu.global.v4.u32 {%0,%1,%2,%3}, [%4];" : "=r"(v.x), "=r"(v.y), "=r"(v.z), "=r"(v.w) : "l"(p) : "memory");
  return v;
}
__device__ __forceinline__ bool ready4(uint4 v) { return v.x != 0u && v.y != 0u && v.z != 0u && v.w != 0u; }
__device__ __forceinline__ uint4 poll4(const uint4* p) {
  uint4 v = ld_poll4(p);
  int it = 0;
  while (!ready4(v) && ++it < SPIN_LIMIT) v = ld_poll4(p);
  return make_uint4(~v.x, ~v.y, ~v.z, ~v.w);
}
__device__ __forceinline__ void st_pub4(uint4* p, uint4 v) {
  asm volatile("st.relaxed.gpu.global.v4.u32 [%0], {%1,%2,%3,%4};" ::"l"(p), "r"(v.x), "r"(v.y), "r"(v.z), "r"(v.w) : "memory");
}
__device__ __forceinline__ void st_pub2(uint2* p, uint32_t a, uint32_t b) {
  asm volatile("st.relaxed.gpu.global.v2.u32 [%0], {%1,%2};" ::"l"(p), "r"(a), "r"(b) : "memory");
}
__device__ __forceinline__ void mma_bf16(float (&c)[4], uint32_t a0, uint32_t a2, uint32_t b0, uint32_t b1) {
  asm volatile("mma.sync.aligned.m16n8k16.row.col.f32.bf16.bf16.f32 {%0,%1,%2,%3}, {%4,%5,%6,%5}, {%7,%8}, {%0,%1,%2,%3};"
               : "+f"(c[0]), "+f"(c[1]), "+f"(c[2]), "+f"(c[3]) : "r"(a0), "r"(0u), "r"(a2), "r"(b0), "r"(b1));
}
__device__ __forceinline__ void mbar_wait(const unsigned long long* bar) {
  const uint32_t mb = smem_u32(bar);
  uint32_t ok = 0;
  int it = 0;
  while (!ok && ++it < SPIN_LIMIT)
    asm volatile("{ .reg .pred p; mbarrier.try_wait.parity.shared.b64 p, [%1], 0; selp.u32 %0, 1, 0, p; }" : "=r"(ok) : "r"(mb) : "memory");
}
__device__ __forceinline__ void bulk_g2s(void* dst, const void* src, uint32_t bytes, const unsigned long long* bar) {
  asm volatile("cp.async.bulk.shared::cluster.global.mbarrier::complete_tx::bytes [%0], [%1], %2, [%3];" ::"r"(smem_u32(dst)),
               "l"(src), "r"(bytes), "r"(smem_u32(bar)) : "memory");
}
__device__ __forceinline__ void mbar_expect(const unsigned long long* bar, uint32_t bytes) {
  asm volatile("mbarrier.arrive.expect_tx.shared.b64 _, [%0], %1;" ::"r"(smem_u32(bar)), "r"(bytes) : "memory");
}
__device__ __forceinline__ float fdivr(float a, float d, float r) {
  float q = a * r;
  float e = fmaf(-q, d, a);
  return fmaf(e, r, q);
}

template <bool FIRST> __device__ __forceinline__ void wgmma32(float (&d)[16], const uint32_t* a, uint64_t desc) {
  if (FIRST) {
    asm volatile("wgmma.mma_async.sync.aligned.m64n32k16.f32.bf16.bf16 {%0,%1,%2,%3,%4,%5,%6,%7,%8,%9,%10,%11,%12,%13,%14,%15}, {%16,%17,%18,%19}, %20, 0, 1, 1, 0;"
                 : "+f"(d[0]), "+f"(d[1]), "+f"(d[2]), "+f"(d[3]), "+f"(d[4]), "+f"(d[5]), "+f"(d[6]), "+f"(d[7]),
                   "+f"(d[8]), "+f"(d[9]), "+f"(d[10]), "+f"(d[11]), "+f"(d[12]), "+f"(d[13]), "+f"(d[14]), "+f"(d[15])
                 : "r"(a[0]), "r"(a[1]), "r"(a[2]), "r"(a[3]), "l"(desc));
  } else {
    asm volatile("wgmma.mma_async.sync.aligned.m64n32k16.f32.bf16.bf16 {%0,%1,%2,%3,%4,%5,%6,%7,%8,%9,%10,%11,%12,%13,%14,%15}, {%16,%17,%18,%19}, %20, 1, 1, 1, 0;"
                 : "+f"(d[0]), "+f"(d[1]), "+f"(d[2]), "+f"(d[3]), "+f"(d[4]), "+f"(d[5]), "+f"(d[6]), "+f"(d[7]),
                   "+f"(d[8]), "+f"(d[9]), "+f"(d[10]), "+f"(d[11]), "+f"(d[12]), "+f"(d[13]), "+f"(d[14]), "+f"(d[15])
                 : "r"(a[0]), "r"(a[1]), "r"(a[2]), "r"(a[3]), "l"(desc));
  }
}

template <int G> __device__ __forceinline__ void load_a(uint32_t (&a)[8], const uint32_t* tp) {
#pragma unroll
  for (int q = 0; q < 2; q++) {
    const int e = 2 * G + q;
    a[4 * q + 0] = tp[-64 * e];
    a[4 * q + 1] = tp[-64 * e - 32];
    a[4 * q + 2] = tp[-64 * e + 4];
    a[4 * q + 3] = tp[-64 * e - 28];
  }
}
__device__ __forceinline__ void load_a_all(uint32_t (&a)[8][8], const uint32_t* tp) {
  load_a<0>(a[0], tp); load_a<1>(a[1], tp); load_a<2>(a[2], tp); load_a<3>(a[3], tp);
  load_a<4>(a[4], tp); load_a<5>(a[5], tp); load_a<6>(a[6], tp); load_a<7>(a[7], tp);
}
template <int G> __device__ __forceinline__ void issue_g(float (&acc)[8][16], uint32_t (&a)[8], uint64_t desc0) {
  wg_fence();
#pragma unroll
  for (int q = 0; q < 2; q++) {
#pragma unroll
    for (int b = G; b < 8; b++) {
      const int delta = 2 * b - (2 * G + q);
      if (G == 0 && q == 0) wgmma32<true>(acc[b], &a[4 * q], desc0 + (uint64_t)(int64_t)(16 * delta));
      else wgmma32<false>(acc[b], &a[4 * q], desc0 + (uint64_t)(int64_t)(16 * delta));
    }
  }
  wg_commit();
}
template <int B> __device__ __forceinline__ void fence_blk(float (&acc)[8][16]) {
#pragma unroll
  for (int i = 0; i < 16; i++) asm volatile("" : "+f"(acc[B][i])::"memory");
}
__device__ __forceinline__ void fence_a(uint32_t (&a)[8]) {
#pragma unroll
  for (int i = 0; i < 8; i++) asm volatile("" : "+r"(a[i])::"memory");
}
template <int B> __device__ __forceinline__ void sts_blk(float (&acc)[8][16], float* zw, int off_even, int off_odd) {
#pragma unroll
  for (int jj = 0; jj < 4; jj++) {
    const int j = 4 * B + jj;
    float p0 = acc[B][4 * jj + 0], p1 = acc[B][4 * jj + 1];
    if (jj > 0) { p0 += acc[B][4 * (jj - 1) + 2]; p1 += acc[B][4 * (jj - 1) + 3]; }
    else if (B > 0) { p0 += acc[B > 0 ? B - 1 : 0][14]; p1 += acc[B > 0 ? B - 1 : 0][15]; }
    zw[64 * j + off_even] = p0;
    zw[64 * j + off_odd] = p1;
  }
}
__device__ __forceinline__ int tab_off(int c) { return c == 4 ? 0 : (c + 1) * 2 * TABW + (c >= 2 ? 1024 : 0); }
__device__ __forceinline__ int tile_perm(int ch) { return ch ^ (((ch >> 3) & 3) << 1); }

__device__ __forceinline__ void wait_ctr(const unsigned int* ctr, uint32_t target) {
  uint32_t v;
  int it = 0;
  do {
    asm volatile("ld.acquire.gpu.global.u32 %0, [%1];" : "=r"(v) : "l"(ctr) : "memory");
  } while ((int)(v - target) < 0 && ++it < SPIN_LIMIT);
}

__device__ __forceinline__ void ln_q_rows(Smem& sm, bf16* qn_s, int row, int lane) {
      const uint32_t* qp = reinterpret_cast<const uint32_t*>(&sm.q[row][0]);
      uint32_t qa[10], qb[10];
      float sa = 0.f, sb = 0.f;
#pragma unroll
      for (int i = 0; i < 10; i++) {
        qa[i] = qp[lane + 32 * i]; qb[i] = qp[QSTR / 2 + lane + 32 * i];
        sa += lo_f(qa[i]) + hi_f(qa[i]); sb += lo_f(qb[i]) + hi_f(qb[i]);
      }
#pragma unroll
      for (int o = 16; o > 0; o >>= 1) { sa += __shfl_xor_sync(0xffffffffu, sa, o); sb += __shfl_xor_sync(0xffffffffu, sb, o); }
      sa *= (1.f / D_); sb *= (1.f / D_);
      float ma = 0.f, mb2 = 0.f;
#pragma unroll
      for (int i = 0; i < 10; i++) {
        const float x = lo_f(qa[i]) - sa, y = hi_f(qa[i]) - sa, z = lo_f(qb[i]) - sb, t = hi_f(qb[i]) - sb;
        ma = fmaf(x, x, fmaf(y, y, ma)); mb2 = fmaf(z, z, fmaf(t, t, mb2));
      }
#pragma unroll
      for (int o = 16; o > 0; o >>= 1) { ma += __shfl_xor_sync(0xffffffffu, ma, o); mb2 += __shfl_xor_sync(0xffffffffu, mb2, o); }
      const float da = rbf(sqrtf(rbf(rbf(ma * (1.f / D_)) + 1e-5f))), db = rbf(sqrtf(rbf(rbf(mb2 * (1.f / D_)) + 1e-5f)));
      const float ra = 1.f / da, rb = 1.f / db;
      const bf162 ma2 = __float2bfloat162_rn(sa), mb3 = __float2bfloat162_rn(sb);
      uint32_t* np = reinterpret_cast<uint32_t*>(qn_s + row * QSTR);
#pragma unroll
      for (int i = 0; i < 10; i++) {
        const uint32_t d = b2u(__hsub2_rn(u2b(qa[i]), ma2)), e = b2u(__hsub2_rn(u2b(qb[i]), mb3));
        np[lane + 32 * i] = pack2(fdivr(lo_f(d), da, ra), fdivr(hi_f(d), da, ra));
        np[QSTR / 2 + lane + 32 * i] = pack2(fdivr(lo_f(e), db, rb), fdivr(hi_f(e), db, rb));
      }
}

__global__ void __launch_bounds__(NTHR, 1)
fused_kernel(const __grid_constant__ CUtensorMap tmg, const __grid_constant__ CUtensorMap tmu,
             const __grid_constant__ CUtensorMap tmd, const bf16* __restrict__ gq, const bf16* __restrict__ gk, const bf16* __restrict__ gv,
             const bf16* __restrict__ gsk, const bf16* __restrict__ gh, const bf16* __restrict__ gD,
             const bf16* __restrict__ gwr, bf16* __restrict__ gout) {
  extern __shared__ __align__(128) unsigned char smraw[];
  Smem& sm = *reinterpret_cast<Smem*>(smraw);
  const int tid = threadIdx.x;
  const int cta = blockIdx.x;
  const int c0 = cta * CPC;
  const int lane = tid & 31;
  const int wid = tid >> 5;
  STAMP(0);
  const long long tstart = clock64();

  {
    uint4* hs = reinterpret_cast<uint4*>(&sm.z[0][0][0]);
    const int oc = tid >> 2;
    const int r0 = cta * 16 + (tid & 3) * 4;
    uint4 kk[7], vv[4], sk[4];
    if (tid < 320) {
      const uint4* kp = reinterpret_cast<const uint4*>(gk) + (size_t)r0 * 80 + oc;
      const uint4* vp = reinterpret_cast<const uint4*>(gv) + (size_t)r0 * 80 + oc;
#pragma unroll
      for (int i = 0; i < 7; i++) kk[i] = (i >= 3 || r0 > 0) ? __ldg(kp + (i - 3) * 80) : make_uint4(0, 0, 0, 0);
#pragma unroll
      for (int i = 0; i < 4; i++) vv[i] = __ldg(vp + i * 80);
#pragma unroll
      for (int i = 0; i < 4; i++) sk[i] = __ldg(reinterpret_cast<const uint4*>(gsk) + oc * 4 + i);
    } else if (tid == 320) {
      asm volatile("mbarrier.init.shared.b64 [%0], 1;" ::"r"(smem_u32(&sm.mbarh)) : "memory");
      asm volatile("mbarrier.init.shared.b64 [%0], 1;" ::"r"(smem_u32(&sm.mbar)) : "memory");
      asm volatile("mbarrier.init.shared.b64 [%0], 1;" ::"r"(smem_u32(&sm.mbarw)) : "memory");
      asm volatile("mbarrier.init.shared.b64 [%0], 1;" ::"r"(smem_u32(&sm.mbarc)) : "memory");
      asm volatile("fence.proxy.async.shared::cta;" ::: "memory");
    }
    if (tid < 320) bar_sync(6, 384); else { bar_arrive(6, 384); bar_sync(5, 64); }
    STAMP(9);
    if (tid < 320) {
      uint32_t o[4][4];
#pragma unroll
      for (int p = 0; p < 4; p++) {
        const bf162 w0 = u2b(__byte_perm(sk[p].x, sk[p].z, 0x5410)), w1 = u2b(__byte_perm(sk[p].x, sk[p].z, 0x7632));
        const bf162 w2 = u2b(__byte_perm(sk[p].y, sk[p].w, 0x5410)), w3 = u2b(__byte_perm(sk[p].y, sk[p].w, 0x7632));
        uint32_t kv[4];
#pragma unroll
        for (int i = 0; i < 4; i++) {
          const uint32_t k0 = p == 0 ? kk[i].x : p == 1 ? kk[i].y : p == 2 ? kk[i].z : kk[i].w;
          const uint32_t k1 = p == 0 ? kk[i + 1].x : p == 1 ? kk[i + 1].y : p == 2 ? kk[i + 1].z : kk[i + 1].w;
          const uint32_t k2 = p == 0 ? kk[i + 2].x : p == 1 ? kk[i + 2].y : p == 2 ? kk[i + 2].z : kk[i + 2].w;
          const uint32_t k3 = p == 0 ? kk[i + 3].x : p == 1 ? kk[i + 3].y : p == 2 ? kk[i + 3].z : kk[i + 3].w;
          const uint32_t vx = p == 0 ? vv[i].x : p == 1 ? vv[i].y : p == 2 ? vv[i].z : vv[i].w;
          bf162 a = __hmul2_rn(u2b(k0), w3);
          a = __hadd2_rn(a, __hmul2_rn(u2b(k1), w2));
          a = __hadd2_rn(a, __hmul2_rn(u2b(k2), w1));
          a = __hadd2_rn(a, __hmul2_rn(u2b(k3), w0));
          kv[i] = b2u(__hmul2_rn(a, u2b(vx)));
        }
        o[p][0] = enc(__byte_perm(kv[0], kv[1], 0x5410)); o[p][1] = enc(__byte_perm(kv[2], kv[3], 0x5410));
        o[p][2] = enc(__byte_perm(kv[0], kv[1], 0x7632)); o[p][3] = enc(__byte_perm(kv[2], kv[3], 0x7632));
      }
      mbar_wait(&sm.mbarc);
      uint2* dst = reinterpret_cast<uint2*>(g_kv) + (size_t)(oc * 8) * 512 + (r0 >> 2);
#pragma unroll
      for (int p = 0; p < 4; p++) {
        st_pub2(dst + (2 * p) * 512, o[p][0], o[p][1]);
        st_pub2(dst + (2 * p + 1) * 512, o[p][2], o[p][3]);
      }
      STAMP(10);
    } else {
      const int t0 = tid - 320;
      const uint4 zz = make_uint4(0, 0, 0, 0);
#pragma unroll 4
      for (int i = 0; i < 20; i++) g_kv[c0 * 256 + t0 + 64 * i] = zz;
      bar_sync(5, 64);
      if (tid == 352) {
        __threadfence();
        const unsigned old = atomicAdd(&g_ctr2, 1u);
        wait_ctr(&g_ctr2, (old / NCTA + 1u) * NCTA);
        asm volatile("mbarrier.arrive.shared.b64 _, [%0];" ::"r"(smem_u32(&sm.mbarc)) : "memory");
      }
      if (tid == 320) {
        while (clock64() - tstart < H_DELAY) {}
        mbar_expect(&sm.mbarh, CPC * S_ * 2);
        bulk_g2s(hs, gh + (size_t)c0 * S_, CPC * S_ * 2, &sm.mbarh);
      }
      __syncwarp();
      for (int t = t0; t < CPC * 17; t += 64) *reinterpret_cast<uint4*>(&sm.u[t / 17][(t % 17) * 8]) = zz;
      if (t0 < 40) *reinterpret_cast<uint4*>(&sm.tabA[0][0][0] + tab_off(t0 >> 3) + ((t0 >> 2) & 1) * TABW + 1024 + 4 * (t0 & 3)) = zz;
      while (clock64() - tstart < Q_DELAY) {}
      if (tid == 320) {
        mbar_expect(&sm.mbar, 17 * D_ * 2);
#pragma unroll 1
        for (int r = 0; r < 16; r++) bulk_g2s(&sm.q[r][0], gq + (size_t)(cta * 16 + r) * D_, D_ * 2, &sm.mbar);
        bulk_g2s(&sm.wr[0], gwr, D_ * 2, &sm.mbar);
      }
      __syncwarp();
#pragma unroll 4
      for (int i = 0; i < 20; i++) g_y2[cta * 1280 + t0 + 64 * i] = zz;
      (&g_cand[cta][0][0])[t0] = zz;
      (&g_cand[cta][0][0])[64 + t0] = zz;
      if (t0 < 32) (&g_cand[cta][0][0])[128 + t0] = zz;
      else if (t0 < 35) { if (cta < N1) g_act[cta * 3 + (t0 - 32)] = zz; }
      else if (t0 == 35) g_keys[cta] = 0u;
      bar_sync(5, 64);
      if (tid == 352) {
        __threadfence();
        const unsigned old = atomicAdd(&g_ctr, 1u);
        sm.target = (old / NCTA + 1u) * NCTA;
      }
      __syncwarp();
    }
    mbar_wait(&sm.mbarh);
#pragma unroll
    for (int i = 0; i < 4; i++) {
      const int t = (NTHR - 1 - tid) + NTHR * i;
      if (t < CPC * 256) {
        uint32_t* tb = &sm.tabA[0][0][0] + tab_off(t >> 8) + (255 - (t & 255)) * 4;
        const uint4 h = hs[t];
        const uint32_t hp = (t & 255) ? reinterpret_cast<const uint32_t*>(hs)[4 * t - 1] : 0u;
        uint4 r1, rr;
        r1.x = __byte_perm(h.w, 0, 0x1032); r1.y = __byte_perm(h.z, 0, 0x1032);
        r1.z = __byte_perm(h.y, 0, 0x1032); r1.w = __byte_perm(h.x, 0, 0x1032);
        rr.x = __byte_perm(h.w, h.z, 0x7610); rr.y = __byte_perm(h.z, h.y, 0x7610);
        rr.z = __byte_perm(h.y, h.x, 0x7610); rr.w = __byte_perm(h.x, hp, 0x7610);
        *reinterpret_cast<uint4*>(tb) = rr;
        *reinterpret_cast<uint4*>(tb + TABW) = r1;
      }
    }
    STAMP(12);
  }
  {
    uint4 v[4];
    uint4* src = g_kv + c0 * 256 + tid;
#pragma unroll
    for (int i = 0; i < 4; i++) if (i < 3 || tid < 128) v[i] = ld_poll4(src + NTHR * i);
#pragma unroll
    for (int i = 0; i < 4; i++) {
      if (i < 3 || tid < 128) {
        int it = 0;
        while (!ready4(v[i]) && ++it < SPIN_LIMIT) { __nanosleep(POLL_NS); v[i] = ld_poll4(src + NTHR * i); }
        const int t = tid + NTHR * i;
        *reinterpret_cast<uint4*>(&sm.u[t >> 8][UPAD + (t & 255) * 8]) = make_uint4(~v[i].x, ~v[i].y, ~v[i].z, ~v[i].w);
      }
    }
    STAMP(11);
    asm volatile("fence.proxy.async.shared::cta;" ::: "memory");
    __syncthreads();
    if (tid >= 256) {
      const int t0 = tid - 256;
      if (((t0 & 15) >> 2) < ((t0 >> 4) & 3))
        *reinterpret_cast<uint4*>(&sm.z[t0 >> 6][(t0 >> 4) & 3][(t0 & 15) * 4]) = make_uint4(0, 0, 0, 0);
    }
  }
  STAMP(1);

  const int wg = __shfl_sync(0xffffffffu, tid >> 7, 0);
  const int wtid = tid & 127;
  uint4* tile = reinterpret_cast<uint4*>(&sm.tabB[0][0][0]);
  bf16* qn_s = reinterpret_cast<bf16*>(&sm.tabA[1][0][0]);
  if (wg < 2) {
    asm volatile("setmaxnreg.inc.sync.aligned.u32 224;");
    const int w = (tid >> 5) & 3, g = lane >> 2, tq = lane & 3;
    float* zw = sm.z[wg][w];
    const int sw = 3 * (((tq + w) >> 1) & 1);
    const int off_even = 16 * (tq + w) + 4 * ((0 + (g >> 2)) ^ sw) + (g & 3);
    const int off_odd = 16 * (tq + w) + 4 * ((2 + (g >> 2)) ^ sw) + (g & 3);
    uint32_t a[8][8];
    const uint32_t* tp0 = &sm.tabA[0][g & 1][1019 - 8 * w - (g >> 1) + tq];
    load_a_all(a, tp0 + tab_off(wg));
    if (wg == 0) bar_arrive(7, 384);
    else {
      mbar_wait(&sm.mbar);
      bar_sync(7, 384);
      ln_q_rows(sm, qn_s, w * 2, lane);
    }
    float acc[8][16];
#pragma unroll
    for (int b = 0; b < 8; b++)
#pragma unroll
      for (int i = 0; i < 16; i++) acc[b][i] = 0.f;
#pragma unroll 1
    for (int c = wg; c < CPC; c += 2) {
      const uint64_t desc = (uint64_t)((smem_u32(&sm.u[c][UPAD - 8]) & 0x3FFFF) >> 4) | ((uint64_t)1 << 16) | ((uint64_t)8 << 32);
      if (c > 0) bar_sync(1 + wg, 256);
      issue_g<0>(acc, a[0], desc);
      issue_g<1>(acc, a[1], desc);
      issue_g<2>(acc, a[2], desc);
      issue_g<3>(acc, a[3], desc);
      issue_g<4>(acc, a[4], desc);
      issue_g<5>(acc, a[5], desc);
      if (c + 1 < CPC) bar_arrive(1 + (wg ^ 1), 256);
      issue_g<6>(acc, a[6], desc);
      issue_g<7>(acc, a[7], desc);
      if (c >= 2) bar_sync(5 + wg, 256);
      wg_wait<4>();
      fence_blk<0>(acc); fence_blk<1>(acc); fence_blk<2>(acc); fence_blk<3>(acc);
      sts_blk<0>(acc, zw, off_even, off_odd);
      sts_blk<1>(acc, zw, off_even, off_odd);
      sts_blk<2>(acc, zw, off_even, off_odd);
      sts_blk<3>(acc, zw, off_even, off_odd);
      wg_wait<0>();
      fence_blk<4>(acc); fence_blk<5>(acc); fence_blk<6>(acc); fence_blk<7>(acc);
#pragma unroll
      for (int i = 0; i < 8; i++) fence_a(a[i]);
      sts_blk<4>(acc, zw, off_even, off_odd);
      sts_blk<5>(acc, zw, off_even, off_odd);
      sts_blk<6>(acc, zw, off_even, off_odd);
      sts_blk<7>(acc, zw, off_even, off_odd);
      bar_arrive(3 + wg, 256);
      if (c + 2 < CPC) load_a_all(a, tp0 + tab_off(c + 2));
    }
    STAMP(2 + wg);
    asm volatile("setmaxnreg.dec.sync.aligned.u32 168;");
    if (wg == 1) {
#pragma unroll 1
      for (int cc = 0; cc < 4; cc++) {
        const int ch = wtid * 5 + cc;
        const uint4* src = g_y2 + cta * 1280 + ch * 2;
        uint4 v0 = ld_poll4(src), v1 = ld_poll4(src + 1);
        int it = 0;
        while (!ready4(v0) && ++it < SPIN_LIMIT) v0 = ld_poll4(src);
        while (!ready4(v1) && ++it < SPIN_LIMIT) v1 = ld_poll4(src + 1);
        const int pc = tile_perm(ch);
        tile[pc] = make_uint4(~v0.x, ~v0.y, ~v0.z, ~v0.w);
        tile[640 + pc] = make_uint4(~v1.x, ~v1.y, ~v1.z, ~v1.w);
      }
    }
  } else {
    asm volatile("setmaxnreg.dec.sync.aligned.u32 56;");
    if (wtid == 32) {
      const uint32_t mw = smem_u32(&sm.mbarw);
      if (cta < N1) {
        asm volatile("mbarrier.arrive.expect_tx.shared.b64 _, [%0], %1;" ::"r"(mw), "r"(3840 * 16) : "memory");
#pragma unroll 1
        for (int i = 0; i < 4; i++) {
          asm volatile("cp.async.bulk.tensor.2d.shared::cluster.global.mbarrier::complete_tx::bytes [%0], [%1, {%3, %4}], [%2];" ::"r"(smem_u32(&sm.w[i * 480])),
                       "l"(&tmg), "r"(mw), "r"(cta * 24), "r"(i * 160) : "memory");
          asm volatile("cp.async.bulk.tensor.2d.shared::cluster.global.mbarrier::complete_tx::bytes [%0], [%1, {%3, %4}], [%2];" ::"r"(smem_u32(&sm.w[1920 + i * 480])),
                       "l"(&tmu), "r"(mw), "r"(cta * 24), "r"(i * 160) : "memory");
        }
      } else if (cta < N1 + N2) {
        asm volatile("mbarrier.arrive.expect_tx.shared.b64 _, [%0], %1;" ::"r"(mw), "r"(3072 * 16) : "memory");
#pragma unroll 1
        for (int i = 0; i < 6; i++)
          asm volatile("cp.async.bulk.tensor.2d.shared::cluster.global.mbarrier::complete_tx::bytes [%0], [%1, {%3, %4}], [%2];" ::"r"(smem_u32(&sm.w[i * 512])),
                       "l"(&tmd), "r"(mw), "r"((cta - N1) * 16), "r"(i * 256) : "memory");
      }
    }
    mbar_wait(&sm.mbar);
    bar_sync(7, 384);
    ln_q_rows(sm, qn_s, 8 + (wid - 8) * 2, lane);
    if (wtid == 0) wait_ctr(&g_ctr, sm.target);
    const int rpb = wtid >> 1, re2 = wtid & 1;
    const int rsw = 3 * ((rpb >> 1) & 1);
    const int roff0 = 16 * rpb + 4 * ((2 * re2 + 0) ^ rsw);
    const int roff1 = 16 * rpb + 4 * ((2 * re2 + 1) ^ rsw);
    const uint32_t dvl = reinterpret_cast<const unsigned short*>(gD)[c0 + (lane < CPC ? lane : 0)];
#pragma unroll 1
    for (int c = 0; c < CPC; c++) {
      const int zg = c & 1;
      const uint32_t dvc = __shfl_sync(0xffffffffu, dvl, c);
      const bf162 d2 = u2b(dvc | (dvc << 16));
      bar_sync(3 + zg, 256);
#pragma unroll
      for (int half = 0; half < 2; half++) {
        const float* zb = sm.z[zg][0] + half * 1024;
        float4 x[4][2];
#pragma unroll
        for (int ww = 0; ww < 4; ww++) {
          x[ww][0] = *reinterpret_cast<const float4*>(zb + ww * ZPB * 16 + roff0);
          x[ww][1] = *reinterpret_cast<const float4*>(zb + ww * ZPB * 16 + roff1);
        }
        const int sidx = half * 1024 + wtid * 8;
        const uint4 kvv = *reinterpret_cast<const uint4*>(&sm.u[c][UPAD + sidx]);
        if (half == 1 && c + 2 < CPC) bar_arrive(5 + zg, 256);
        uint4 o;
        o.x = pack2((x[0][0].x + x[1][0].x) + (x[2][0].x + x[3][0].x), (x[0][0].y + x[1][0].y) + (x[2][0].y + x[3][0].y));
        o.y = pack2((x[0][0].z + x[1][0].z) + (x[2][0].z + x[3][0].z), (x[0][0].w + x[1][0].w) + (x[2][0].w + x[3][0].w));
        o.z = pack2((x[0][1].x + x[1][1].x) + (x[2][1].x + x[3][1].x), (x[0][1].y + x[1][1].y) + (x[2][1].y + x[3][1].y));
        o.w = pack2((x[0][1].z + x[1][1].z) + (x[2][1].z + x[3][1].z), (x[0][1].w + x[1][1].w) + (x[2][1].w + x[3][1].w));
        o.x = b2u(__hadd2_rn(u2b(o.x), __hmul2_rn(u2b(kvv.x), d2)));
        o.y = b2u(__hadd2_rn(u2b(o.y), __hmul2_rn(u2b(kvv.y), d2)));
        o.z = b2u(__hadd2_rn(u2b(o.z), __hmul2_rn(u2b(kvv.z), d2)));
        o.w = b2u(__hadd2_rn(u2b(o.w), __hmul2_rn(u2b(kvv.w), d2)));
        st_pub4(g_y2 + ((64 * half + rpb) * 640 + c0 + c) * 2 + re2, enc4(o));
      }
    }
    STAMP(4);
    asm volatile("setmaxnreg.inc.sync.aligned.u32 168;");
  }

  if (tid < 128 || tid >= 256) {
    const int t = tid < 128 ? tid : tid - 128;
    const int ch = (t >> 1) * 5 + 4, hh = t & 1;
    const uint4 v = poll4(g_y2 + cta * 1280 + ch * 2 + hh);
    tile[hh * 640 + tile_perm(ch)] = v;
  }
  __syncthreads();
  STAMP(5);

  const int g = lane >> 2, tq = lane & 3;
  const int hh = wid & 1, gqi = wid >> 1;
  const int row = hh * 8 + g;
  uint32_t hreg[16], hnreg[16];
  if (wid < 10) {
    float cs[4] = {0.f, 0.f, 0.f, 0.f};
#pragma unroll
    for (int k = 0; k < 4; k++) {
      const int base = 32 * (4 * gqi + k);
      const int lch = base + 8 * ((lane & 7) >> 1) + 2 * (lane >> 3) + (lane & 1);
      uint32_t y[4];
      asm volatile("ldmatrix.sync.aligned.m8n8.x4.trans.shared.b16 {%0,%1,%2,%3}, [%4];"
                   : "=r"(y[0]), "=r"(y[1]), "=r"(y[2]), "=r"(y[3]) : "r"(smem_u32(&tile[hh * 640 + tile_perm(lch)])) : "memory");
      const uint4 qv4 = *reinterpret_cast<const uint4*>(&sm.q[row][base + 8 * tq]);
      const uint4 qn4 = *reinterpret_cast<const uint4*>(qn_s + row * QSTR + base + 8 * tq);
      hreg[4 * k + 0] = b2u(__hadd2_rn(u2b(qv4.x), __hmul2_rn(u2b(qn4.x), u2b(y[0]))));
      hreg[4 * k + 1] = b2u(__hadd2_rn(u2b(qv4.y), __hmul2_rn(u2b(qn4.y), u2b(y[1]))));
      hreg[4 * k + 2] = b2u(__hadd2_rn(u2b(qv4.z), __hmul2_rn(u2b(qn4.z), u2b(y[2]))));
      hreg[4 * k + 3] = b2u(__hadd2_rn(u2b(qv4.w), __hmul2_rn(u2b(qn4.w), u2b(y[3]))));
      mma_bf16(cs, hreg[4 * k + 0], hreg[4 * k + 1], 0x3F803F80u, 0x3F803F80u);
      mma_bf16(cs, hreg[4 * k + 2], hreg[4 * k + 3], 0x3F803F80u, 0x3F803F80u);
    }
    const float mean = cs[0] * (1.f / 128.f);
    float m2a = 0.f, m2b = 0.f;
#pragma unroll
    for (int i = 0; i < 16; i++) {
      const float a = lo_f(hreg[i]) - mean, b = hi_f(hreg[i]) - mean;
      m2a = fmaf(a, a, m2a); m2b = fmaf(b, b, m2b);
    }
    float m2 = m2a + m2b;
    m2 += __shfl_xor_sync(0xffffffffu, m2, 1);
    m2 += __shfl_xor_sync(0xffffffffu, m2, 2);
    if (tq == 0) sm.st[row][gqi] = make_float2(mean, m2);
  }
  STAMP(13);
  __syncthreads();
  if (wid < 10) {
    float mean = 0.f, m2 = 0.f;
    float2 p[5];
#pragma unroll
    for (int i = 0; i < 5; i++) { p[i] = sm.st[row][i]; mean += p[i].x; }
    mean *= 0.2f;
#pragma unroll
    for (int i = 0; i < 5; i++) { const float dl = p[i].x - mean; m2 += p[i].y + 128.f * dl * dl; }
    const float hd = rbf(sqrtf(rbf(rbf(m2 * (1.f / D_)) + 1e-5f)));
    const float hr = 1.f / hd;
    const bf162 hm2 = __float2bfloat162_rn(mean);
    float cr[4] = {0.f, 0.f, 0.f, 0.f};
#pragma unroll
    for (int k = 0; k < 4; k++) {
      const uint4 w4 = sm.wr[4 * (4 * gqi + k) + tq];
#pragma unroll
      for (int i = 0; i < 4; i++) {
        const uint32_t d = b2u(__hsub2_rn(u2b(hreg[4 * k + i]), hm2));
        hnreg[4 * k + i] = pack2(fdivr(lo_f(d), hd, hr), fdivr(hi_f(d), hd, hr));
      }
      mma_bf16(cr, hnreg[4 * k + 0], hnreg[4 * k + 1], w4.x, w4.y);
      mma_bf16(cr, hnreg[4 * k + 2], hnreg[4 * k + 3], w4.z, w4.w);
    }
    if (tq == 0) sm.rp[row][gqi] = cr[0];
  }
  STAMP(14);
  __syncthreads();
  uint32_t best;
  {
    const int rr = lane & 15;
    const float r = ((sm.rp[rr][0] + sm.rp[rr][1]) + (sm.rp[rr][2] + sm.rp[rr][3])) + sm.rp[rr][4];
    const uint32_t bits = __bfloat16_as_ushort(__float2bfloat16_rn(r));
    const uint32_t ord = (bits & 0x8000u) ? (bits ^ 0xFFFFu) : (bits ^ 0x8000u);
    const uint32_t key = (ord << 16) | 0x8000u | (uint32_t)(2047 - (cta * 16 + rr));
    best = __reduce_max_sync(0xffffffffu, key);
  }
  if (tid == 352) asm volatile("st.relaxed.gpu.global.u32 [%0], %1;" ::"l"(&g_keys[cta]), "r"(best) : "memory");
  STAMP(15);
  const int brow = (2047 - (int)(best & 0x7FFu)) - cta * 16;
  uint4 outv[4];
  if (wid < 10) {
#pragma unroll
    for (int k = 0; k < 4; k++) {
      outv[k].x = b2u(__hadd2_rn(u2b(hreg[4 * k + 0]), u2b(hnreg[4 * k + 0])));
      outv[k].y = b2u(__hadd2_rn(u2b(hreg[4 * k + 1]), u2b(hnreg[4 * k + 1])));
      outv[k].z = b2u(__hadd2_rn(u2b(hreg[4 * k + 2]), u2b(hnreg[4 * k + 2])));
      outv[k].w = b2u(__hadd2_rn(u2b(hreg[4 * k + 3]), u2b(hnreg[4 * k + 3])));
      const int chunk = 4 * (4 * gqi + k) + tq;
      if (row == brow) {
        st_pub4(&g_cand[cta][0][chunk], enc4(make_uint4(hnreg[4 * k], hnreg[4 * k + 1], hnreg[4 * k + 2], hnreg[4 * k + 3])));
        st_pub4(&g_cand[cta][1][chunk], enc4(make_uint4(hreg[4 * k], hreg[4 * k + 1], hreg[4 * k + 2], hreg[4 * k + 3])));
      } else {
        *reinterpret_cast<uint4*>(gout + (size_t)(cta * 16 + row) * D_ + chunk * 8) = outv[k];
      }
    }
  }
  STAMP(6);
  if (wid == 11) {
    const uint4* kp = reinterpret_cast<const uint4*>(g_keys) + lane;
    uint4 v = ld_poll4(kp);
    int it = 0;
    while (!ready4(v) && ++it < SPIN_LIMIT) v = ld_poll4(kp);
    const uint32_t m = max(max(v.x, v.y), max(v.z, v.w));
    const uint32_t wk = __reduce_max_sync(0xffffffffu, m);
    if (lane == 0) sm.win = wk;
  }
  __syncthreads();
  const uint32_t win = sm.win;
  const int wrow = 2047 - (int)(win & 0x7FFu);
  const int wcta = wrow >> 4;
  if (wid < 10 && row == brow && wcta != cta) {
#pragma unroll
    for (int k = 0; k < 4; k++)
      *reinterpret_cast<uint4*>(gout + (size_t)(cta * 16 + row) * D_ + (4 * (4 * gqi + k) + tq) * 8) = outv[k];
  }
  STAMP(7);
  if (cta < N1 + N2) mbar_wait(&sm.mbarw);
  float* xs = &sm.z[0][0][0];
  float* part = xs + 2048;
  if (cta < N1) {
    if (tid < 80) {
      const uint4 v = poll4(&g_cand[wcta][0][tid]);
      float4* xp = reinterpret_cast<float4*>(xs + tid * 8);
      xp[0] = make_float4(lo_f(v.x), hi_f(v.x), lo_f(v.y), hi_f(v.y));
      xp[1] = make_float4(lo_f(v.z), hi_f(v.z), lo_f(v.w), hi_f(v.w));
    }
    __syncthreads();
    const int m = wid / 6, hc = (wid % 6) >> 1, rs = (wid & 1) * 32 + lane;
    float a[8];
#pragma unroll
    for (int j = 0; j < 8; j++) a[j] = 0.f;
#pragma unroll
    for (int it = 0; it < 10; it++) {
      const int r = rs + 64 * it;
      const uint4 wv = sm.w[m * 1920 + r * 3 + hc];
      const float x = xs[r];
      a[0] = fmaf(x, lo_f(wv.x), a[0]); a[1] = fmaf(x, hi_f(wv.x), a[1]);
      a[2] = fmaf(x, lo_f(wv.y), a[2]); a[3] = fmaf(x, hi_f(wv.y), a[3]);
      a[4] = fmaf(x, lo_f(wv.z), a[4]); a[5] = fmaf(x, hi_f(wv.z), a[5]);
      a[6] = fmaf(x, lo_f(wv.w), a[6]); a[7] = fmaf(x, hi_f(wv.w), a[7]);
    }
    {
      const bool up = lane & 16;
#pragma unroll
      for (int j = 0; j < 4; j++) {
        const float send = up ? a[j] : a[j + 4], keep = up ? a[j + 4] : a[j];
        a[j] = keep + __shfl_xor_sync(0xffffffffu, send, 16);
      }
      const bool up2 = lane & 8;
#pragma unroll
      for (int j = 0; j < 2; j++) {
        const float send = up2 ? a[j] : a[j + 2], keep = up2 ? a[j + 2] : a[j];
        a[j] = keep + __shfl_xor_sync(0xffffffffu, send, 8);
      }
      const bool up3 = lane & 4;
      const float send = up3 ? a[0] : a[1], keep = up3 ? a[1] : a[0];
      a[0] = keep + __shfl_xor_sync(0xffffffffu, send, 4);
      a[0] += __shfl_xor_sync(0xffffffffu, a[0], 2);
      a[0] += __shfl_xor_sync(0xffffffffu, a[0], 1);
      if ((lane & 3) == 0) part[wid * 8 + (lane >> 2)] = a[0];
    }
    __syncthreads();
    if (wid == 0) {
      uint32_t bits = 0;
      if (lane < 24) {
        const int hc2 = lane >> 3, j = lane & 7;
        const float gt = rbf(part[(2 * hc2) * 8 + j] + part[(2 * hc2 + 1) * 8 + j]);
        const float up = rbf(part[(6 + 2 * hc2) * 8 + j] + part[(6 + 2 * hc2 + 1) * 8 + j]);
        const float sg = rbf(gt / (1.f + __expf(-gt)));
        bits = __bfloat16_as_ushort(__float2bfloat16_rn(sg * up));
      }
      const uint32_t nb = __shfl_down_sync(0xffffffffu, bits, 1);
      const uint32_t pw = bits | (nb << 16);
      const uint32_t w1 = __shfl_down_sync(0xffffffffu, pw, 2), w2 = __shfl_down_sync(0xffffffffu, pw, 4), w3 = __shfl_down_sync(0xffffffffu, pw, 6);
      if (lane < 24 && (lane & 7) == 0) st_pub4(&g_act[cta * 3 + (lane >> 3)], enc4(make_uint4(pw, w1, w2, w3)));
    }
  } else if (cta < N1 + N2) {
    const int j2 = cta - N1;
    uint4 rowv = make_uint4(0, 0, 0, 0);
    if (tid < 192) {
      const uint4 v = poll4(&g_act[tid]);
      float4* xp = reinterpret_cast<float4*>(xs + tid * 8);
      xp[0] = make_float4(lo_f(v.x), hi_f(v.x), lo_f(v.y), hi_f(v.y));
      xp[1] = make_float4(lo_f(v.z), hi_f(v.z), lo_f(v.w), hi_f(v.w));
    } else if (tid < 196) {
      const int t = tid - 192;
      rowv = poll4(&g_cand[wcta][t >> 1][j2 * 2 + (t & 1)]);
      reinterpret_cast<uint4*>(part + 256)[t] = rowv;
    }
    __syncthreads();
    const int hc = lane & 1, rs = wid * 16 + (lane >> 1);
    float a[8];
#pragma unroll
    for (int j = 0; j < 8; j++) a[j] = 0.f;
#pragma unroll
    for (int it = 0; it < 8; it++) {
      const int r = rs + 192 * it;
      const uint4 wv = sm.w[r * 2 + hc];
      const float x = xs[r];
      a[0] = fmaf(x, lo_f(wv.x), a[0]); a[1] = fmaf(x, hi_f(wv.x), a[1]);
      a[2] = fmaf(x, lo_f(wv.y), a[2]); a[3] = fmaf(x, hi_f(wv.y), a[3]);
      a[4] = fmaf(x, lo_f(wv.z), a[4]); a[5] = fmaf(x, hi_f(wv.z), a[5]);
      a[6] = fmaf(x, lo_f(wv.w), a[6]); a[7] = fmaf(x, hi_f(wv.w), a[7]);
    }
    {
      const bool up = lane & 16;
#pragma unroll
      for (int j = 0; j < 4; j++) {
        const float send = up ? a[j] : a[j + 4], keep = up ? a[j + 4] : a[j];
        a[j] = keep + __shfl_xor_sync(0xffffffffu, send, 16);
      }
      const bool up2 = lane & 8;
#pragma unroll
      for (int j = 0; j < 2; j++) {
        const float send = up2 ? a[j] : a[j + 2], keep = up2 ? a[j + 2] : a[j];
        a[j] = keep + __shfl_xor_sync(0xffffffffu, send, 8);
      }
      const bool up3 = lane & 4;
      const float send = up3 ? a[0] : a[1], keep = up3 ? a[1] : a[0];
      a[0] = keep + __shfl_xor_sync(0xffffffffu, send, 4);
      a[0] += __shfl_xor_sync(0xffffffffu, a[0], 2);
      if ((lane & 2) == 0) part[wid * 16 + hc * 8 + (lane >> 2)] = a[0];
    }
    __syncthreads();
    if (tid < 16) {
      float y = 0.f;
#pragma unroll
      for (int i = 0; i < 12; i++) y += part[i * 16 + tid];
      const uint32_t ord = win >> 16;
      const uint32_t rb = (ord & 0x8000u) ? (ord ^ 0x8000u) : (ord ^ 0xFFFFu);
      const float r = __uint_as_float(rb << 16);
      const float sg = rbf(1.f / (1.f + __expf(-r)));
      const float yy = rbf(rbf(y) * sg);
      const unsigned short* rv = reinterpret_cast<const unsigned short*>(part + 256);
      const float hn = __uint_as_float((uint32_t)rv[tid] << 16), h = __uint_as_float((uint32_t)rv[16 + tid] << 16);
      gout[(size_t)wrow * D_ + j2 * 16 + tid] = __float2bfloat16_rn(h + rbf(hn + yy));
    }
  }
  STAMP(8);
}

}

typedef CUresult (*EncodeFn)(CUtensorMap*, CUtensorMapDataType, cuuint32_t, void*, const cuuint64_t*, const cuuint64_t*,
                             const cuuint32_t*, const cuuint32_t*, CUtensorMapInterleave, CUtensorMapSwizzle,
                             CUtensorMapL2promotion, CUtensorMapFloatOOBfill);

extern "C" void kernel_launch(void* const* d_in, const int* in_sizes, int n_in, void* d_out, int out_size) {
  (void)in_sizes; (void)n_in; (void)out_size;
  static EncodeFn encode = nullptr;
  static CUtensorMap tmg, tmu, tmd;
  static void* cached[3] = {nullptr, nullptr, nullptr};
  if (!encode) {
    cudaFuncSetAttribute(fused_kernel, cudaFuncAttributeMaxDynamicSharedMemorySize, (int)sizeof(Smem));
    void* fn = nullptr;
    cudaDriverEntryPointQueryResult qr;
    cudaGetDriverEntryPoint("cuTensorMapEncodeTiled", &fn, cudaEnableDefault, &qr);
    encode = (EncodeFn)fn;
  }
  if (cached[0] != d_in[8] || cached[1] != d_in[9] || cached[2] != d_in[10]) {
    const cuuint32_t es[2] = {1, 1};
    {
      const cuuint64_t dims[2] = {F_, D_}, strides[1] = {F_ * 2};
      const cuuint32_t box[2] = {24, 160};
      encode(&tmg, CU_TENSOR_MAP_DATA_TYPE_BFLOAT16, 2, d_in[8], dims, strides, box, es, CU_TENSOR_MAP_INTERLEAVE_NONE,
             CU_TENSOR_MAP_SWIZZLE_NONE, CU_TENSOR_MAP_L2_PROMOTION_NONE, CU_TENSOR_MAP_FLOAT_OOB_FILL_NONE);
      encode(&tmu, CU_TENSOR_MAP_DATA_TYPE_BFLOAT16, 2, d_in[9], dims, strides, box, es, CU_TENSOR_MAP_INTERLEAVE_NONE,
             CU_TENSOR_MAP_SWIZZLE_NONE, CU_TENSOR_MAP_L2_PROMOTION_NONE, CU_TENSOR_MAP_FLOAT_OOB_FILL_NONE);
    }
    {
      const cuuint64_t dims[2] = {D_, F_}, strides[1] = {D_ * 2};
      const cuuint32_t box[2] = {16, 256};
      encode(&tmd, CU_TENSOR_MAP_DATA_TYPE_BFLOAT16, 2, d_in[10], dims, strides, box, es, CU_TENSOR_MAP_INTERLEAVE_NONE,
             CU_TENSOR_MAP_SWIZZLE_NONE, CU_TENSOR_MAP_L2_PROMOTION_NONE, CU_TENSOR_MAP_FLOAT_OOB_FILL_NONE);
    }
    cached[0] = d_in[8]; cached[1] = d_in[9]; cached[2] = d_in[10];
  }
  fused_kernel<<<NCTA, NTHR, sizeof(Smem), cudaStreamPerThread>>>(
      tmg, tmu, tmd, (const bf16*)d_in[0], (const bf16*)d_in[1], (const bf16*)d_in[2], (const bf16*)d_in[3],
      (const bf16*)d_in[4], (const bf16*)d_in[5], (const bf16*)d_in[7], (bf16*)d_out);
}
```

```cpp
#include <cuda_runtime.h>
#include <cuda_bf16.h>
#include <cuda.h>
#include <stdint.h>

namespace {

typedef __nv_bfloat16 bf16;
typedef __nv_bfloat162 bf162;

constexpr int S_ = 2048, D_ = 640, F_ = 1536;
constexpr int NCTA = 128, CPC = 5, NTHR = 384;
constexpr int UPAD = 136, USTR = 2192;
constexpr int TABW = 1040;
constexpr int ZPB = 132;
constexpr int QSTR = 648;
constexpr int N1 = 64;
constexpr int N2 = 40;
constexpr int SPIN_LIMIT = 1 << 19;
#define POLL_NS 100
#define H_DELAY 2000
#define Q_DELAY 4500

struct __align__(128) Smem {
  uint32_t tabA[3][2][TABW];
  uint32_t extra[1024];
  uint32_t tabB[2][2][TABW];
  bf16 u[CPC][USTR];
  float z[2][4][ZPB * 16];
  bf16 q[16][QSTR];
  alignas(128) uint4 w[3840];
  uint4 wr[80];
  float2 st[16][5];
  float rp[16][5];
  unsigned long long mbar;
  unsigned long long mbarw;
  unsigned long long mbarc;
  unsigned long long mbarh;
  uint32_t target;
  uint32_t best;
  uint32_t win;
};

__device__ uint4 g_kv[D_ * S_ / 8];
__device__ uint4 g_y2[D_ * S_ / 8];
__device__ uint32_t g_keys[NCTA];
__device__ uint4 g_cand[NCTA][2][80];
__device__ uint4 g_act[F_ / 8];
__device__ unsigned int g_ctr;
__device__ unsigned int g_ctr2;
#define STAMP(i)
#define CST(c, i)

__device__ __forceinline__ uint32_t smem_u32(const void* p) { return (uint32_t)__cvta_generic_to_shared(p); }
__device__ __forceinline__ void wg_fence() { asm volatile("wgmma.fence.sync.aligned;" ::: "memory"); }
__device__ __forceinline__ void wg_commit() { asm volatile("wgmma.commit_group.sync.aligned;" ::: "memory"); }
template <int N> __device__ __forceinline__ void wg_wait() { asm volatile("wgmma.wait_group.sync.aligned %0;" ::"n"(N) : "memory"); }
__device__ __forceinline__ void bar_sync(int id, int n) { asm volatile("bar.sync %0, %1;" ::"r"(id), "r"(n) : "memory"); }
__device__ __forceinline__ void bar_arrive(int id, int n) { asm volatile("bar.arrive %0, %1;" ::"r"(id), "r"(n) : "memory"); }
__device__ __forceinline__ bf162 u2b(uint32_t u) { return *reinterpret_cast<bf162*>(&u); }
__device__ __forceinline__ uint32_t b2u(bf162 b) { return *reinterpret_cast<uint32_t*>(&b); }
__device__ __forceinline__ float lo_f(uint32_t u) { return __uint_as_float(u << 16); }
__device__ __forceinline__ float hi_f(uint32_t u) { return __uint_as_float(u & 0xFFFF0000u); }
__device__ __forceinline__ float rbf(float x) { return __bfloat162float(__float2bfloat16_rn(x)); }
__device__ __forceinline__ uint32_t pack2(float a, float b) { return b2u(__floats2bfloat162_rn(a, b)); }
__device__ __forceinline__ uint32_t enc(uint32_t w) { return max(~w, 1u); }
__device__ __forceinline__ uint4 enc4(uint4 v) { return make_uint4(enc(v.x), enc(v.y), enc(v.z), enc(v.w)); }
__device__ __forceinline__ uint4 ld_poll4(const uint4* p) {
  uint4 v;
  asm volatile("ld.relaxed.gpu.global.v4.u32 {%0,%1,%2,%3}, [%4];" : "=r"(v.x), "=r"(v.y), "=r"(v.z), "=r"(v.w) : "l"(p) : "memory");
  return v;
}
__device__ __forceinline__ bool ready4(uint4 v) { return v.x != 0u && v.y != 0u && v.z != 0u && v.w != 0u; }
__device__ __forceinline__ uint4 poll4(const uint4* p) {
  uint4 v = ld_poll4(p);
  int it = 0;
  while (!ready4(v) && ++it < SPIN_LIMIT) v = ld_poll4(p);
  return make_uint4(~v.x, ~v.y, ~v.z, ~v.w);
}
__device__ __forceinline__ void st_pub4(uint4* p, uint4 v) {
  asm volatile("st.relaxed.gpu.global.v4.u32 [%0], {%1,%2,%3,%4};" ::"l"(p), "r"(v.x), "r"(v.y), "r"(v.z), "r"(v.w) : "memory");
}
__device__ __forceinline__ void st_pub2(uint2* p, uint32_t a, uint32_t b) {
  asm volatile("st.relaxed.gpu.global.v2.u32 [%0], {%1,%2};" ::"l"(p), "r"(a), "r"(b) : "memory");
}
__device__ __forceinline__ void mma_bf16(float (&c)[4], uint32_t a0, uint32_t a2, uint32_t b0, uint32_t b1) {
  asm volatile("mma.sync.aligned.m16n8k16.row.col.f32.bf16.bf16.f32 {%0,%1,%2,%3}, {%4,%5,%6,%5}, {%7,%8}, {%0,%1,%2,%3};"
               : "+f"(c[0]), "+f"(c[1]), "+f"(c[2]), "+f"(c[3]) : "r"(a0), "r"(0u), "r"(a2), "r"(b0), "r"(b1));
}
__device__ __forceinline__ void mbar_wait(const unsigned long long* bar) {
  const uint32_t mb = smem_u32(bar);
  uint32_t ok = 0;
  int it = 0;
  while (!ok && ++it < SPIN_LIMIT)
    asm volatile("{ .reg .pred p; mbarrier.try_wait.parity.shared.b64 p, [%1], 0; selp.u32 %0, 1, 0, p; }" : "=r"(ok) : "r"(mb) : "memory");
}
__device__ __forceinline__ void bulk_g2s(void* dst, const void* src, uint32_t bytes, const unsigned long long* bar) {
  asm volatile("cp.async.bulk.shared::cluster.global.mbarrier::complete_tx::bytes [%0], [%1], %2, [%3];" ::"r"(smem_u32(dst)),
               "l"(src), "r"(bytes), "r"(smem_u32(bar)) : "memory");
}
__device__ __forceinline__ void mbar_expect(const unsigned long long* bar, uint32_t bytes) {
  asm volatile("mbarrier.arrive.expect_tx.shared.b64 _, [%0], %1;" ::"r"(smem_u32(bar)), "r"(bytes) : "memory");
}
__device__ __forceinline__ float fdivr(float a, float d, float r) {
  float q = a * r;
  float e = fmaf(-q, d, a);
  return fmaf(e, r, q);
}

template <bool FIRST> __device__ __forceinline__ void wgmma32(float (&d)[16], const uint32_t* a, uint64_t desc) {
  if (FIRST) {
    asm volatile("wgmma.mma_async.sync.aligned.m64n32k16.f32.bf16.bf16 {%0,%1,%2,%3,%4,%5,%6,%7,%8,%9,%10,%11,%12,%13,%14,%15}, {%16,%17,%18,%19}, %20, 0, 1, 1, 0;"
                 : "+f"(d[0]), "+f"(d[1]), "+f"(d[2]), "+f"(d[3]), "+f"(d[4]), "+f"(d[5]), "+f"(d[6]), "+f"(d[7]),
                   "+f"(d[8]), "+f"(d[9]), "+f"(d[10]), "+f"(d[11]), "+f"(d[12]), "+f"(d[13]), "+f"(d[14]), "+f"(d[15])
                 : "r"(a[0]), "r"(a[1]), "r"(a[2]), "r"(a[3]), "l"(desc));
  } else {
    asm volatile("wgmma.mma_async.sync.aligned.m64n32k16.f32.bf16.bf16 {%0,%1,%2,%3,%4,%5,%6,%7,%8,%9,%10,%11,%12,%13,%14,%15}, {%16,%17,%18,%19}, %20, 1, 1, 1, 0;"
                 : "+f"(d[0]), "+f"(d[1]), "+f"(d[2]), "+f"(d[3]), "+f"(d[4]), "+f"(d[5]), "+f"(d[6]), "+f"(d[7]),
                   "+f"(d[8]), "+f"(d[9]), "+f"(d[10]), "+f"(d[11]), "+f"(d[12]), "+f"(d[13]), "+f"(d[14]), "+f"(d[15])
                 : "r"(a[0]), "r"(a[1]), "r"(a[2]), "r"(a[3]), "l"(desc));
  }
}

template <int G> __device__ __forceinline__ void load_a(uint32_t (&a)[8], const uint32_t* tp) {
#pragma unroll
  for (int q = 0; q < 2; q++) {
    const int e = 2 * G + q;
    a[4 * q + 0] = tp[-64 * e];
    a[4 * q + 1] = tp[-64 * e - 32];
    a[4 * q + 2] = tp[-64 * e + 4];
    a[4 * q + 3] = tp[-64 * e - 28];
  }
}
__device__ __forceinline__ void load_a_all(uint32_t (&a)[8][8], const uint32_t* tp) {
  load_a<0>(a[0], tp); load_a<1>(a[1], tp); load_a<2>(a[2], tp); load_a<3>(a[3], tp);
  load_a<4>(a[4], tp); load_a<5>(a[5], tp); load_a<6>(a[6], tp); load_a<7>(a[7], tp);
}
template <int G> __device__ __forceinline__ void issue_g(float (&acc)[8][16], uint32_t (&a)[8], uint64_t desc0) {
  wg_fence();
#pragma unroll
  for (int q = 0; q < 2; q++) {
#pragma unroll
    for (int b = G; b < 8; b++) {
      const int delta = 2 * b - (2 * G + q);
      if (G == 0 && q == 0) wgmma32<true>(acc[b], &a[4 * q], desc0 + (uint64_t)(int64_t)(16 * delta));
      else wgmma32<false>(acc[b], &a[4 * q], desc0 + (uint64_t)(int64_t)(16 * delta));
    }
  }
  wg_commit();
}
template <int B> __device__ __forceinline__ void fence_blk(float (&acc)[8][16]) {
#pragma unroll
  for (int i = 0; i < 16; i++) asm volatile("" : "+f"(acc[B][i])::"memory");
}
__device__ __forceinline__ void fence_a(uint32_t (&a)[8]) {
#pragma unroll
  for (int i = 0; i < 8; i++) asm volatile("" : "+r"(a[i])::"memory");
}
template <int B> __device__ __forceinline__ void sts_blk(float (&acc)[8][16], float* zw, int off_even, int off_odd) {
#pragma unroll
  for (int jj = 0; jj < 4; jj++) {
    const int j = 4 * B + jj;
    float p0 = acc[B][4 * jj + 0], p1 = acc[B][4 * jj + 1];
    if (jj > 0) { p0 += acc[B][4 * (jj - 1) + 2]; p1 += acc[B][4 * (jj - 1) + 3]; }
    else if (B > 0) { p0 += acc[B > 0 ? B - 1 : 0][14]; p1 += acc[B > 0 ? B - 1 : 0][15]; }
    zw[64 * j + off_even] = p0;
    zw[64 * j + off_odd] = p1;
  }
}
__device__ __forceinline__ int tab_off(int c) { return c == 4 ? 0 : (c + 1) * 2 * TABW + (c >= 2 ? 1024 : 0); }
__device__ __forceinline__ int tile_perm(int ch) { return ch ^ (((ch >> 3) & 3) << 1); }

__device__ __forceinline__ void wait_ctr(const unsigned int* ctr, uint32_t target) {
  uint32_t v;
  int it = 0;
  do {
    asm volatile("ld.acquire.gpu.global.u32 %0, [%1];" : "=r"(v) : "l"(ctr) : "memory");
  } while ((int)(v - target) < 0 && ++it < SPIN_LIMIT);
}

__device__ __forceinline__ void ln_q_rows(Smem& sm, bf16* qn_s, int row, int lane) {
      const uint32_t* qp = reinterpret_cast<const uint32_t*>(&sm.q[row][0]);
      uint32_t qa[10], qb[10];
      float sa = 0.f, sb = 0.f;
#pragma unroll
      for (int i = 0; i < 10; i++) {
        qa[i] = qp[lane + 32 * i]; qb[i] = qp[QSTR / 2 + lane + 32 * i];
        sa += lo_f(qa[i]) + hi_f(qa[i]); sb += lo_f(qb[i]) + hi_f(qb[i]);
      }
#pragma unroll
      for (int o = 16; o > 0; o >>= 1) { sa += __shfl_xor_sync(0xffffffffu, sa, o); sb += __shfl_xor_sync(0xffffffffu, sb, o); }
      sa *= (1.f / D_); sb *= (1.f / D_);
      float ma = 0.f, mb2 = 0.f;
#pragma unroll
      for (int i = 0; i < 10; i++) {
        const float x = lo_f(qa[i]) - sa, y = hi_f(qa[i]) - sa, z = lo_f(qb[i]) - sb, t = hi_f(qb[i]) - sb;
        ma = fmaf(x, x, fmaf(y, y, ma)); mb2 = fmaf(z, z, fmaf(t, t, mb2));
      }
#pragma unroll
      for (int o = 16; o > 0; o >>= 1) { ma += __shfl_xor_sync(0xffffffffu, ma, o); mb2 += __shfl_xor_sync(0xffffffffu, mb2, o); }
      const float da = rbf(sqrtf(rbf(rbf(ma * (1.f / D_)) + 1e-5f))), db = rbf(sqrtf(rbf(rbf(mb2 * (1.f / D_)) + 1e-5f)));
      const float ra = 1.f / da, rb = 1.f / db;
      const bf162 ma2 = __float2bfloat162_rn(sa), mb3 = __float2bfloat162_rn(sb);
      uint32_t* np = reinterpret_cast<uint32_t*>(qn_s + row * QSTR);
#pragma unroll
      for (int i = 0; i < 10; i++) {
        const uint32_t d = b2u(__hsub2_rn(u2b(qa[i]), ma2)), e = b2u(__hsub2_rn(u2b(qb[i]), mb3));
        np[lane + 32 * i] = pack2(fdivr(lo_f(d), da, ra), fdivr(hi_f(d), da, ra));
        np[QSTR / 2 + lane + 32 * i] = pack2(fdivr(lo_f(e), db, rb), fdivr(hi_f(e), db, rb));
      }
}

__global__ void __launch_bounds__(NTHR, 1)
fused_kernel(const __grid_constant__ CUtensorMap tmg, const __grid_constant__ CUtensorMap tmu,
             const __grid_constant__ CUtensorMap tmd, const bf16* __restrict__ gq, const bf16* __restrict__ gk, const bf16* __restrict__ gv,
             const bf16* __restrict__ gsk, const bf16* __restrict__ gh, const bf16* __restrict__ gD,
             const bf16* __restrict__ gwr, bf16* __restrict__ gout) {
  extern __shared__ __align__(128) unsigned char smraw[];
  Smem& sm = *reinterpret_cast<Smem*>(smraw);
  const int tid = threadIdx.x;
  const int cta = blockIdx.x;
  const int c0 = cta * CPC;
  const int lane = tid & 31;
  const int wid = tid >> 5;
  STAMP(0);
  const long long tstart = clock64();

  {
    uint4* hs = reinterpret_cast<uint4*>(&sm.z[0][0][0]);
    const int oc = tid >> 2;
    const int r0 = cta * 16 + (tid & 3) * 4;
    uint4 kk[7], vv[4], sk[4];
    if (tid < 320) {
      const uint4* kp = reinterpret_cast<const uint4*>(gk) + (size_t)r0 * 80 + oc;
      const uint4* vp = reinterpret_cast<const uint4*>(gv) + (size_t)r0 * 80 + oc;
#pragma unroll
      for (int i = 0; i < 7; i++) kk[i] = (i >= 3 || r0 > 0) ? __ldg(kp + (i - 3) * 80) : make_uint4(0, 0, 0, 0);
#pragma unroll
      for (int i = 0; i < 4; i++) vv[i] = __ldg(vp + i * 80);
#pragma unroll
      for (int i = 0; i < 4; i++) sk[i] = __ldg(reinterpret_cast<const uint4*>(gsk) + oc * 4 + i);
    } else if (tid == 320) {
      asm volatile("mbarrier.init.shared.b64 [%0], 1;" ::"r"(smem_u32(&sm.mbarh)) : "memory");
      asm volatile("mbarrier.init.shared.b64 [%0], 1;" ::"r"(smem_u32(&sm.mbar)) : "memory");
      asm volatile("mbarrier.init.shared.b64 [%0], 1;" ::"r"(smem_u32(&sm.mbarw)) : "memory");
      asm volatile("mbarrier.init.shared.b64 [%0], 1;" ::"r"(smem_u32(&sm.mbarc)) : "memory");
      asm volatile("fence.proxy.async.shared::cta;" ::: "memory");
    }
    if (tid < 320) bar_sync(6, 384); else { bar_arrive(6, 384); bar_sync(5, 64); }
    STAMP(9);
    if (tid < 320) {
      uint32_t o[4][4];
#pragma unroll
      for (int p = 0; p < 4; p++) {
        const bf162 w0 = u2b(__byte_perm(sk[p].x, sk[p].z, 0x5410)), w1 = u2b(__byte_perm(sk[p].x, sk[p].z, 0x7632));
        const bf162 w2 = u2b(__byte_perm(sk[p].y, sk[p].w, 0x5410)), w3 = u2b(__byte_perm(sk[p].y, sk[p].w, 0x7632));
        uint32_t kv[4];
#pragma unroll
        for (int i = 0; i < 4; i++) {
          const uint32_t k0 = p == 0 ? kk[i].x : p == 1 ? kk[i].y : p == 2 ? kk[i].z : kk[i].w;
          const uint32_t k1 = p == 0 ? kk[i + 1].x : p == 1 ? kk[i + 1].y : p == 2 ? kk[i + 1].z : kk[i + 1].w;
          const uint32_t k2 = p == 0 ? kk[i + 2].x : p == 1 ? kk[i + 2].y : p == 2 ? kk[i + 2].z : kk[i + 2].w;
          const uint32_t k3 = p == 0 ? kk[i + 3].x : p == 1 ? kk[i + 3].y : p == 2 ? kk[i + 3].z : kk[i + 3].w;
          const uint32_t vx = p == 0 ? vv[i].x : p == 1 ? vv[i].y : p == 2 ? vv[i].z : vv[i].w;
          bf162 a = __hmul2_rn(u2b(k0), w3);
          a = __hadd2_rn(a, __hmul2_rn(u2b(k1), w2));
          a = __hadd2_rn(a, __hmul2_rn(u2b(k2), w1));
          a = __hadd2_rn(a, __hmul2_rn(u2b(k3), w0));
          kv[i] = b2u(__hmul2_rn(a, u2b(vx)));
        }
        o[p][0] = enc(__byte_perm(kv[0], kv[1], 0x5410)); o[p][1] = enc(__byte_perm(kv[2], kv[3], 0x5410));
        o[p][2] = enc(__byte_perm(kv[0], kv[1], 0x7632)); o[p][3] = enc(__byte_perm(kv[2], kv[3], 0x7632));
      }
      uint2* dst = reinterpret_cast<uint2*>(g_kv) + (size_t)(oc * 8) * 512 + (r0 >> 2);
#pragma unroll
      for (int p = 0; p < 4; p++) {
        st_pub2(dst + (2 * p) * 512, o[p][0], o[p][1]);
        st_pub2(dst + (2 * p + 1) * 512, o[p][2], o[p][3]);
      }
      STAMP(10);
      if (wid == 0) bar_sync(4, 320); else bar_arrive(4, 320);
      if (tid == 0) {
        const unsigned old = atomicAdd(&g_ctr2, 1u);
        const unsigned target = (old / NCTA + 1u) * NCTA;
        uint32_t v;
        int it = 0;
        do {
          asm volatile("ld.relaxed.gpu.global.u32 %0, [%1];" : "=r"(v) : "l"(&g_ctr2) : "memory");
        } while ((int)(v - target) < 0 && ++it < SPIN_LIMIT);
        asm volatile("mbarrier.arrive.shared.b64 _, [%0];" ::"r"(smem_u32(&sm.mbarc)) : "memory");
      }
      __syncwarp();
    } else {
      const int t0 = tid - 320;
      const uint4 zz = make_uint4(0, 0, 0, 0);
      if (tid == 320) {
        while (clock64() - tstart < H_DELAY) {}
        mbar_expect(&sm.mbarh, CPC * S_ * 2);
        bulk_g2s(hs, gh + (size_t)c0 * S_, CPC * S_ * 2, &sm.mbarh);
      }
      __syncwarp();
      for (int t = t0; t < CPC * 17; t += 64) *reinterpret_cast<uint4*>(&sm.u[t / 17][(t % 17) * 8]) = zz;
      if (t0 < 40) *reinterpret_cast<uint4*>(&sm.tabA[0][0][0] + tab_off(t0 >> 3) + ((t0 >> 2) & 1) * TABW + 1024 + 4 * (t0 & 3)) = zz;
      while (clock64() - tstart < Q_DELAY) {}
      if (tid == 320) {
        mbar_expect(&sm.mbar, 17 * D_ * 2);
#pragma unroll 1
        for (int r = 0; r < 16; r++) bulk_g2s(&sm.q[r][0], gq + (size_t)(cta * 16 + r) * D_, D_ * 2, &sm.mbar);
        bulk_g2s(&sm.wr[0], gwr, D_ * 2, &sm.mbar);
      }
      __syncwarp();
#pragma unroll 4
      for (int i = 0; i < 20; i++) g_y2[cta * 1280 + t0 + 64 * i] = zz;
      (&g_cand[cta][0][0])[t0] = zz;
      (&g_cand[cta][0][0])[64 + t0] = zz;
      if (t0 < 32) (&g_cand[cta][0][0])[128 + t0] = zz;
      else if (t0 < 35) { if (cta < N1) g_act[cta * 3 + (t0 - 32)] = zz; }
      else if (t0 == 35) g_keys[cta] = 0u;
      bar_sync(5, 64);
      if (tid == 352) {
        __threadfence();
        const unsigned old = atomicAdd(&g_ctr, 1u);
        sm.target = (old / NCTA + 1u) * NCTA;
      }
      __syncwarp();
    }
    mbar_wait(&sm.mbarh);
#pragma unroll
    for (int i = 0; i < 4; i++) {
      const int t = (NTHR - 1 - tid) + NTHR * i;
      if (t < CPC * 256) {
        uint32_t* tb = &sm.tabA[0][0][0] + tab_off(t >> 8) + (255 - (t & 255)) * 4;
        const uint4 h = hs[t];
        const uint32_t hp = (t & 255) ? reinterpret_cast<const uint32_t*>(hs)[4 * t - 1] : 0u;
        uint4 r1, rr;
        r1.x = __byte_perm(h.w, 0, 0x1032); r1.y = __byte_perm(h.z, 0, 0x1032);
        r1.z = __byte_perm(h.y, 0, 0x1032); r1.w = __byte_perm(h.x, 0, 0x1032);
        rr.x = __byte_perm(h.w, h.z, 0x7610); rr.y = __byte_perm(h.z, h.y, 0x7610);
        rr.z = __byte_perm(h.y, h.x, 0x7610); rr.w = __byte_perm(h.x, hp, 0x7610);
        *reinterpret_cast<uint4*>(tb) = rr;
        *reinterpret_cast<uint4*>(tb + TABW) = r1;
      }
    }
    STAMP(12);
  }
  mbar_wait(&sm.mbarc);
  {
    uint4 v[4];
    uint4* src = g_kv + c0 * 256 + tid;
#pragma unroll
    for (int i = 0; i < 4; i++) if (i < 3 || tid < 128) v[i] = ld_poll4(src + NTHR * i);
#pragma unroll
    for (int i = 0; i < 4; i++) {
      if (i < 3 || tid < 128) {
        int it = 0;
        while (!ready4(v[i]) && ++it < SPIN_LIMIT) { __nanosleep(POLL_NS); v[i] = ld_poll4(src + NTHR * i); }
        const int t = tid + NTHR * i;
        *reinterpret_cast<uint4*>(&sm.u[t >> 8][UPAD + (t & 255) * 8]) = make_uint4(~v[i].x, ~v[i].y, ~v[i].z, ~v[i].w);
      }
    }
    STAMP(11);
    asm volatile("fence.proxy.async.shared::cta;" ::: "memory");
    __syncthreads();
#pragma unroll
    for (int i = 0; i < 4; i++) if (i < 3 || tid < 128) src[NTHR * i] = make_uint4(0, 0, 0, 0);
    if (tid >= 256) {
      const int t0 = tid - 256;
      if (((t0 & 15) >> 2) < ((t0 >> 4) & 3))
        *reinterpret_cast<uint4*>(&sm.z[t0 >> 6][(t0 >> 4) & 3][(t0 & 15) * 4]) = make_uint4(0, 0, 0, 0);
    }
  }
  STAMP(1);

  const int wg = __shfl_sync(0xffffffffu, tid >> 7, 0);
  const int wtid = tid & 127;
  uint4* tile = reinterpret_cast<uint4*>(&sm.tabB[0][0][0]);
  bf16* qn_s = reinterpret_cast<bf16*>(&sm.tabA[1][0][0]);
  if (wg < 2) {
    asm volatile("setmaxnreg.inc.sync.aligned.u32 224;");
    const int w = (tid >> 5) & 3, g = lane >> 2, tq = lane & 3;
    float* zw = sm.z[wg][w];
    const int sw = 3 * (((tq + w) >> 1) & 1);
    const int off_even = 16 * (tq + w) + 4 * ((0 + (g >> 2)) ^ sw) + (g & 3);
    const int off_odd = 16 * (tq + w) + 4 * ((2 + (g >> 2)) ^ sw) + (g & 3);
    uint32_t a[8][8];
    const uint32_t* tp0 = &sm.tabA[0][g & 1][1019 - 8 * w - (g >> 1) + tq];
    load_a_all(a, tp0 + tab_off(wg));
    if (wg == 0) bar_arrive(7, 384);
    else {
      mbar_wait(&sm.mbar);
      bar_sync(7, 384);
      ln_q_rows(sm, qn_s, w * 2, lane);
    }
    float acc[8][16];
#pragma unroll
    for (int b = 0; b < 8; b++)
#pragma unroll
      for (int i = 0; i < 16; i++) acc[b][i] = 0.f;
#pragma unroll 1
    for (int c = wg; c < CPC; c += 2) {
      const uint64_t desc = (uint64_t)((smem_u32(&sm.u[c][UPAD - 8]) & 0x3FFFF) >> 4) | ((uint64_t)1 << 16) | ((uint64_t)8 << 32);
      CST(c, 0);
      if (c > 0) bar_sync(1 + wg, 256);
      issue_g<0>(acc, a[0], desc);
      CST(c, 1);
      issue_g<1>(acc, a[1], desc);
      issue_g<2>(acc, a[2], desc);
      issue_g<3>(acc, a[3], desc);
      issue_g<4>(acc, a[4], desc);
      issue_g<5>(acc, a[5], desc);
      if (c + 1 < CPC) bar_arrive(1 + (wg ^ 1), 256);
      issue_g<6>(acc, a[6], desc);
      issue_g<7>(acc, a[7], desc);
      CST(c, 2);
      if (c >= 2) bar_sync(5 + wg, 256);
      wg_wait<4>();
      fence_blk<0>(acc); fence_blk<1>(acc); fence_blk<2>(acc); fence_blk<3>(acc);
      sts_blk<0>(acc, zw, off_even, off_odd);
      sts_blk<1>(acc, zw, off_even, off_odd);
      sts_blk<2>(acc, zw, off_even, off_odd);
      sts_blk<3>(acc, zw, off_even, off_odd);
      CST(c, 3);
      wg_wait<0>();
      fence_blk<4>(acc); fence_blk<5>(acc); fence_blk<6>(acc); fence_blk<7>(acc);
#pragma unroll
      for (int i = 0; i < 8; i++) fence_a(a[i]);
      sts_blk<4>(acc, zw, off_even, off_odd);
      sts_blk<5>(acc, zw, off_even, off_odd);
      sts_blk<6>(acc, zw, off_even, off_odd);
      sts_blk<7>(acc, zw, off_even, off_odd);
      bar_arrive(3 + wg, 256);
      CST(c, 4);
      if (c + 2 < CPC) load_a_all(a, tp0 + tab_off(c + 2));
    }
    STAMP(2 + wg);
    asm volatile("setmaxnreg.dec.sync.aligned.u32 168;");
    if (wg == 1) {
#pragma unroll 1
      for (int cc = 0; cc < 4; cc++) {
        const int ch = wtid * 5 + cc;
        const uint4* src = g_y2 + cta * 1280 + ch * 2;
        uint4 v0 = ld_poll4(src), v1 = ld_poll4(src + 1);
        int it = 0;
        while (!ready4(v0) && ++it < SPIN_LIMIT) v0 = ld_poll4(src);
        while (!ready4(v1) && ++it < SPIN_LIMIT) v1 = ld_poll4(src + 1);
        const int pc = tile_perm(ch);
        tile[pc] = make_uint4(~v0.x, ~v0.y, ~v0.z, ~v0.w);
        tile[640 + pc] = make_uint4(~v1.x, ~v1.y, ~v1.z, ~v1.w);
      }
    }
  } else {
    asm volatile("setmaxnreg.dec.sync.aligned.u32 56;");
    if (wtid == 32) {
      const uint32_t mw = smem_u32(&sm.mbarw);
      if (cta < N1) {
        asm volatile("mbarrier.arrive.expect_tx.shared.b64 _, [%0], %1;" ::"r"(mw), "r"(3840 * 16) : "memory");
#pragma unroll 1
        for (int i = 0; i < 4; i++) {
          asm volatile("cp.async.bulk.tensor.2d.shared::cluster.global.mbarrier::complete_tx::bytes [%0], [%1, {%3, %4}], [%2];" ::"r"(smem_u32(&sm.w[i * 480])),
                       "l"(&tmg), "r"(mw), "r"(cta * 24), "r"(i * 160) : "memory");
          asm volatile("cp.async.bulk.tensor.2d.shared::cluster.global.mbarrier::complete_tx::bytes [%0], [%1, {%3, %4}], [%2];" ::"r"(smem_u32(&sm.w[1920 + i * 480])),
                       "l"(&tmu), "r"(mw), "r"(cta * 24), "r"(i * 160) : "memory");
        }
      } else if (cta < N1 + N2) {
        asm volatile("mbarrier.arrive.expect_tx.shared.b64 _, [%0], %1;" ::"r"(mw), "r"(3072 * 16) : "memory");
#pragma unroll 1
        for (int i = 0; i < 6; i++)
          asm volatile("cp.async.bulk.tensor.2d.shared::cluster.global.mbarrier::complete_tx::bytes [%0], [%1, {%3, %4}], [%2];" ::"r"(smem_u32(&sm.w[i * 512])),
                       "l"(&tmd), "r"(mw), "r"((cta - N1) * 16), "r"(i * 256) : "memory");
      }
    }
    mbar_wait(&sm.mbar);
    bar_sync(7, 384);
    ln_q_rows(sm, qn_s, 8 + (wid - 8) * 2, lane);
    if (wtid == 0) wait_ctr(&g_ctr, sm.target);
    const int rpb = wtid >> 1, re2 = wtid & 1;
    const int rsw = 3 * ((rpb >> 1) & 1);
    const int roff0 = 16 * rpb + 4 * ((2 * re2 + 0) ^ rsw);
    const int roff1 = 16 * rpb + 4 * ((2 * re2 + 1) ^ rsw);
    const uint32_t dvl = reinterpret_cast<const unsigned short*>(gD)[c0 + (lane < CPC ? lane : 0)];
#pragma unroll 1
    for (int c = 0; c < CPC; c++) {
      const int zg = c & 1;
      const uint32_t dvc = __shfl_sync(0xffffffffu, dvl, c);
      const bf162 d2 = u2b(dvc | (dvc << 16));
      CST(c, 5);
      bar_sync(3 + zg, 256);
#pragma unroll
      for (int half = 0; half < 2; half++) {
        const float* zb = sm.z[zg][0] + half * 1024;
        float4 x[4][2];
#pragma unroll
        for (int ww = 0; ww < 4; ww++) {
          x[ww][0] = *reinterpret_cast<const float4*>(zb + ww * ZPB * 16 + roff0);
          x[ww][1] = *reinterpret_cast<const float4*>(zb + ww * ZPB * 16 + roff1);
        }
        const int sidx = half * 1024 + wtid * 8;
        const uint4 kvv = *reinterpret_cast<const uint4*>(&sm.u[c][UPAD + sidx]);
        if (half == 1 && c + 2 < CPC) bar_arrive(5 + zg, 256);
        uint4 o;
        o.x = pack2((x[0][0].x + x[1][0].x) + (x[2][0].x + x[3][0].x), (x[0][0].y + x[1][0].y) + (x[2][0].y + x[3][0].y));
        o.y = pack2((x[0][0].z + x[1][0].z) + (x[2][0].z + x[3][0].z), (x[0][0].w + x[1][0].w) + (x[2][0].w + x[3][0].w));
        o.z = pack2((x[0][1].x + x[1][1].x) + (x[2][1].x + x[3][1].x), (x[0][1].y + x[1][1].y) + (x[2][1].y + x[3][1].y));
        o.w = pack2((x[0][1].z + x[1][1].z) + (x[2][1].z + x[3][1].z), (x[0][1].w + x[1][1].w) + (x[2][1].w + x[3][1].w));
        o.x = b2u(__hadd2_rn(u2b(o.x), __hmul2_rn(u2b(kvv.x), d2)));
        o.y = b2u(__hadd2_rn(u2b(o.y), __hmul2_rn(u2b(kvv.y), d2)));
        o.z = b2u(__hadd2_rn(u2b(o.z), __hmul2_rn(u2b(kvv.z), d2)));
        o.w = b2u(__hadd2_rn(u2b(o.w), __hmul2_rn(u2b(kvv.w), d2)));
        st_pub4(g_y2 + ((64 * half + rpb) * 640 + c0 + c) * 2 + re2, enc4(o));
        CST(c, 6 + half);
      }
    }
    STAMP(4);
    asm volatile("setmaxnreg.inc.sync.aligned.u32 168;");
  }

  if (tid < 128 || tid >= 256) {
    const int t = tid < 128 ? tid : tid - 128;
    const int ch = (t >> 1) * 5 + 4, hh = t & 1;
    const uint4 v = poll4(g_y2 + cta * 1280 + ch * 2 + hh);
    tile[hh * 640 + tile_perm(ch)] = v;
  }
  __syncthreads();
  STAMP(5);

  const int g = lane >> 2, tq = lane & 3;
  const int hh = wid & 1, gqi = wid >> 1;
  const int row = hh * 8 + g;
  uint32_t hreg[16], hnreg[16];
  if (wid < 10) {
    float cs[4] = {0.f, 0.f, 0.f, 0.f};
#pragma unroll
    for (int k = 0; k < 4; k++) {
      const int base = 32 * (4 * gqi + k);
      const int lch = base + 8 * ((lane & 7) >> 1) + 2 * (lane >> 3) + (lane & 1);
      uint32_t y[4];
      asm volatile("ldmatrix.sync.aligned.m8n8.x4.trans.shared.b16 {%0,%1,%2,%3}, [%4];"
                   : "=r"(y[0]), "=r"(y[1]), "=r"(y[2]), "=r"(y[3]) : "r"(smem_u32(&tile[hh * 640 + tile_perm(lch)])) : "memory");
      const uint4 qv4 = *reinterpret_cast<const uint4*>(&sm.q[row][base + 8 * tq]);
      const uint4 qn4 = *reinterpret_cast<const uint4*>(qn_s + row * QSTR + base + 8 * tq);
      hreg[4 * k + 0] = b2u(__hadd2_rn(u2b(qv4.x), __hmul2_rn(u2b(qn4.x), u2b(y[0]))));
      hreg[4 * k + 1] = b2u(__hadd2_rn(u2b(qv4.y), __hmul2_rn(u2b(qn4.y), u2b(y[1]))));
      hreg[4 * k + 2] = b2u(__hadd2_rn(u2b(qv4.z), __hmul2_rn(u2b(qn4.z), u2b(y[2]))));
      hreg[4 * k + 3] = b2u(__hadd2_rn(u2b(qv4.w), __hmul2_rn(u2b(qn4.w), u2b(y[3]))));
      mma_bf16(cs, hreg[4 * k + 0], hreg[4 * k + 1], 0x3F803F80u, 0x3F803F80u);
      mma_bf16(cs, hreg[4 * k + 2], hreg[4 * k + 3], 0x3F803F80u, 0x3F803F80u);
    }
    const float mean = cs[0] * (1.f / 128.f);
    float m2a = 0.f, m2b = 0.f;
#pragma unroll
    for (int i = 0; i < 16; i++) {
      const float a = lo_f(hreg[i]) - mean, b = hi_f(hreg[i]) - mean;
      m2a = fmaf(a, a, m2a); m2b = fmaf(b, b, m2b);
    }
    float m2 = m2a + m2b;
    m2 += __shfl_xor_sync(0xffffffffu, m2, 1);
    m2 += __shfl_xor_sync(0xffffffffu, m2, 2);
    if (tq == 0) sm.st[row][gqi] = make_float2(mean, m2);
  }
  STAMP(13);
  __syncthreads();
  if (wid < 10) {
    float mean = 0.f, m2 = 0.f;
    float2 p[5];
#pragma unroll
    for (int i = 0; i < 5; i++) { p[i] = sm.st[row][i]; mean += p[i].x; }
    mean *= 0.2f;
#pragma unroll
    for (int i = 0; i < 5; i++) { const float dl = p[i].x - mean; m2 += p[i].y + 128.f * dl * dl; }
    const float hd = rbf(sqrtf(rbf(rbf(m2 * (1.f / D_)) + 1e-5f)));
    const float hr = 1.f / hd;
    const bf162 hm2 = __float2bfloat162_rn(mean);
    float cr[4] = {0.f, 0.f, 0.f, 0.f};
#pragma unroll
    for (int k = 0; k < 4; k++) {
      const uint4 w4 = sm.wr[4 * (4 * gqi + k) + tq];
#pragma unroll
      for (int i = 0; i < 4; i++) {
        const uint32_t d = b2u(__hsub2_rn(u2b(hreg[4 * k + i]), hm2));
        hnreg[4 * k + i] = pack2(fdivr(lo_f(d), hd, hr), fdivr(hi_f(d), hd, hr));
      }
      mma_bf16(cr, hnreg[4 * k + 0], hnreg[4 * k + 1], w4.x, w4.y);
      mma_bf16(cr, hnreg[4 * k + 2], hnreg[4 * k + 3], w4.z, w4.w);
    }
    if (tq == 0) sm.rp[row][gqi] = cr[0];
  }
  STAMP(14);
  __syncthreads();
  uint32_t best;
  {
    const int rr = lane & 15;
    const float r = ((sm.rp[rr][0] + sm.rp[rr][1]) + (sm.rp[rr][2] + sm.rp[rr][3])) + sm.rp[rr][4];
    const uint32_t bits = __bfloat16_as_ushort(__float2bfloat16_rn(r));
    const uint32_t ord = (bits & 0x8000u) ? (bits ^ 0xFFFFu) : (bits ^ 0x8000u);
    const uint32_t key = (ord << 16) | 0x8000u | (uint32_t)(2047 - (cta * 16 + rr));
    best = __reduce_max_sync(0xffffffffu, key);
  }
  if (tid == 352) asm volatile("st.relaxed.gpu.global.u32 [%0], %1;" ::"l"(&g_keys[cta]), "r"(best) : "memory");
  STAMP(15);
  const int brow = (2047 - (int)(best & 0x7FFu)) - cta * 16;
  uint4 outv[4];
  if (wid < 10) {
#pragma unroll
    for (int k = 0; k < 4; k++) {
      outv[k].x = b2u(__hadd2_rn(u2b(hreg[4 * k + 0]), u2b(hnreg[4 * k + 0])));
      outv[k].y = b2u(__hadd2_rn(u2b(hreg[4 * k + 1]), u2b(hnreg[4 * k + 1])));
      outv[k].z = b2u(__hadd2_rn(u2b(hreg[4 * k + 2]), u2b(hnreg[4 * k + 2])));
      outv[k].w = b2u(__hadd2_rn(u2b(hreg[4 * k + 3]), u2b(hnreg[4 * k + 3])));
      const int chunk = 4 * (4 * gqi + k) + tq;
      if (row == brow) {
        st_pub4(&g_cand[cta][0][chunk], enc4(make_uint4(hnreg[4 * k], hnreg[4 * k + 1], hnreg[4 * k + 2], hnreg[4 * k + 3])));
        st_pub4(&g_cand[cta][1][chunk], enc4(make_uint4(hreg[4 * k], hreg[4 * k + 1], hreg[4 * k + 2], hreg[4 * k + 3])));
      } else {
        *reinterpret_cast<uint4*>(gout + (size_t)(cta * 16 + row) * D_ + chunk * 8) = outv[k];
      }
    }
  }
  STAMP(6);
  if (wid == 11) {
    const uint4* kp = reinterpret_cast<const uint4*>(g_keys) + lane;
    uint4 v = ld_poll4(kp);
    int it = 0;
    while (!ready4(v) && ++it < SPIN_LIMIT) v = ld_poll4(kp);
    const uint32_t m = max(max(v.x, v.y), max(v.z, v.w));
    const uint32_t wk = __reduce_max_sync(0xffffffffu, m);
    if (lane == 0) sm.win = wk;
  }
  __syncthreads();
  const uint32_t win = sm.win;
  const int wrow = 2047 - (int)(win & 0x7FFu);
  const int wcta = wrow >> 4;
  if (wid < 10 && row == brow && wcta != cta) {
#pragma unroll
    for (int k = 0; k < 4; k++)
      *reinterpret_cast<uint4*>(gout + (size_t)(cta * 16 + row) * D_ + (4 * (4 * gqi + k) + tq) * 8) = outv[k];
  }
  STAMP(7);
  if (cta < N1 + N2) mbar_wait(&sm.mbarw);
  float* xs = &sm.z[0][0][0];
  float* part = xs + 2048;
  if (cta < N1) {
    if (tid < 80) {
      const uint4 v = poll4(&g_cand[wcta][0][tid]);
      float4* xp = reinterpret_cast<float4*>(xs + tid * 8);
      xp[0] = make_float4(lo_f(v.x), hi_f(v.x), lo_f(v.y), hi_f(v.y));
      xp[1] = make_float4(lo_f(v.z), hi_f(v.z), lo_f(v.w), hi_f(v.w));
    }
    __syncthreads();
    const int m = wid / 6, hc = (wid % 6) >> 1, rs = (wid & 1) * 32 + lane;
    float a[8];
#pragma unroll
    for (int j = 0; j < 8; j++) a[j] = 0.f;
#pragma unroll
    for (int it = 0; it < 10; it++) {
      const int r = rs + 64 * it;
      const uint4 wv = sm.w[m * 1920 + r * 3 + hc];
      const float x = xs[r];
      a[0] = fmaf(x, lo_f(wv.x), a[0]); a[1] = fmaf(x, hi_f(wv.x), a[1]);
      a[2] = fmaf(x, lo_f(wv.y), a[2]); a[3] = fmaf(x, hi_f(wv.y), a[3]);
      a[4] = fmaf(x, lo_f(wv.z), a[4]); a[5] = fmaf(x, hi_f(wv.z), a[5]);
      a[6] = fmaf(x, lo_f(wv.w), a[6]); a[7] = fmaf(x, hi_f(wv.w), a[7]);
    }
    {
      const bool up = lane & 16;
#pragma unroll
      for (int j = 0; j < 4; j++) {
        const float send = up ? a[j] : a[j + 4], keep = up ? a[j + 4] : a[j];
        a[j] = keep + __shfl_xor_sync(0xffffffffu, send, 16);
      }
      const bool up2 = lane & 8;
#pragma unroll
      for (int j = 0; j < 2; j++) {
        const float send = up2 ? a[j] : a[j + 2], keep = up2 ? a[j + 2] : a[j];
        a[j] = keep + __shfl_xor_sync(0xffffffffu, send, 8);
      }
      const bool up3 = lane & 4;
      const float send = up3 ? a[0] : a[1], keep = up3 ? a[1] : a[0];
      a[0] = keep + __shfl_xor_sync(0xffffffffu, send, 4);
      a[0] += __shfl_xor_sync(0xffffffffu, a[0], 2);
      a[0] += __shfl_xor_sync(0xffffffffu, a[0], 1);
      if ((lane & 3) == 0) part[wid * 8 + (lane >> 2)] = a[0];
    }
    __syncthreads();
    if (wid == 0) {
      uint32_t bits = 0;
      if (lane < 24) {
        const int hc2 = lane >> 3, j = lane & 7;
        const float gt = rbf(part[(2 * hc2) * 8 + j] + part[(2 * hc2 + 1) * 8 + j]);
        const float up = rbf(part[(6 + 2 * hc2) * 8 + j] + part[(6 + 2 * hc2 + 1) * 8 + j]);
        const float sg = rbf(gt / (1.f + __expf(-gt)));
        bits = __bfloat16_as_ushort(__float2bfloat16_rn(sg * up));
      }
      const uint32_t nb = __shfl_down_sync(0xffffffffu, bits, 1);
      const uint32_t pw = bits | (nb << 16);
      const uint32_t w1 = __shfl_down_sync(0xffffffffu, pw, 2), w2 = __shfl_down_sync(0xffffffffu, pw, 4), w3 = __shfl_down_sync(0xffffffffu, pw, 6);
      if (lane < 24 && (lane & 7) == 0) st_pub4(&g_act[cta * 3 + (lane >> 3)], enc4(make_uint4(pw, w1, w2, w3)));
    }
  } else if (cta < N1 + N2) {
    const int j2 = cta - N1;
    uint4 rowv = make_uint4(0, 0, 0, 0);
    if (tid < 192) {
      const uint4 v = poll4(&g_act[tid]);
      float4* xp = reinterpret_cast<float4*>(xs + tid * 8);
      xp[0] = make_float4(lo_f(v.x), hi_f(v.x), lo_f(v.y), hi_f(v.y));
      xp[1] = make_float4(lo_f(v.z), hi_f(v.z), lo_f(v.w), hi_f(v.w));
    } else if (tid < 196) {
      const int t = tid - 192;
      rowv = poll4(&g_cand[wcta][t >> 1][j2 * 2 + (t & 1)]);
      reinterpret_cast<uint4*>(part + 256)[t] = rowv;
    }
    __syncthreads();
    const int hc = lane & 1, rs = wid * 16 + (lane >> 1);
    float a[8];
#pragma unroll
    for (int j = 0; j < 8; j++) a[j] = 0.f;
#pragma unroll
    for (int it = 0; it < 8; it++) {
      const int r = rs + 192 * it;
      const uint4 wv = sm.w[r * 2 + hc];
      const float x = xs[r];
      a[0] = fmaf(x, lo_f(wv.x), a[0]); a[1] = fmaf(x, hi_f(wv.x), a[1]);
      a[2] = fmaf(x, lo_f(wv.y), a[2]); a[3] = fmaf(x, hi_f(wv.y), a[3]);
      a[4] = fmaf(x, lo_f(wv.z), a[4]); a[5] = fmaf(x, hi_f(wv.z), a[5]);
      a[6] = fmaf(x, lo_f(wv.w), a[6]); a[7] = fmaf(x, hi_f(wv.w), a[7]);
    }
    {
      const bool up = lane & 16;
#pragma unroll
      for (int j = 0; j < 4; j++) {
        const float send = up ? a[j] : a[j + 4], keep = up ? a[j + 4] : a[j];
        a[j] = keep + __shfl_xor_sync(0xffffffffu, send, 16);
      }
      const bool up2 = lane & 8;
#pragma unroll
      for (int j = 0; j < 2; j++) {
        const float send = up2 ? a[j] : a[j + 2], keep = up2 ? a[j + 2] : a[j];
        a[j] = keep + __shfl_xor_sync(0xffffffffu, send, 8);
      }
      const bool up3 = lane & 4;
      const float send = up3 ? a[0] : a[1], keep = up3 ? a[1] : a[0];
      a[0] = keep + __shfl_xor_sync(0xffffffffu, send, 4);
      a[0] += __shfl_xor_sync(0xffffffffu, a[0], 2);
      if ((lane & 2) == 0) part[wid * 16 + hc * 8 + (lane >> 2)] = a[0];
    }
    __syncthreads();
    if (tid < 16) {
      float y = 0.f;
#pragma unroll
      for (int i = 0; i < 12; i++) y += part[i * 16 + tid];
      const uint32_t ord = win >> 16;
      const uint32_t rb = (ord & 0x8000u) ? (ord ^ 0x8000u) : (ord ^ 0xFFFFu);
      const float r = __uint_as_float(rb << 16);
      const float sg = rbf(1.f / (1.f + __expf(-r)));
      const float yy = rbf(rbf(y) * sg);
      const unsigned short* rv = reinterpret_cast<const unsigned short*>(part + 256);
      const float hn = __uint_as_float((uint32_t)rv[tid] << 16), h = __uint_as_float((uint32_t)rv[16 + tid] << 16);
      gout[(size_t)wrow * D_ + j2 * 16 + tid] = __float2bfloat16_rn(h + rbf(hn + yy));
    }
  }
  STAMP(8);
}

}

typedef CUresult (*EncodeFn)(CUtensorMap*, CUtensorMapDataType, cuuint32_t, void*, const cuuint64_t*, const cuuint64_t*,
                             const cuuint32_t*, const cuuint32_t*, CUtensorMapInterleave, CUtensorMapSwizzle,
                             CUtensorMapL2promotion, CUtensorMapFloatOOBfill);

extern "C" void kernel_launch(void* const* d_in, const int* in_sizes, int n_in, void* d_out, int out_size) {
  (void)in_sizes; (void)n_in; (void)out_size;
  static EncodeFn encode = nullptr;
  static CUtensorMap tmg, tmu, tmd;
  static void* cached[3] = {nullptr, nullptr, nullptr};
  if (!encode) {
    cudaFuncSetAttribute(fused_kernel, cudaFuncAttributeMaxDynamicSharedMemorySize, (int)sizeof(Smem));
    void* fn = nullptr;
    cudaDriverEntryPointQueryResult qr;
    cudaGetDriverEntryPoint("cuTensorMapEncodeTiled", &fn, cudaEnableDefault, &qr);
    encode = (EncodeFn)fn;
  }
  if (cached[0] != d_in[8] || cached[1] != d_in[9] || cached[2] != d_in[10]) {
    const cuuint32_t es[2] = {1, 1};
    {
      const cuuint64_t dims[2] = {F_, D_}, strides[1] = {F_ * 2};
      const cuuint32_t box[2] = {24, 160};
      encode(&tmg, CU_TENSOR_MAP_DATA_TYPE_BFLOAT16, 2, d_in[8], dims, strides, box, es, CU_TENSOR_MAP_INTERLEAVE_NONE,
             CU_TENSOR_MAP_SWIZZLE_NONE, CU_TENSOR_MAP_L2_PROMOTION_NONE, CU_TENSOR_MAP_FLOAT_OOB_FILL_NONE);
      encode(&tmu, CU_TENSOR_MAP_DATA_TYPE_BFLOAT16, 2, d_in[9], dims, strides, box, es, CU_TENSOR_MAP_INTERLEAVE_NONE,
             CU_TENSOR_MAP_SWIZZLE_NONE, CU_TENSOR_MAP_L2_PROMOTION_NONE, CU_TENSOR_MAP_FLOAT_OOB_FILL_NONE);
    }
    {
      const cuuint64_t dims[2] = {D_, F_}, strides[1] = {D_ * 2};
      const cuuint32_t box[2] = {16, 256};
      encode(&tmd, CU_TENSOR_MAP_DATA_TYPE_BFLOAT16, 2, d_in[10], dims, strides, box, es, CU_TENSOR_MAP_INTERLEAVE_NONE,
             CU_TENSOR_MAP_SWIZZLE_NONE, CU_TENSOR_MAP_L2_PROMOTION_NONE, CU_TENSOR_MAP_FLOAT_OOB_FILL_NONE);
    }
    cached[0] = d_in[8]; cached[1] = d_in[9]; cached[2] = d_in[10];
  }
  fused_kernel<<<NCTA, NTHR, sizeof(Smem), cudaStreamPerThread>>>(
      tmg, tmu, tmd, (const bf16*)d_in[0], (const bf16*)d_in[1], (const bf16*)d_in[2], (const bf16*)d_in[3],
      (const bf16*)d_in[4], (const bf16*)d_in[5], (const bf16*)d_in[7], (bf16*)d_out);
}
```

```cpp
#include <cuda_runtime.h>
#include <cuda_bf16.h>
#include <cuda.h>
#include <stdint.h>

namespace {

typedef __nv_bfloat16 bf16;
typedef __nv_bfloat162 bf162;

constexpr int S_ = 2048, D_ = 640, F_ = 1536;
constexpr int NCTA = 128, CPC = 5, NTHR = 384;
constexpr int UPAD = 136, USTR = 2192;
constexpr int TABW = 1040;
constexpr int ZPB = 132;
constexpr int QSTR = 648;
constexpr int N1 = 64;
constexpr int N2 = 40;
constexpr int SPIN_LIMIT = 1 << 19;
#define POLL_NS 100
#define H_DELAY 2000
#define Q_DELAY 4500

struct __align__(128) Smem {
  uint32_t tabA[3][2][TABW];
  uint32_t extra[1024];
  uint32_t tabB[2][2][TABW];
  bf16 u[CPC][USTR];
  float z[2][4][ZPB * 16];
  bf16 q[16][QSTR];
  alignas(128) uint4 w[3840];
  uint4 wr[80];
  float4 qstat[16];
  float2 st[16][5];
  float rp[16][5];
  unsigned long long mbar;
  unsigned long long mbarw;
  unsigned long long mbarc;
  unsigned long long mbarh;
  uint32_t target;
  uint32_t best;
  uint32_t win;
};

__device__ uint4 g_kv[D_ * S_ / 8];
__device__ uint4 g_y2[D_ * S_ / 8];
__device__ uint32_t g_keys[NCTA];
__device__ uint4 g_cand[NCTA][2][80];
__device__ uint4 g_act[F_ / 8];
__device__ unsigned int g_ctr;
__device__ unsigned int g_ctr2;
#define STAMP(i)
#define CST(c, i)

__device__ __forceinline__ uint32_t smem_u32(const void* p) { return (uint32_t)__cvta_generic_to_shared(p); }
__device__ __forceinline__ void wg_fence() { asm volatile("wgmma.fence.sync.aligned;" ::: "memory"); }
__device__ __forceinline__ void wg_commit() { asm volatile("wgmma.commit_group.sync.aligned;" ::: "memory"); }
template <int N> __device__ __forceinline__ void wg_wait() { asm volatile("wgmma.wait_group.sync.aligned %0;" ::"n"(N) : "memory"); }
__device__ __forceinline__ void bar_sync(int id, int n) { asm volatile("bar.sync %0, %1;" ::"r"(id), "r"(n) : "memory"); }
__device__ __forceinline__ void bar_arrive(int id, int n) { asm volatile("bar.arrive %0, %1;" ::"r"(id), "r"(n) : "memory"); }
__device__ __forceinline__ bf162 u2b(uint32_t u) { return *reinterpret_cast<bf162*>(&u); }
__device__ __forceinline__ uint32_t b2u(bf162 b) { return *reinterpret_cast<uint32_t*>(&b); }
__device__ __forceinline__ float lo_f(uint32_t u) { return __uint_as_float(u << 16); }
__device__ __forceinline__ float hi_f(uint32_t u) { return __uint_as_float(u & 0xFFFF0000u); }
__device__ __forceinline__ float rbf(float x) { return __bfloat162float(__float2bfloat16_rn(x)); }
__device__ __forceinline__ uint32_t pack2(float a, float b) { return b2u(__floats2bfloat162_rn(a, b)); }
__device__ __forceinline__ uint32_t enc(uint32_t w) { return max(~w, 1u); }
__device__ __forceinline__ uint4 enc4(uint4 v) { return make_uint4(enc(v.x), enc(v.y), enc(v.z), enc(v.w)); }
__device__ __forceinline__ uint4 ld_poll4(const uint4* p) {
  uint4 v;
  asm volatile("ld.relaxed.gpu.global.v4.u32 {%0,%1,%2,%3}, [%4];" : "=r"(v.x), "=r"(v.y), "=r"(v.z), "=r"(v.w) : "l"(p) : "memory");
  return v;
}
__device__ __forceinline__ bool ready4(uint4 v) { return v.x != 0u && v.y != 0u && v.z != 0u && v.w != 0u; }
__device__ __forceinline__ uint4 poll4(const uint4* p) {
  uint4 v = ld_poll4(p);
  int it = 0;
  while (!ready4(v) && ++it < SPIN_LIMIT) v = ld_poll4(p);
  return make_uint4(~v.x, ~v.y, ~v.z, ~v.w);
}
__device__ __forceinline__ void st_pub4(uint4* p, uint4 v) {
  asm volatile("st.relaxed.gpu.global.v4.u32 [%0], {%1,%2,%3,%4};" ::"l"(p), "r"(v.x), "r"(v.y), "r"(v.z), "r"(v.w) : "memory");
}
__device__ __forceinline__ void st_pub2(uint2* p, uint32_t a, uint32_t b) {
  asm volatile("st.relaxed.gpu.global.v2.u32 [%0], {%1,%2};" ::"l"(p), "r"(a), "r"(b) : "memory");
}
__device__ __forceinline__ void mma_bf16(float (&c)[4], uint32_t a0, uint32_t a2, uint32_t b0, uint32_t b1) {
  asm volatile("mma.sync.aligned.m16n8k16.row.col.f32.bf16.bf16.f32 {%0,%1,%2,%3}, {%4,%5,%6,%5}, {%7,%8}, {%0,%1,%2,%3};"
               : "+f"(c[0]), "+f"(c[1]), "+f"(c[2]), "+f"(c[3]) : "r"(a0), "r"(0u), "r"(a2), "r"(b0), "r"(b1));
}
__device__ __forceinline__ void mbar_wait(const unsigned long long* bar) {
  const uint32_t mb = smem_u32(bar);
  uint32_t ok = 0;
  int it = 0;
  while (!ok && ++it < SPIN_LIMIT)
    asm volatile("{ .reg .pred p; mbarrier.try_wait.parity.shared.b64 p, [%1], 0; selp.u32 %0, 1, 0, p; }" : "=r"(ok) : "r"(mb) : "memory");
}
__device__ __forceinline__ void bulk_g2s(void* dst, const void* src, uint32_t bytes, const unsigned long long* bar) {
  asm volatile("cp.async.bulk.shared::cluster.global.mbarrier::complete_tx::bytes [%0], [%1], %2, [%3];" ::"r"(smem_u32(dst)),
               "l"(src), "r"(bytes), "r"(smem_u32(bar)) : "memory");
}
__device__ __forceinline__ void mbar_expect(const unsigned long long* bar, uint32_t bytes) {
  asm volatile("mbarrier.arrive.expect_tx.shared.b64 _, [%0], %1;" ::"r"(smem_u32(bar)), "r"(bytes) : "memory");
}
__device__ __forceinline__ float fdivr(float a, float d, float r) {
  float q = a * r;
  float e = fmaf(-q, d, a);
  return fmaf(e, r, q);
}

template <bool FIRST> __device__ __forceinline__ void wgmma32(float (&d)[16], const uint32_t* a, uint64_t desc) {
  if (FIRST) {
    asm volatile("wgmma.mma_async.sync.aligned.m64n32k16.f32.bf16.bf16 {%0,%1,%2,%3,%4,%5,%6,%7,%8,%9,%10,%11,%12,%13,%14,%15}, {%16,%17,%18,%19}, %20, 0, 1, 1, 0;"
                 : "+f"(d[0]), "+f"(d[1]), "+f"(d[2]), "+f"(d[3]), "+f"(d[4]), "+f"(d[5]), "+f"(d[6]), "+f"(d[7]),
                   "+f"(d[8]), "+f"(d[9]), "+f"(d[10]), "+f"(d[11]), "+f"(d[12]), "+f"(d[13]), "+f"(d[14]), "+f"(d[15])
                 : "r"(a[0]), "r"(a[1]), "r"(a[2]), "r"(a[3]), "l"(desc));
  } else {
    asm volatile("wgmma.mma_async.sync.aligned.m64n32k16.f32.bf16.bf16 {%0,%1,%2,%3,%4,%5,%6,%7,%8,%9,%10,%11,%12,%13,%14,%15}, {%16,%17,%18,%19}, %20, 1, 1, 1, 0;"
                 : "+f"(d[0]), "+f"(d[1]), "+f"(d[2]), "+f"(d[3]), "+f"(d[4]), "+f"(d[5]), "+f"(d[6]), "+f"(d[7]),
                   "+f"(d[8]), "+f"(d[9]), "+f"(d[10]), "+f"(d[11]), "+f"(d[12]), "+f"(d[13]), "+f"(d[14]), "+f"(d[15])
                 : "r"(a[0]), "r"(a[1]), "r"(a[2]), "r"(a[3]), "l"(desc));
  }
}

template <int G> __device__ __forceinline__ void load_a(uint32_t (&a)[8], const uint32_t* tp) {
#pragma unroll
  for (int q = 0; q < 2; q++) {
    const int e = 2 * G + q;
    a[4 * q + 0] = tp[-64 * e];
    a[4 * q + 1] = tp[-64 * e - 32];
    a[4 * q + 2] = tp[-64 * e + 4];
    a[4 * q + 3] = tp[-64 * e - 28];
  }
}
__device__ __forceinline__ void load_a_all(uint32_t (&a)[8][8], const uint32_t* tp) {
  load_a<0>(a[0], tp); load_a<1>(a[1], tp); load_a<2>(a[2], tp); load_a<3>(a[3], tp);
  load_a<4>(a[4], tp); load_a<5>(a[5], tp); load_a<6>(a[6], tp); load_a<7>(a[7], tp);
}
template <int G> __device__ __forceinline__ void issue_g(float (&acc)[8][16], uint32_t (&a)[8], uint64_t desc0) {
  wg_fence();
#pragma unroll
  for (int q = 0; q < 2; q++) {
#pragma unroll
    for (int b = G; b < 8; b++) {
      const int delta = 2 * b - (2 * G + q);
      if (G == 0 && q == 0) wgmma32<true>(acc[b], &a[4 * q], desc0 + (uint64_t)(int64_t)(16 * delta));
      else wgmma32<false>(acc[b], &a[4 * q], desc0 + (uint64_t)(int64_t)(16 * delta));
    }
  }
  wg_commit();
}
template <int B> __device__ __forceinline__ void fence_blk(float (&acc)[8][16]) {
#pragma unroll
  for (int i = 0; i < 16; i++) asm volatile("" : "+f"(acc[B][i])::"memory");
}
__device__ __forceinline__ void fence_a(uint32_t (&a)[8]) {
#pragma unroll
  for (int i = 0; i < 8; i++) asm volatile("" : "+r"(a[i])::"memory");
}
template <int B> __device__ __forceinline__ void sts_blk(float (&acc)[8][16], float* zw, int off_even, int off_odd) {
#pragma unroll
  for (int jj = 0; jj < 4; jj++) {
    const int j = 4 * B + jj;
    float p0 = acc[B][4 * jj + 0], p1 = acc[B][4 * jj + 1];
    if (jj > 0) { p0 += acc[B][4 * (jj - 1) + 2]; p1 += acc[B][4 * (jj - 1) + 3]; }
    else if (B > 0) { p0 += acc[B > 0 ? B - 1 : 0][14]; p1 += acc[B > 0 ? B - 1 : 0][15]; }
    zw[64 * j + off_even] = p0;
    zw[64 * j + off_odd] = p1;
  }
}
__device__ __forceinline__ int tab_off(int c) { return c == 4 ? 0 : (c + 1) * 2 * TABW + (c >= 2 ? 1024 : 0); }
__device__ __forceinline__ int tile_perm(int ch) { return ch ^ (((ch >> 3) & 3) << 1); }

__device__ __forceinline__ void wait_ctr(const unsigned int* ctr, uint32_t target) {
  uint32_t v;
  int it = 0;
  do {
    asm volatile("ld.acquire.gpu.global.u32 %0, [%1];" : "=r"(v) : "l"(ctr) : "memory");
  } while ((int)(v - target) < 0 && ++it < SPIN_LIMIT);
}

__device__ __forceinline__ void ln_q_stats(Smem& sm, int row, int lane) {
  const uint32_t* qp = reinterpret_cast<const uint32_t*>(&sm.q[row][0]);
  uint32_t qa[10], qb[10];
  float sa = 0.f, sb = 0.f;
#pragma unroll
  for (int i = 0; i < 10; i++) {
    qa[i] = qp[lane + 32 * i]; qb[i] = qp[QSTR / 2 + lane + 32 * i];
    sa += lo_f(qa[i]) + hi_f(qa[i]); sb += lo_f(qb[i]) + hi_f(qb[i]);
  }
#pragma unroll
  for (int o = 16; o > 0; o >>= 1) { sa += __shfl_xor_sync(0xffffffffu, sa, o); sb += __shfl_xor_sync(0xffffffffu, sb, o); }
  sa *= (1.f / D_); sb *= (1.f / D_);
  float ma = 0.f, mb = 0.f;
#pragma unroll
  for (int i = 0; i < 10; i++) {
    const float x = lo_f(qa[i]) - sa, y = hi_f(qa[i]) - sa, z = lo_f(qb[i]) - sb, t = hi_f(qb[i]) - sb;
    ma = fmaf(x, x, fmaf(y, y, ma)); mb = fmaf(z, z, fmaf(t, t, mb));
  }
#pragma unroll
  for (int o = 16; o > 0; o >>= 1) { ma += __shfl_xor_sync(0xffffffffu, ma, o); mb += __shfl_xor_sync(0xffffffffu, mb, o); }
  if (lane < 2) {
    const float m = lane ? sb : sa, v = lane ? mb : ma;
    const float d = rbf(sqrtf(rbf(rbf(v * (1.f / D_)) + 1e-5f)));
    sm.qstat[row + lane] = make_float4(rbf(m), d, 1.f / d, 0.f);
  }
}

__global__ void __launch_bounds__(NTHR, 1)
fused_kernel(const __grid_constant__ CUtensorMap tmg, const __grid_constant__ CUtensorMap tmu,
             const __grid_constant__ CUtensorMap tmd, const bf16* __restrict__ gq, const bf16* __restrict__ gk, const bf16* __restrict__ gv,
             const bf16* __restrict__ gsk, const bf16* __restrict__ gh, const bf16* __restrict__ gD,
             const bf16* __restrict__ gwr, bf16* __restrict__ gout) {
  extern __shared__ __align__(128) unsigned char smraw[];
  Smem& sm = *reinterpret_cast<Smem*>(smraw);
  const int tid = threadIdx.x;
  const int cta = blockIdx.x;
  const int c0 = cta * CPC;
  const int lane = tid & 31;
  const int wid = tid >> 5;
  STAMP(0);
  const long long tstart = clock64();

  {
    uint4* hs = reinterpret_cast<uint4*>(&sm.z[0][0][0]);
    const int oc = tid >> 2;
    const int r0 = cta * 16 + (tid & 3) * 4;
    uint4 kk[7], vv[4], sk[4];
    if (tid < 320) {
      const uint4* kp = reinterpret_cast<const uint4*>(gk) + (size_t)r0 * 80 + oc;
      const uint4* vp = reinterpret_cast<const uint4*>(gv) + (size_t)r0 * 80 + oc;
#pragma unroll
      for (int i = 0; i < 7; i++) kk[i] = (i >= 3 || r0 > 0) ? __ldg(kp + (i - 3) * 80) : make_uint4(0, 0, 0, 0);
#pragma unroll
      for (int i = 0; i < 4; i++) vv[i] = __ldg(vp + i * 80);
#pragma unroll
      for (int i = 0; i < 4; i++) sk[i] = __ldg(reinterpret_cast<const uint4*>(gsk) + oc * 4 + i);
    } else if (tid == 320) {
      asm volatile("mbarrier.init.shared.b64 [%0], 1;" ::"r"(smem_u32(&sm.mbarh)) : "memory");
      asm volatile("mbarrier.init.shared.b64 [%0], 1;" ::"r"(smem_u32(&sm.mbar)) : "memory");
      asm volatile("mbarrier.init.shared.b64 [%0], 1;" ::"r"(smem_u32(&sm.mbarw)) : "memory");
      asm volatile("mbarrier.init.shared.b64 [%0], 1;" ::"r"(smem_u32(&sm.mbarc)) : "memory");
      asm volatile("fence.proxy.async.shared::cta;" ::: "memory");
    }
    if (tid < 320) bar_sync(6, 384); else { bar_arrive(6, 384); bar_sync(5, 64); }
    STAMP(9);
    if (tid < 320) {
      uint32_t o[4][4];
#pragma unroll
      for (int p = 0; p < 4; p++) {
        const bf162 w0 = u2b(__byte_perm(sk[p].x, sk[p].z, 0x5410)), w1 = u2b(__byte_perm(sk[p].x, sk[p].z, 0x7632));
        const bf162 w2 = u2b(__byte_perm(sk[p].y, sk[p].w, 0x5410)), w3 = u2b(__byte_perm(sk[p].y, sk[p].w, 0x7632));
        uint32_t kv[4];
#pragma unroll
        for (int i = 0; i < 4; i++) {
          const uint32_t k0 = p == 0 ? kk[i].x : p == 1 ? kk[i].y : p == 2 ? kk[i].z : kk[i].w;
          const uint32_t k1 = p == 0 ? kk[i + 1].x : p == 1 ? kk[i + 1].y : p == 2 ? kk[i + 1].z : kk[i + 1].w;
          const uint32_t k2 = p == 0 ? kk[i + 2].x : p == 1 ? kk[i + 2].y : p == 2 ? kk[i + 2].z : kk[i + 2].w;
          const uint32_t k3 = p == 0 ? kk[i + 3].x : p == 1 ? kk[i + 3].y : p == 2 ? kk[i + 3].z : kk[i + 3].w;
          const uint32_t vx = p == 0 ? vv[i].x : p == 1 ? vv[i].y : p == 2 ? vv[i].z : vv[i].w;
          bf162 a = __hmul2_rn(u2b(k0), w3);
          a = __hadd2_rn(a, __hmul2_rn(u2b(k1), w2));
          a = __hadd2_rn(a, __hmul2_rn(u2b(k2), w1));
          a = __hadd2_rn(a, __hmul2_rn(u2b(k3), w0));
          kv[i] = b2u(__hmul2_rn(a, u2b(vx)));
        }
        o[p][0] = enc(__byte_perm(kv[0], kv[1], 0x5410)); o[p][1] = enc(__byte_perm(kv[2], kv[3], 0x5410));
        o[p][2] = enc(__byte_perm(kv[0], kv[1], 0x7632)); o[p][3] = enc(__byte_perm(kv[2], kv[3], 0x7632));
      }
      uint2* dst = reinterpret_cast<uint2*>(g_kv) + (size_t)(oc * 8) * 512 + (r0 >> 2);
#pragma unroll
      for (int p = 0; p < 4; p++) {
        st_pub2(dst + (2 * p) * 512, o[p][0], o[p][1]);
        st_pub2(dst + (2 * p + 1) * 512, o[p][2], o[p][3]);
      }
      STAMP(10);
      if (wid == 0) bar_sync(4, 320); else bar_arrive(4, 320);
      if (tid == 0) {
        const unsigned old = atomicAdd(&g_ctr2, 1u);
        const unsigned target = (old / NCTA + 1u) * NCTA;
        uint32_t v;
        int it = 0;
        do {
          asm volatile("ld.relaxed.gpu.global.u32 %0, [%1];" : "=r"(v) : "l"(&g_ctr2) : "memory");
        } while ((int)(v - target) < 0 && ++it < SPIN_LIMIT);
        asm volatile("mbarrier.arrive.shared.b64 _, [%0];" ::"r"(smem_u32(&sm.mbarc)) : "memory");
      }
      __syncwarp();
    } else {
      const int t0 = tid - 320;
      const uint4 zz = make_uint4(0, 0, 0, 0);
      if (tid == 320) {
        while (clock64() - tstart < H_DELAY) {}
        mbar_expect(&sm.mbarh, CPC * S_ * 2);
        bulk_g2s(hs, gh + (size_t)c0 * S_, CPC * S_ * 2, &sm.mbarh);
      }
      __syncwarp();
      for (int t = t0; t < CPC * 17; t += 64) *reinterpret_cast<uint4*>(&sm.u[t / 17][(t % 17) * 8]) = zz;
      if (t0 < 40) *reinterpret_cast<uint4*>(&sm.tabA[0][0][0] + tab_off(t0 >> 3) + ((t0 >> 2) & 1) * TABW + 1024 + 4 * (t0 & 3)) = zz;
      while (clock64() - tstart < Q_DELAY) {}
      if (tid == 320) {
        mbar_expect(&sm.mbar, 17 * D_ * 2);
#pragma unroll 1
        for (int r = 0; r < 16; r++) bulk_g2s(&sm.q[r][0], gq + (size_t)(cta * 16 + r) * D_, D_ * 2, &sm.mbar);
        bulk_g2s(&sm.wr[0], gwr, D_ * 2, &sm.mbar);
      }
      __syncwarp();
#pragma unroll 4
      for (int i = 0; i < 20; i++) g_y2[cta * 1280 + t0 + 64 * i] = zz;
      (&g_cand[cta][0][0])[t0] = zz;
      (&g_cand[cta][0][0])[64 + t0] = zz;
      if (t0 < 32) (&g_cand[cta][0][0])[128 + t0] = zz;
      else if (t0 < 35) { if (cta < N1) g_act[cta * 3 + (t0 - 32)] = zz; }
      else if (t0 == 35) g_keys[cta] = 0u;
      bar_sync(5, 64);
      if (tid == 352) {
        __threadfence();
        const unsigned old = atomicAdd(&g_ctr, 1u);
        sm.target = (old / NCTA + 1u) * NCTA;
      }
      __syncwarp();
    }
    mbar_wait(&sm.mbarh);
#pragma unroll
    for (int i = 0; i < 4; i++) {
      const int t = (NTHR - 1 - tid) + NTHR * i;
      if (t < CPC * 256) {
        uint32_t* tb = &sm.tabA[0][0][0] + tab_off(t >> 8) + (255 - (t & 255)) * 4;
        const uint4 h = hs[t];
        const uint32_t hp = (t & 255) ? reinterpret_cast<const uint32_t*>(hs)[4 * t - 1] : 0u;
        uint4 r1, rr;
        r1.x = __byte_perm(h.w, 0, 0x1032); r1.y = __byte_perm(h.z, 0, 0x1032);
        r1.z = __byte_perm(h.y, 0, 0x1032); r1.w = __byte_perm(h.x, 0, 0x1032);
        rr.x = __byte_perm(h.w, h.z, 0x7610); rr.y = __byte_perm(h.z, h.y, 0x7610);
        rr.z = __byte_perm(h.y, h.x, 0x7610); rr.w = __byte_perm(h.x, hp, 0x7610);
        *reinterpret_cast<uint4*>(tb) = rr;
        *reinterpret_cast<uint4*>(tb + TABW) = r1;
      }
    }
    if (wid >= 1 && wid <= 8) {
      mbar_wait(&sm.mbar);
      ln_q_stats(sm, (wid - 1) * 2, lane);
    }
    STAMP(12);
  }
  mbar_wait(&sm.mbarc);
  {
    uint4 v[4];
    uint4* src = g_kv + c0 * 256 + tid;
#pragma unroll
    for (int i = 0; i < 4; i++) if (i < 3 || tid < 128) v[i] = ld_poll4(src + NTHR * i);
#pragma unroll
    for (int i = 0; i < 4; i++) {
      if (i < 3 || tid < 128) {
        int it = 0;
        while (!ready4(v[i]) && ++it < SPIN_LIMIT) { __nanosleep(POLL_NS); v[i] = ld_poll4(src + NTHR * i); }
        const int t = tid + NTHR * i;
        *reinterpret_cast<uint4*>(&sm.u[t >> 8][UPAD + (t & 255) * 8]) = make_uint4(~v[i].x, ~v[i].y, ~v[i].z, ~v[i].w);
      }
    }
    STAMP(11);
    asm volatile("fence.proxy.async.shared::cta;" ::: "memory");
    __syncthreads();
#pragma unroll
    for (int i = 0; i < 4; i++) if (i < 3 || tid < 128) src[NTHR * i] = make_uint4(0, 0, 0, 0);
    if (tid >= 256) {
      const int t0 = tid - 256;
      if (((t0 & 15) >> 2) < ((t0 >> 4) & 3))
        *reinterpret_cast<uint4*>(&sm.z[t0 >> 6][(t0 >> 4) & 3][(t0 & 15) * 4]) = make_uint4(0, 0, 0, 0);
    }
  }
  STAMP(1);

  const int wg = __shfl_sync(0xffffffffu, tid >> 7, 0);
  const int wtid = tid & 127;
  uint4* tile = reinterpret_cast<uint4*>(&sm.tabB[0][0][0]);
  bf16* qn_s = reinterpret_cast<bf16*>(&sm.tabA[1][0][0]);
  if (wg < 2) {
    asm volatile("setmaxnreg.inc.sync.aligned.u32 224;");
    const int w = (tid >> 5) & 3, g = lane >> 2, tq = lane & 3;
    float* zw = sm.z[wg][w];
    const int sw = 3 * (((tq + w) >> 1) & 1);
    const int off_even = 16 * (tq + w) + 4 * ((0 + (g >> 2)) ^ sw) + (g & 3);
    const int off_odd = 16 * (tq + w) + 4 * ((2 + (g >> 2)) ^ sw) + (g & 3);
    uint32_t a[8][8];
    const uint32_t* tp0 = &sm.tabA[0][g & 1][1019 - 8 * w - (g >> 1) + tq];
    load_a_all(a, tp0 + tab_off(wg));
    float acc[8][16];
#pragma unroll
    for (int b = 0; b < 8; b++)
#pragma unroll
      for (int i = 0; i < 16; i++) acc[b][i] = 0.f;
#pragma unroll 1
    for (int c = wg; c < CPC; c += 2) {
      const uint64_t desc = (uint64_t)((smem_u32(&sm.u[c][UPAD - 8]) & 0x3FFFF) >> 4) | ((uint64_t)1 << 16) | ((uint64_t)8 << 32);
      CST(c, 0);
      if (c > 0) bar_sync(1 + wg, 256);
      issue_g<0>(acc, a[0], desc);
      CST(c, 1);
      issue_g<1>(acc, a[1], desc);
      issue_g<2>(acc, a[2], desc);
      issue_g<3>(acc, a[3], desc);
      issue_g<4>(acc, a[4], desc);
      issue_g<5>(acc, a[5], desc);
      if (c + 1 < CPC) bar_arrive(1 + (wg ^ 1), 256);
      issue_g<6>(acc, a[6], desc);
      issue_g<7>(acc, a[7], desc);
      CST(c, 2);
      if (c >= 2) bar_sync(5 + wg, 256);
      wg_wait<4>();
      fence_blk<0>(acc); fence_blk<1>(acc); fence_blk<2>(acc); fence_blk<3>(acc);
      sts_blk<0>(acc, zw, off_even, off_odd);
      sts_blk<1>(acc, zw, off_even, off_odd);
      sts_blk<2>(acc, zw, off_even, off_odd);
      sts_blk<3>(acc, zw, off_even, off_odd);
      CST(c, 3);
      wg_wait<0>();
      fence_blk<4>(acc); fence_blk<5>(acc); fence_blk<6>(acc); fence_blk<7>(acc);
#pragma unroll
      for (int i = 0; i < 8; i++) fence_a(a[i]);
      sts_blk<4>(acc, zw, off_even, off_odd);
      sts_blk<5>(acc, zw, off_even, off_odd);
      sts_blk<6>(acc, zw, off_even, off_odd);
      sts_blk<7>(acc, zw, off_even, off_odd);
      bar_arrive(3 + wg, 256);
      CST(c, 4);
      if (c + 2 < CPC) load_a_all(a, tp0 + tab_off(c + 2));
    }
    STAMP(2 + wg);
    asm volatile("setmaxnreg.dec.sync.aligned.u32 168;");
    if (wg == 1) {
#pragma unroll 2
      for (int i = wtid; i < 1280; i += 128) {
        const int r = i / 80, ck = i - r * 80;
        const float4 st = sm.qstat[r];
        const bf162 m2 = __float2bfloat162_rn(st.x);
        const uint4 qv = *reinterpret_cast<const uint4*>(&sm.q[r][ck * 8]);
        const uint32_t d0 = b2u(__hsub2_rn(u2b(qv.x), m2)), d1 = b2u(__hsub2_rn(u2b(qv.y), m2));
        const uint32_t d2 = b2u(__hsub2_rn(u2b(qv.z), m2)), d3 = b2u(__hsub2_rn(u2b(qv.w), m2));
        uint4 o;
        o.x = pack2(fdivr(lo_f(d0), st.y, st.z), fdivr(hi_f(d0), st.y, st.z));
        o.y = pack2(fdivr(lo_f(d1), st.y, st.z), fdivr(hi_f(d1), st.y, st.z));
        o.z = pack2(fdivr(lo_f(d2), st.y, st.z), fdivr(hi_f(d2), st.y, st.z));
        o.w = pack2(fdivr(lo_f(d3), st.y, st.z), fdivr(hi_f(d3), st.y, st.z));
        *reinterpret_cast<uint4*>(qn_s + r * QSTR + ck * 8) = o;
      }
#pragma unroll 1
      for (int cc = 0; cc < 4; cc++) {
        const int ch = wtid * 5 + cc;
        const uint4* src = g_y2 + cta * 1280 + ch * 2;
        uint4 v0 = ld_poll4(src), v1 = ld_poll4(src + 1);
        int it = 0;
        while (!ready4(v0) && ++it < SPIN_LIMIT) v0 = ld_poll4(src);
        while (!ready4(v1) && ++it < SPIN_LIMIT) v1 = ld_poll4(src + 1);
        const int pc = tile_perm(ch);
        tile[pc] = make_uint4(~v0.x, ~v0.y, ~v0.z, ~v0.w);
        tile[640 + pc] = make_uint4(~v1.x, ~v1.y, ~v1.z, ~v1.w);
      }
    }
  } else {
    asm volatile("setmaxnreg.dec.sync.aligned.u32 56;");
    if (wtid == 32) {
      const uint32_t mw = smem_u32(&sm.mbarw);
      if (cta < N1) {
        asm volatile("mbarrier.arrive.expect_tx.shared.b64 _, [%0], %1;" ::"r"(mw), "r"(3840 * 16) : "memory");
#pragma unroll 1
        for (int i = 0; i < 4; i++) {
          asm volatile("cp.async.bulk.tensor.2d.shared::cluster.global.mbarrier::complete_tx::bytes [%0], [%1, {%3, %4}], [%2];" ::"r"(smem_u32(&sm.w[i * 480])),
                       "l"(&tmg), "r"(mw), "r"(cta * 24), "r"(i * 160) : "memory");
          asm volatile("cp.async.bulk.tensor.2d.shared::cluster.global.mbarrier::complete_tx::bytes [%0], [%1, {%3, %4}], [%2];" ::"r"(smem_u32(&sm.w[1920 + i * 480])),
                       "l"(&tmu), "r"(mw), "r"(cta * 24), "r"(i * 160) : "memory");
        }
      } else if (cta < N1 + N2) {
        asm volatile("mbarrier.arrive.expect_tx.shared.b64 _, [%0], %1;" ::"r"(mw), "r"(3072 * 16) : "memory");
#pragma unroll 1
        for (int i = 0; i < 6; i++)
          asm volatile("cp.async.bulk.tensor.2d.shared::cluster.global.mbarrier::complete_tx::bytes [%0], [%1, {%3, %4}], [%2];" ::"r"(smem_u32(&sm.w[i * 512])),
                       "l"(&tmd), "r"(mw), "r"((cta - N1) * 16), "r"(i * 256) : "memory");
      }
    }
    if (wtid == 0) wait_ctr(&g_ctr, sm.target);
    const int rpb = wtid >> 1, re2 = wtid & 1;
    const int rsw = 3 * ((rpb >> 1) & 1);
    const int roff0 = 16 * rpb + 4 * ((2 * re2 + 0) ^ rsw);
    const int roff1 = 16 * rpb + 4 * ((2 * re2 + 1) ^ rsw);
    const uint32_t dvl = reinterpret_cast<const unsigned short*>(gD)[c0 + (lane < CPC ? lane : 0)];
#pragma unroll 1
    for (int c = 0; c < CPC; c++) {
      const int zg = c & 1;
      const uint32_t dvc = __shfl_sync(0xffffffffu, dvl, c);
      const bf162 d2 = u2b(dvc | (dvc << 16));
      CST(c, 5);
      bar_sync(3 + zg, 256);
#pragma unroll
      for (int half = 0; half < 2; half++) {
        const float* zb = sm.z[zg][0] + half * 1024;
        float4 x[4][2];
#pragma unroll
        for (int ww = 0; ww < 4; ww++) {
          x[ww][0] = *reinterpret_cast<const float4*>(zb + ww * ZPB * 16 + roff0);
          x[ww][1] = *reinterpret_cast<const float4*>(zb + ww * ZPB * 16 + roff1);
        }
        const int sidx = half * 1024 + wtid * 8;
        const uint4 kvv = *reinterpret_cast<const uint4*>(&sm.u[c][UPAD + sidx]);
        if (half == 1 && c + 2 < CPC) bar_arrive(5 + zg, 256);
        uint4 o;
        o.x = pack2((x[0][0].x + x[1][0].x) + (x[2][0].x + x[3][0].x), (x[0][0].y + x[1][0].y) + (x[2][0].y + x[3][0].y));
        o.y = pack2((x[0][0].z + x[1][0].z) + (x[2][0].z + x[3][0].z), (x[0][0].w + x[1][0].w) + (x[2][0].w + x[3][0].w));
        o.z = pack2((x[0][1].x + x[1][1].x) + (x[2][1].x + x[3][1].x), (x[0][1].y + x[1][1].y) + (x[2][1].y + x[3][1].y));
        o.w = pack2((x[0][1].z + x[1][1].z) + (x[2][1].z + x[3][1].z), (x[0][1].w + x[1][1].w) + (x[2][1].w + x[3][1].w));
        o.x = b2u(__hadd2_rn(u2b(o.x), __hmul2_rn(u2b(kvv.x), d2)));
        o.y = b2u(__hadd2_rn(u2b(o.y), __hmul2_rn(u2b(kvv.y), d2)));
        o.z = b2u(__hadd2_rn(u2b(o.z), __hmul2_rn(u2b(kvv.z), d2)));
        o.w = b2u(__hadd2_rn(u2b(o.w), __hmul2_rn(u2b(kvv.w), d2)));
        st_pub4(g_y2 + ((64 * half + rpb) * 640 + c0 + c) * 2 + re2, enc4(o));
        CST(c, 6 + half);
      }
    }
    STAMP(4);
    asm volatile("setmaxnreg.inc.sync.aligned.u32 168;");
  }

  if (tid < 128 || tid >= 256) {
    const int t = tid < 128 ? tid : tid - 128;
    const int ch = (t >> 1) * 5 + 4, hh = t & 1;
    const uint4 v = poll4(g_y2 + cta * 1280 + ch * 2 + hh);
    tile[hh * 640 + tile_perm(ch)] = v;
  }
  __syncthreads();
  STAMP(5);

  const int g = lane >> 2, tq = lane & 3;
  const int hh = wid & 1, gqi = wid >> 1;
  const int row = hh * 8 + g;
  uint32_t hreg[16], hnreg[16];
  if (wid < 10) {
    float cs[4] = {0.f, 0.f, 0.f, 0.f};
#pragma unroll
    for (int k = 0; k < 4; k++) {
      const int base = 32 * (4 * gqi + k);
      const int lch = base + 8 * ((lane & 7) >> 1) + 2 * (lane >> 3) + (lane & 1);
      uint32_t y[4];
      asm volatile("ldmatrix.sync.aligned.m8n8.x4.trans.shared.b16 {%0,%1,%2,%3}, [%4];"
                   : "=r"(y[0]), "=r"(y[1]), "=r"(y[2]), "=r"(y[3]) : "r"(smem_u32(&tile[hh * 640 + tile_perm(lch)])) : "memory");
      const uint4 qv4 = *reinterpret_cast<const uint4*>(&sm.q[row][base + 8 * tq]);
      const uint4 qn4 = *reinterpret_cast<const uint4*>(qn_s + row * QSTR + base + 8 * tq);
      hreg[4 * k + 0] = b2u(__hadd2_rn(u2b(qv4.x), __hmul2_rn(u2b(qn4.x), u2b(y[0]))));
      hreg[4 * k + 1] = b2u(__hadd2_rn(u2b(qv4.y), __hmul2_rn(u2b(qn4.y), u2b(y[1]))));
      hreg[4 * k + 2] = b2u(__hadd2_rn(u2b(qv4.z), __hmul2_rn(u2b(qn4.z), u2b(y[2]))));
      hreg[4 * k + 3] = b2u(__hadd2_rn(u2b(qv4.w), __hmul2_rn(u2b(qn4.w), u2b(y[3]))));
      mma_bf16(cs, hreg[4 * k + 0], hreg[4 * k + 1], 0x3F803F80u, 0x3F803F80u);
      mma_bf16(cs, hreg[4 * k + 2], hreg[4 * k + 3], 0x3F803F80u, 0x3F803F80u);
    }
    const float mean = cs[0] * (1.f / 128.f);
    float m2a = 0.f, m2b = 0.f;
#pragma unroll
    for (int i = 0; i < 16; i++) {
      const float a = lo_f(hreg[i]) - mean, b = hi_f(hreg[i]) - mean;
      m2a = fmaf(a, a, m2a); m2b = fmaf(b, b, m2b);
    }
    float m2 = m2a + m2b;
    m2 += __shfl_xor_sync(0xffffffffu, m2, 1);
    m2 += __shfl_xor_sync(0xffffffffu, m2, 2);
    if (tq == 0) sm.st[row][gqi] = make_float2(mean, m2);
  }
  STAMP(13);
  __syncthreads();
  if (wid < 10) {
    float mean = 0.f, m2 = 0.f;
    float2 p[5];
#pragma unroll
    for (int i = 0; i < 5; i++) { p[i] = sm.st[row][i]; mean += p[i].x; }
    mean *= 0.2f;
#pragma unroll
    for (int i = 0; i < 5; i++) { const float dl = p[i].x - mean; m2 += p[i].y + 128.f * dl * dl; }
    const float hd = rbf(sqrtf(rbf(rbf(m2 * (1.f / D_)) + 1e-5f)));
    const float hr = 1.f / hd;
    const bf162 hm2 = __float2bfloat162_rn(mean);
    float cr[4] = {0.f, 0.f, 0.f, 0.f};
#pragma unroll
    for (int k = 0; k < 4; k++) {
      const uint4 w4 = sm.wr[4 * (4 * gqi + k) + tq];
#pragma unroll
      for (int i = 0; i < 4; i++) {
        const uint32_t d = b2u(__hsub2_rn(u2b(hreg[4 * k + i]), hm2));
        hnreg[4 * k + i] = pack2(fdivr(lo_f(d), hd, hr), fdivr(hi_f(d), hd, hr));
      }
      mma_bf16(cr, hnreg[4 * k + 0], hnreg[4 * k + 1], w4.x, w4.y);
      mma_bf16(cr, hnreg[4 * k + 2], hnreg[4 * k + 3], w4.z, w4.w);
    }
    if (tq == 0) sm.rp[row][gqi] = cr[0];
  }
  STAMP(14);
  __syncthreads();
  uint32_t best;
  {
    const int rr = lane & 15;
    const float r = ((sm.rp[rr][0] + sm.rp[rr][1]) + (sm.rp[rr][2] + sm.rp[rr][3])) + sm.rp[rr][4];
    const uint32_t bits = __bfloat16_as_ushort(__float2bfloat16_rn(r));
    const uint32_t ord = (bits & 0x8000u) ? (bits ^ 0xFFFFu) : (bits ^ 0x8000u);
    const uint32_t key = (ord << 16) | 0x8000u | (uint32_t)(2047 - (cta * 16 + rr));
    best = __reduce_max_sync(0xffffffffu, key);
  }
  if (tid == 352) asm volatile("st.relaxed.gpu.global.u32 [%0], %1;" ::"l"(&g_keys[cta]), "r"(best) : "memory");
  STAMP(15);
  const int brow = (2047 - (int)(best & 0x7FFu)) - cta * 16;
  uint4 outv[4];
  if (wid < 10) {
#pragma unroll
    for (int k = 0; k < 4; k++) {
      outv[k].x = b2u(__hadd2_rn(u2b(hreg[4 * k + 0]), u2b(hnreg[4 * k + 0])));
      outv[k].y = b2u(__hadd2_rn(u2b(hreg[4 * k + 1]), u2b(hnreg[4 * k + 1])));
      outv[k].z = b2u(__hadd2_rn(u2b(hreg[4 * k + 2]), u2b(hnreg[4 * k + 2])));
      outv[k].w = b2u(__hadd2_rn(u2b(hreg[4 * k + 3]), u2b(hnreg[4 * k + 3])));
      const int chunk = 4 * (4 * gqi + k) + tq;
      if (row == brow) {
        st_pub4(&g_cand[cta][0][chunk], enc4(make_uint4(hnreg[4 * k], hnreg[4 * k + 1], hnreg[4 * k + 2], hnreg[4 * k + 3])));
        st_pub4(&g_cand[cta][1][chunk], enc4(make_uint4(hreg[4 * k], hreg[4 * k + 1], hreg[4 * k + 2], hreg[4 * k + 3])));
      } else {
        *reinterpret_cast<uint4*>(gout + (size_t)(cta * 16 + row) * D_ + chunk * 8) = outv[k];
      }
    }
  }
  STAMP(6);
  if (wid == 11) {
    const uint4* kp = reinterpret_cast<const uint4*>(g_keys) + lane;
    uint4 v = ld_poll4(kp);
    int it = 0;
    while (!ready4(v) && ++it < SPIN_LIMIT) v = ld_poll4(kp);
    const uint32_t m = max(max(v.x, v.y), max(v.z, v.w));
    const uint32_t wk = __reduce_max_sync(0xffffffffu, m);
    if (lane == 0) sm.win = wk;
  }
  __syncthreads();
  const uint32_t win = sm.win;
  const int wrow = 2047 - (int)(win & 0x7FFu);
  const int wcta = wrow >> 4;
  if (wid < 10 && row == brow && wcta != cta) {
#pragma unroll
    for (int k = 0; k < 4; k++)
      *reinterpret_cast<uint4*>(gout + (size_t)(cta * 16 + row) * D_ + (4 * (4 * gqi + k) + tq) * 8) = outv[k];
  }
  STAMP(7);
  if (cta < N1 + N2) mbar_wait(&sm.mbarw);
  float* xs = &sm.z[0][0][0];
  float* part = xs + 2048;
  if (cta < N1) {
    if (tid < 80) {
      const uint4 v = poll4(&g_cand[wcta][0][tid]);
      float4* xp = reinterpret_cast<float4*>(xs + tid * 8);
      xp[0] = make_float4(lo_f(v.x), hi_f(v.x), lo_f(v.y), hi_f(v.y));
      xp[1] = make_float4(lo_f(v.z), hi_f(v.z), lo_f(v.w), hi_f(v.w));
    }
    __syncthreads();
    const int m = wid / 6, hc = (wid % 6) >> 1, rs = (wid & 1) * 32 + lane;
    float a[8];
#pragma unroll
    for (int j = 0; j < 8; j++) a[j] = 0.f;
#pragma unroll
    for (int it = 0; it < 10; it++) {
      const int r = rs + 64 * it;
      const uint4 wv = sm.w[m * 1920 + r * 3 + hc];
      const float x = xs[r];
      a[0] = fmaf(x, lo_f(wv.x), a[0]); a[1] = fmaf(x, hi_f(wv.x), a[1]);
      a[2] = fmaf(x, lo_f(wv.y), a[2]); a[3] = fmaf(x, hi_f(wv.y), a[3]);
      a[4] = fmaf(x, lo_f(wv.z), a[4]); a[5] = fmaf(x, hi_f(wv.z), a[5]);
      a[6] = fmaf(x, lo_f(wv.w), a[6]); a[7] = fmaf(x, hi_f(wv.w), a[7]);
    }
    {
      const bool up = lane & 16;
#pragma unroll
      for (int j = 0; j < 4; j++) {
        const float send = up ? a[j] : a[j + 4], keep = up ? a[j + 4] : a[j];
        a[j] = keep + __shfl_xor_sync(0xffffffffu, send, 16);
      }
      const bool up2 = lane & 8;
#pragma unroll
      for (int j = 0; j < 2; j++) {
        const float send = up2 ? a[j] : a[j + 2], keep = up2 ? a[j + 2] : a[j];
        a[j] = keep + __shfl_xor_sync(0xffffffffu, send, 8);
      }
      const bool up3 = lane & 4;
      const float send = up3 ? a[0] : a[1], keep = up3 ? a[1] : a[0];
      a[0] = keep + __shfl_xor_sync(0xffffffffu, send, 4);
      a[0] += __shfl_xor_sync(0xffffffffu, a[0], 2);
      a[0] += __shfl_xor_sync(0xffffffffu, a[0], 1);
      if ((lane & 3) == 0) part[wid * 8 + (lane >> 2)] = a[0];
    }
    __syncthreads();
    if (wid == 0) {
      uint32_t bits = 0;
      if (lane < 24) {
        const int hc2 = lane >> 3, j = lane & 7;
        const float gt = rbf(part[(2 * hc2) * 8 + j] + part[(2 * hc2 + 1) * 8 + j]);
        const float up = rbf(part[(6 + 2 * hc2) * 8 + j] + part[(6 + 2 * hc2 + 1) * 8 + j]);
        const float sg = rbf(gt / (1.f + __expf(-gt)));
        bits = __bfloat16_as_ushort(__float2bfloat16_rn(sg * up));
      }
      const uint32_t nb = __shfl_down_sync(0xffffffffu, bits, 1);
      const uint32_t pw = bits | (nb << 16);
      const uint32_t w1 = __shfl_down_sync(0xffffffffu, pw, 2), w2 = __shfl_down_sync(0xffffffffu, pw, 4), w3 = __shfl_down_sync(0xffffffffu, pw, 6);
      if (lane < 24 && (lane & 7) == 0) st_pub4(&g_act[cta * 3 + (lane >> 3)], enc4(make_uint4(pw, w1, w2, w3)));
    }
  } else if (cta < N1 + N2) {
    const int j2 = cta - N1;
    uint4 rowv = make_uint4(0, 0, 0, 0);
    if (tid < 192) {
      const uint4 v = poll4(&g_act[tid]);
      float4* xp = reinterpret_cast<float4*>(xs + tid * 8);
      xp[0] = make_float4(lo_f(v.x), hi_f(v.x), lo_f(v.y), hi_f(v.y));
      xp[1] = make_float4(lo_f(v.z), hi_f(v.z), lo_f(v.w), hi_f(v.w));
    } else if (tid < 196) {
      const int t = tid - 192;
      rowv = poll4(&g_cand[wcta][t >> 1][j2 * 2 + (t & 1)]);
      reinterpret_cast<uint4*>(part + 256)[t] = rowv;
    }
    __syncthreads();
    const int hc = lane & 1, rs = wid * 16 + (lane >> 1);
    float a[8];
#pragma unroll
    for (int j = 0; j < 8; j++) a[j] = 0.f;
#pragma unroll
    for (int it = 0; it < 8; it++) {
      const int r = rs + 192 * it;
      const uint4 wv = sm.w[r * 2 + hc];
      const float x = xs[r];
      a[0] = fmaf(x, lo_f(wv.x), a[0]); a[1] = fmaf(x, hi_f(wv.x), a[1]);
      a[2] = fmaf(x, lo_f(wv.y), a[2]); a[3] = fmaf(x, hi_f(wv.y), a[3]);
      a[4] = fmaf(x, lo_f(wv.z), a[4]); a[5] = fmaf(x, hi_f(wv.z), a[5]);
      a[6] = fmaf(x, lo_f(wv.w), a[6]); a[7] = fmaf(x, hi_f(wv.w), a[7]);
    }
    {
      const bool up = lane & 16;
#pragma unroll
      for (int j = 0; j < 4; j++) {
        const float send = up ? a[j] : a[j + 4], keep = up ? a[j + 4] : a[j];
        a[j] = keep + __shfl_xor_sync(0xffffffffu, send, 16);
      }
      const bool up2 = lane & 8;
#pragma unroll
      for (int j = 0; j < 2; j++) {
        const float send = up2 ? a[j] : a[j + 2], keep = up2 ? a[j + 2] : a[j];
        a[j] = keep + __shfl_xor_sync(0xffffffffu, send, 8);
      }
      const bool up3 = lane & 4;
      const float send = up3 ? a[0] : a[1], keep = up3 ? a[1] : a[0];
      a[0] = keep + __shfl_xor_sync(0xffffffffu, send, 4);
      a[0] += __shfl_xor_sync(0xffffffffu, a[0], 2);
      if ((lane & 2) == 0) part[wid * 16 + hc * 8 + (lane >> 2)] = a[0];
    }
    __syncthreads();
    if (tid < 16) {
      float y = 0.f;
#pragma unroll
      for (int i = 0; i < 12; i++) y += part[i * 16 + tid];
      const uint32_t ord = win >> 16;
      const uint32_t rb = (ord & 0x8000u) ? (ord ^ 0x8000u) : (ord ^ 0xFFFFu);
      const float r = __uint_as_float(rb << 16);
      const float sg = rbf(1.f / (1.f + __expf(-r)));
      const float yy = rbf(rbf(y) * sg);
      const unsigned short* rv = reinterpret_cast<const unsigned short*>(part + 256);
      const float hn = __uint_as_float((uint32_t)rv[tid] << 16), h = __uint_as_float((uint32_t)rv[16 + tid] << 16);
      gout[(size_t)wrow * D_ + j2 * 16 + tid] = __float2bfloat16_rn(h + rbf(hn + yy));
    }
  }
  STAMP(8);
}

}

typedef CUresult (*EncodeFn)(CUtensorMap*, CUtensorMapDataType, cuuint32_t, void*, const cuuint64_t*, const cuuint64_t*,
                             const cuuint32_t*, const cuuint32_t*, CUtensorMapInterleave, CUtensorMapSwizzle,
                             CUtensorMapL2promotion, CUtensorMapFloatOOBfill);

extern "C" void kernel_launch(void* const* d_in, const int* in_sizes, int n_in, void* d_out, int out_size) {
  (void)in_sizes; (void)n_in; (void)out_size;
  static EncodeFn encode = nullptr;
  static CUtensorMap tmg, tmu, tmd;
  static void* cached[3] = {nullptr, nullptr, nullptr};
  if (!encode) {
    cudaFuncSetAttribute(fused_kernel, cudaFuncAttributeMaxDynamicSharedMemorySize, (int)sizeof(Smem));
    void* fn = nullptr;
    cudaDriverEntryPointQueryResult qr;
    cudaGetDriverEntryPoint("cuTensorMapEncodeTiled", &fn, cudaEnableDefault, &qr);
    encode = (EncodeFn)fn;
  }
  if (cached[0] != d_in[8] || cached[1] != d_in[9] || cached[2] != d_in[10]) {
    const cuuint32_t es[2] = {1, 1};
    {
      const cuuint64_t dims[2] = {F_, D_}, strides[1] = {F_ * 2};
      const cuuint32_t box[2] = {24, 160};
      encode(&tmg, CU_TENSOR_MAP_DATA_TYPE_BFLOAT16, 2, d_in[8], dims, strides, box, es, CU_TENSOR_MAP_INTERLEAVE_NONE,
             CU_TENSOR_MAP_SWIZZLE_NONE, CU_TENSOR_MAP_L2_PROMOTION_NONE, CU_TENSOR_MAP_FLOAT_OOB_FILL_NONE);
      encode(&tmu, CU_TENSOR_MAP_DATA_TYPE_BFLOAT16, 2, d_in[9], dims, strides, box, es, CU_TENSOR_MAP_INTERLEAVE_NONE,
             CU_TENSOR_MAP_SWIZZLE_NONE, CU_TENSOR_MAP_L2_PROMOTION_NONE, CU_TENSOR_MAP_FLOAT_OOB_FILL_NONE);
    }
    {
      const cuuint64_t dims[2] = {D_, F_}, strides[1] = {D_ * 2};
      const cuuint32_t box[2] = {16, 256};
      encode(&tmd, CU_TENSOR_MAP_DATA_TYPE_BFLOAT16, 2, d_in[10], dims, strides, box, es, CU_TENSOR_MAP_INTERLEAVE_NONE,
             CU_TENSOR_MAP_SWIZZLE_NONE, CU_TENSOR_MAP_L2_PROMOTION_NONE, CU_TENSOR_MAP_FLOAT_OOB_FILL_NONE);
    }
    cached[0] = d_in[8]; cached[1] = d_in[9]; cached[2] = d_in[10];
  }
  fused_kernel<<<NCTA, NTHR, sizeof(Smem), cudaStreamPerThread>>>(
      tmg, tmu, tmd, (const bf16*)d_in[0], (const bf16*)d_in[1], (const bf16*)d_in[2], (const bf16*)d_in[3],
      (const bf16*)d_in[4], (const bf16*)d_in[5], (const bf16*)d_in[7], (bf16*)d_out);
}
```

```cpp
#include <cuda_runtime.h>
#include <cuda_bf16.h>
#include <cuda.h>
#include <stdint.h>

namespace {

typedef __nv_bfloat16 bf16;
typedef __nv_bfloat162 bf162;

constexpr int S_ = 2048, D_ = 640, F_ = 1536;
constexpr int NCTA = 128, CPC = 5, NTHR = 384;
constexpr int UPAD = 136, USTR = 2192;
constexpr int TABW = 1040;
constexpr int ZPB = 132;
constexpr int QSTR = 648;
constexpr int N1 = 64;
constexpr int N2 = 40;
constexpr int SPIN_LIMIT = 1 << 19;
#define POLL_NS 100
#define H_DELAY 0
#define Q_DELAY 4500

struct __align__(128) Smem {
  uint32_t tabA[3][2][TABW];
  uint32_t extra[1024];
  uint32_t tabB[2][2][TABW];
  bf16 u[CPC][USTR];
  float z[2][4][ZPB * 16];
  bf16 q[16][QSTR];
  alignas(128) uint4 w[3840];
  uint4 wr[80];
  float2 st[16][5];
  float rp[16][5];
  unsigned long long mbar;
  unsigned long long mbarw;
  unsigned long long mbarc;
  unsigned long long mbarh;
  uint32_t target;
  uint32_t best;
  uint32_t win;
};

__device__ uint4 g_kv[D_ * S_ / 8];
__device__ uint4 g_y2[D_ * S_ / 8];
__device__ uint32_t g_keys[NCTA];
__device__ uint4 g_cand[NCTA][2][80];
__device__ uint4 g_act[F_ / 8];
__device__ unsigned int g_ctr;
__device__ unsigned int g_ctr2;
#define STAMP(i)
#define CST(c, i)

__device__ __forceinline__ uint32_t smem_u32(const void* p) { return (uint32_t)__cvta_generic_to_shared(p); }
__device__ __forceinline__ void wg_fence() { asm volatile("wgmma.fence.sync.aligned;" ::: "memory"); }
__device__ __forceinline__ void wg_commit() { asm volatile("wgmma.commit_group.sync.aligned;" ::: "memory"); }
template <int N> __device__ __forceinline__ void wg_wait() { asm volatile("wgmma.wait_group.sync.aligned %0;" ::"n"(N) : "memory"); }
__device__ __forceinline__ void bar_sync(int id, int n) { asm volatile("bar.sync %0, %1;" ::"r"(id), "r"(n) : "memory"); }
__device__ __forceinline__ void bar_arrive(int id, int n) { asm volatile("bar.arrive %0, %1;" ::"r"(id), "r"(n) : "memory"); }
__device__ __forceinline__ bf162 u2b(uint32_t u) { return *reinterpret_cast<bf162*>(&u); }
__device__ __forceinline__ uint32_t b2u(bf162 b) { return *reinterpret_cast<uint32_t*>(&b); }
__device__ __forceinline__ float lo_f(uint32_t u) { return __uint_as_float(u << 16); }
__device__ __forceinline__ float hi_f(uint32_t u) { return __uint_as_float(u & 0xFFFF0000u); }
__device__ __forceinline__ float rbf(float x) { return __bfloat162float(__float2bfloat16_rn(x)); }
__device__ __forceinline__ uint32_t pack2(float a, float b) { return b2u(__floats2bfloat162_rn(a, b)); }
__device__ __forceinline__ uint32_t enc(uint32_t w) { return max(~w, 1u); }
__device__ __forceinline__ uint4 enc4(uint4 v) { return make_uint4(enc(v.x), enc(v.y), enc(v.z), enc(v.w)); }
__device__ __forceinline__ uint4 ld_poll4(const uint4* p) {
  uint4 v;
  asm volatile("ld.relaxed.gpu.global.v4.u32 {%0,%1,%2,%3}, [%4];" : "=r"(v.x), "=r"(v.y), "=r"(v.z), "=r"(v.w) : "l"(p) : "memory");
  return v;
}
__device__ __forceinline__ bool ready4(uint4 v) { return v.x != 0u && v.y != 0u && v.z != 0u && v.w != 0u; }
__device__ __forceinline__ uint4 poll4(const uint4* p) {
  uint4 v = ld_poll4(p);
  int it = 0;
  while (!ready4(v) && ++it < SPIN_LIMIT) v = ld_poll4(p);
  return make_uint4(~v.x, ~v.y, ~v.z, ~v.w);
}
__device__ __forceinline__ void st_pub4(uint4* p, uint4 v) {
  asm volatile("st.relaxed.gpu.global.v4.u32 [%0], {%1,%2,%3,%4};" ::"l"(p), "r"(v.x), "r"(v.y), "r"(v.z), "r"(v.w) : "memory");
}
__device__ __forceinline__ void st_pub2(uint2* p, uint32_t a, uint32_t b) {
  asm volatile("st.relaxed.gpu.global.v2.u32 [%0], {%1,%2};" ::"l"(p), "r"(a), "r"(b) : "memory");
}
__device__ __forceinline__ void mma_bf16(float (&c)[4], uint32_t a0, uint32_t a2, uint32_t b0, uint32_t b1) {
  asm volatile("mma.sync.aligned.m16n8k16.row.col.f32.bf16.bf16.f32 {%0,%1,%2,%3}, {%4,%5,%6,%5}, {%7,%8}, {%0,%1,%2,%3};"
               : "+f"(c[0]), "+f"(c[1]), "+f"(c[2]), "+f"(c[3]) : "r"(a0), "r"(0u), "r"(a2), "r"(b0), "r"(b1));
}
__device__ __forceinline__ void mbar_wait(const unsigned long long* bar) {
  const uint32_t mb = smem_u32(bar);
  uint32_t ok = 0;
  int it = 0;
  while (!ok && ++it < SPIN_LIMIT)
    asm volatile("{ .reg .pred p; mbarrier.try_wait.parity.shared.b64 p, [%1], 0; selp.u32 %0, 1, 0, p; }" : "=r"(ok) : "r"(mb) : "memory");
}
__device__ __forceinline__ void bulk_g2s(void* dst, const void* src, uint32_t bytes, const unsigned long long* bar) {
  asm volatile("cp.async.bulk.shared::cluster.global.mbarrier::complete_tx::bytes [%0], [%1], %2, [%3];" ::"r"(smem_u32(dst)),
               "l"(src), "r"(bytes), "r"(smem_u32(bar)) : "memory");
}
__device__ __forceinline__ void mbar_expect(const unsigned long long* bar, uint32_t bytes) {
  asm volatile("mbarrier.arrive.expect_tx.shared.b64 _, [%0], %1;" ::"r"(smem_u32(bar)), "r"(bytes) : "memory");
}
__device__ __forceinline__ float fdivr(float a, float d, float r) {
  float q = a * r;
  float e = fmaf(-q, d, a);
  return fmaf(e, r, q);
}

template <bool FIRST> __device__ __forceinline__ void wgmma32(float (&d)[16], const uint32_t* a, uint64_t desc) {
  if (FIRST) {
    asm volatile("wgmma.mma_async.sync.aligned.m64n32k16.f32.bf16.bf16 {%0,%1,%2,%3,%4,%5,%6,%7,%8,%9,%10,%11,%12,%13,%14,%15}, {%16,%17,%18,%19}, %20, 0, 1, 1, 0;"
                 : "+f"(d[0]), "+f"(d[1]), "+f"(d[2]), "+f"(d[3]), "+f"(d[4]), "+f"(d[5]), "+f"(d[6]), "+f"(d[7]),
                   "+f"(d[8]), "+f"(d[9]), "+f"(d[10]), "+f"(d[11]), "+f"(d[12]), "+f"(d[13]), "+f"(d[14]), "+f"(d[15])
                 : "r"(a[0]), "r"(a[1]), "r"(a[2]), "r"(a[3]), "l"(desc));
  } else {
    asm volatile("wgmma.mma_async.sync.aligned.m64n32k16.f32.bf16.bf16 {%0,%1,%2,%3,%4,%5,%6,%7,%8,%9,%10,%11,%12,%13,%14,%15}, {%16,%17,%18,%19}, %20, 1, 1, 1, 0;"
                 : "+f"(d[0]), "+f"(d[1]), "+f"(d[2]), "+f"(d[3]), "+f"(d[4]), "+f"(d[5]), "+f"(d[6]), "+f"(d[7]),
                   "+f"(d[8]), "+f"(d[9]), "+f"(d[10]), "+f"(d[11]), "+f"(d[12]), "+f"(d[13]), "+f"(d[14]), "+f"(d[15])
                 : "r"(a[0]), "r"(a[1]), "r"(a[2]), "r"(a[3]), "l"(desc));
  }
}

template <int G> __device__ __forceinline__ void load_a(uint32_t (&a)[8], const uint32_t* tp) {
#pragma unroll
  for (int q = 0; q < 2; q++) {
    const int e = 2 * G + q;
    a[4 * q + 0] = tp[-64 * e];
    a[4 * q + 1] = tp[-64 * e - 32];
    a[4 * q + 2] = tp[-64 * e + 4];
    a[4 * q + 3] = tp[-64 * e - 28];
  }
}
__device__ __forceinline__ void load_a_all(uint32_t (&a)[8][8], const uint32_t* tp) {
  load_a<0>(a[0], tp); load_a<1>(a[1], tp); load_a<2>(a[2], tp); load_a<3>(a[3], tp);
  load_a<4>(a[4], tp); load_a<5>(a[5], tp); load_a<6>(a[6], tp); load_a<7>(a[7], tp);
}
template <int G> __device__ __forceinline__ void issue_g(float (&acc)[8][16], uint32_t (&a)[8], uint64_t desc0) {
  wg_fence();
#pragma unroll
  for (int q = 0; q < 2; q++) {
#pragma unroll
    for (int b = G; b < 8; b++) {
      const int delta = 2 * b - (2 * G + q);
      if (G == 0 && q == 0) wgmma32<true>(acc[b], &a[4 * q], desc0 + (uint64_t)(int64_t)(16 * delta));
      else wgmma32<false>(acc[b], &a[4 * q], desc0 + (uint64_t)(int64_t)(16 * delta));
    }
  }
  wg_commit();
}
template <int B> __device__ __forceinline__ void fence_blk(float (&acc)[8][16]) {
#pragma unroll
  for (int i = 0; i < 16; i++) asm volatile("" : "+f"(acc[B][i])::"memory");
}
__device__ __forceinline__ void fence_a(uint32_t (&a)[8]) {
#pragma unroll
  for (int i = 0; i < 8; i++) asm volatile("" : "+r"(a[i])::"memory");
}
template <int B> __device__ __forceinline__ void sts_blk(float (&acc)[8][16], float* zw, int off_even, int off_odd) {
#pragma unroll
  for (int jj = 0; jj < 4; jj++) {
    const int j = 4 * B + jj;
    float p0 = acc[B][4 * jj + 0], p1 = acc[B][4 * jj + 1];
    if (jj > 0) { p0 += acc[B][4 * (jj - 1) + 2]; p1 += acc[B][4 * (jj - 1) + 3]; }
    else if (B > 0) { p0 += acc[B > 0 ? B - 1 : 0][14]; p1 += acc[B > 0 ? B - 1 : 0][15]; }
    zw[64 * j + off_even] = p0;
    zw[64 * j + off_odd] = p1;
  }
}
__device__ __forceinline__ int tab_off(int c) { return c == 4 ? 0 : (c + 1) * 2 * TABW + (c >= 2 ? 1024 : 0); }
__device__ __forceinline__ int tile_perm(int ch) { return ch ^ (((ch >> 3) & 3) << 1); }

__device__ __forceinline__ void wait_ctr(const unsigned int* ctr, uint32_t target) {
  uint32_t v;
  int it = 0;
  do {
    asm volatile("ld.acquire.gpu.global.u32 %0, [%1];" : "=r"(v) : "l"(ctr) : "memory");
  } while ((int)(v - target) < 0 && ++it < SPIN_LIMIT);
}

__device__ __forceinline__ void ln_q_row(Smem& sm, bf16* qn_s, int row, int lane) {
  const uint32_t* qp = reinterpret_cast<const uint32_t*>(&sm.q[row][0]);
  uint32_t qa[10];
  float s0 = 0.f, s1 = 0.f;
#pragma unroll
  for (int i = 0; i < 10; i++) { qa[i] = qp[lane + 32 * i]; s0 += lo_f(qa[i]); s1 += hi_f(qa[i]); }
  float sa = s0 + s1;
#pragma unroll
  for (int o = 16; o > 0; o >>= 1) sa += __shfl_xor_sync(0xffffffffu, sa, o);
  sa *= (1.f / D_);
  float m0 = 0.f, m1 = 0.f;
#pragma unroll
  for (int i = 0; i < 10; i++) {
    const float x = lo_f(qa[i]) - sa, y = hi_f(qa[i]) - sa;
    m0 = fmaf(x, x, m0); m1 = fmaf(y, y, m1);
  }
  float ma = m0 + m1;
#pragma unroll
  for (int o = 16; o > 0; o >>= 1) ma += __shfl_xor_sync(0xffffffffu, ma, o);
  const float d = rbf(sqrtf(rbf(rbf(ma * (1.f / D_)) + 1e-5f)));
  const float r = 1.f / d;
  const bf162 m2 = __float2bfloat162_rn(sa);
  uint32_t* np = reinterpret_cast<uint32_t*>(qn_s + row * QSTR);
#pragma unroll
  for (int i = 0; i < 10; i++) {
    const uint32_t e = b2u(__hsub2_rn(u2b(qa[i]), m2));
    np[lane + 32 * i] = pack2(fdivr(lo_f(e), d, r), fdivr(hi_f(e), d, r));
  }
}

__global__ void __launch_bounds__(NTHR, 1)
fused_kernel(const __grid_constant__ CUtensorMap tmg, const __grid_constant__ CUtensorMap tmu,
             const __grid_constant__ CUtensorMap tmd, const bf16* __restrict__ gq, const bf16* __restrict__ gk, const bf16* __restrict__ gv,
             const bf16* __restrict__ gsk, const bf16* __restrict__ gh, const bf16* __restrict__ gD,
             const bf16* __restrict__ gwr, bf16* __restrict__ gout) {
  extern __shared__ __align__(128) unsigned char smraw[];
  Smem& sm = *reinterpret_cast<Smem*>(smraw);
  const int tid = threadIdx.x;
  const int cta = blockIdx.x;
  const int c0 = cta * CPC;
  const int lane = tid & 31;
  const int wid = tid >> 5;
  STAMP(0);
  const long long tstart = clock64();

  {
    uint4* hs = reinterpret_cast<uint4*>(&sm.z[0][0][0]);
    const int oc = tid >> 2;
    const int r0 = cta * 16 + (tid & 3) * 4;
    uint4 kk[7], vv[4], sk[4];
    if (tid < 320) {
      const uint4* kp = reinterpret_cast<const uint4*>(gk) + (size_t)r0 * 80 + oc;
      const uint4* vp = reinterpret_cast<const uint4*>(gv) + (size_t)r0 * 80 + oc;
#pragma unroll
      for (int i = 0; i < 7; i++) kk[i] = (i >= 3 || r0 > 0) ? __ldg(kp + (i - 3) * 80) : make_uint4(0, 0, 0, 0);
#pragma unroll
      for (int i = 0; i < 4; i++) vv[i] = __ldg(vp + i * 80);
#pragma unroll
      for (int i = 0; i < 4; i++) sk[i] = __ldg(reinterpret_cast<const uint4*>(gsk) + oc * 4 + i);
    } else if (tid == 320) {
      asm volatile("mbarrier.init.shared.b64 [%0], 1;" ::"r"(smem_u32(&sm.mbarh)) : "memory");
      asm volatile("mbarrier.init.shared.b64 [%0], 1;" ::"r"(smem_u32(&sm.mbar)) : "memory");
      asm volatile("mbarrier.init.shared.b64 [%0], 1;" ::"r"(smem_u32(&sm.mbarw)) : "memory");
      asm volatile("mbarrier.init.shared.b64 [%0], 1;" ::"r"(smem_u32(&sm.mbarc)) : "memory");
      asm volatile("fence.proxy.async.shared::cta;" ::: "memory");
    }
    if (tid < 320) bar_sync(6, 384); else { bar_arrive(6, 384); bar_sync(5, 64); }
    STAMP(9);
    if (tid < 320) {
      uint32_t o[4][4];
#pragma unroll
      for (int p = 0; p < 4; p++) {
        const bf162 w0 = u2b(__byte_perm(sk[p].x, sk[p].z, 0x5410)), w1 = u2b(__byte_perm(sk[p].x, sk[p].z, 0x7632));
        const bf162 w2 = u2b(__byte_perm(sk[p].y, sk[p].w, 0x5410)), w3 = u2b(__byte_perm(sk[p].y, sk[p].w, 0x7632));
        uint32_t kv[4];
#pragma unroll
        for (int i = 0; i < 4; i++) {
          const uint32_t k0 = p == 0 ? kk[i].x : p == 1 ? kk[i].y : p == 2 ? kk[i].z : kk[i].w;
          const uint32_t k1 = p == 0 ? kk[i + 1].x : p == 1 ? kk[i + 1].y : p == 2 ? kk[i + 1].z : kk[i + 1].w;
          const uint32_t k2 = p == 0 ? kk[i + 2].x : p == 1 ? kk[i + 2].y : p == 2 ? kk[i + 2].z : kk[i + 2].w;
          const uint32_t k3 = p == 0 ? kk[i + 3].x : p == 1 ? kk[i + 3].y : p == 2 ? kk[i + 3].z : kk[i + 3].w;
          const uint32_t vx = p == 0 ? vv[i].x : p == 1 ? vv[i].y : p == 2 ? vv[i].z : vv[i].w;
          bf162 a = __hmul2_rn(u2b(k0), w3);
          a = __hadd2_rn(a, __hmul2_rn(u2b(k1), w2));
          a = __hadd2_rn(a, __hmul2_rn(u2b(k2), w1));
          a = __hadd2_rn(a, __hmul2_rn(u2b(k3), w0));
          kv[i] = b2u(__hmul2_rn(a, u2b(vx)));
        }
        o[p][0] = enc(__byte_perm(kv[0], kv[1], 0x5410)); o[p][1] = enc(__byte_perm(kv[2], kv[3], 0x5410));
        o[p][2] = enc(__byte_perm(kv[0], kv[1], 0x7632)); o[p][3] = enc(__byte_perm(kv[2], kv[3], 0x7632));
      }
      uint2* dst = reinterpret_cast<uint2*>(g_kv) + (size_t)(oc * 8) * 512 + (r0 >> 2);
#pragma unroll
      for (int p = 0; p < 4; p++) {
        st_pub2(dst + (2 * p) * 512, o[p][0], o[p][1]);
        st_pub2(dst + (2 * p + 1) * 512, o[p][2], o[p][3]);
      }
      STAMP(10);
      if (wid == 0) bar_sync(4, 320); else bar_arrive(4, 320);
      if (tid == 0) {
        const unsigned old = atomicAdd(&g_ctr2, 1u);
        const unsigned target = (old / NCTA + 1u) * NCTA;
        uint32_t v;
        int it = 0;
        do {
          asm volatile("ld.relaxed.gpu.global.u32 %0, [%1];" : "=r"(v) : "l"(&g_ctr2) : "memory");
        } while ((int)(v - target) < 0 && ++it < SPIN_LIMIT);
        asm volatile("mbarrier.arrive.shared.b64 _, [%0];" ::"r"(smem_u32(&sm.mbarc)) : "memory");
      }
      __syncwarp();
    } else {
      const int t0 = tid - 320;
      const uint4 zz = make_uint4(0, 0, 0, 0);
      if (tid == 320) {
        while (clock64() - tstart < H_DELAY) {}
        mbar_expect(&sm.mbarh, CPC * S_ * 2);
        bulk_g2s(hs, gh + (size_t)c0 * S_, CPC * S_ * 2, &sm.mbarh);
      }
      __syncwarp();
      for (int t = t0; t < CPC * 17; t += 64) *reinterpret_cast<uint4*>(&sm.u[t / 17][(t % 17) * 8]) = zz;
      if (t0 < 40) *reinterpret_cast<uint4*>(&sm.tabA[0][0][0] + tab_off(t0 >> 3) + ((t0 >> 2) & 1) * TABW + 1024 + 4 * (t0 & 3)) = zz;
#pragma unroll 4
      for (int i = 0; i < 20; i++) g_y2[cta * 1280 + t0 + 64 * i] = zz;
      (&g_cand[cta][0][0])[t0] = zz;
      (&g_cand[cta][0][0])[64 + t0] = zz;
      if (t0 < 32) (&g_cand[cta][0][0])[128 + t0] = zz;
      else if (t0 < 35) { if (cta < N1) g_act[cta * 3 + (t0 - 32)] = zz; }
      else if (t0 == 35) g_keys[cta] = 0u;
      bar_sync(5, 64);
      if (tid == 352) {
        __threadfence();
        const unsigned old = atomicAdd(&g_ctr, 1u);
        sm.target = (old / NCTA + 1u) * NCTA;
      }
      __syncwarp();
    }
    mbar_wait(&sm.mbarh);
#pragma unroll
    for (int i = 0; i < 4; i++) {
      const int t = (NTHR - 1 - tid) + NTHR * i;
      if (t < CPC * 256) {
        uint32_t* tb = &sm.tabA[0][0][0] + tab_off(t >> 8) + (255 - (t & 255)) * 4;
        const uint4 h = hs[t];
        const uint32_t hp = (t & 255) ? reinterpret_cast<const uint32_t*>(hs)[4 * t - 1] : 0u;
        uint4 r1, rr;
        r1.x = __byte_perm(h.w, 0, 0x1032); r1.y = __byte_perm(h.z, 0, 0x1032);
        r1.z = __byte_perm(h.y, 0, 0x1032); r1.w = __byte_perm(h.x, 0, 0x1032);
        rr.x = __byte_perm(h.w, h.z, 0x7610); rr.y = __byte_perm(h.z, h.y, 0x7610);
        rr.z = __byte_perm(h.y, h.x, 0x7610); rr.w = __byte_perm(h.x, hp, 0x7610);
        *reinterpret_cast<uint4*>(tb) = rr;
        *reinterpret_cast<uint4*>(tb + TABW) = r1;
      }
    }
    STAMP(12);
  }
  mbar_wait(&sm.mbarc);
  {
    uint4 v[4];
    uint4* src = g_kv + c0 * 256 + tid;
#pragma unroll
    for (int i = 0; i < 4; i++) if (i < 3 || tid < 128) v[i] = ld_poll4(src + NTHR * i);
#pragma unroll
    for (int i = 0; i < 4; i++) {
      if (i < 3 || tid < 128) {
        int it = 0;
        while (!ready4(v[i]) && ++it < SPIN_LIMIT) { __nanosleep(POLL_NS); v[i] = ld_poll4(src + NTHR * i); }
        const int t = tid + NTHR * i;
        *reinterpret_cast<uint4*>(&sm.u[t >> 8][UPAD + (t & 255) * 8]) = make_uint4(~v[i].x, ~v[i].y, ~v[i].z, ~v[i].w);
      }
    }
    STAMP(11);
    asm volatile("fence.proxy.async.shared::cta;" ::: "memory");
    __syncthreads();
#pragma unroll
    for (int i = 0; i < 4; i++) if (i < 3 || tid < 128) src[NTHR * i] = make_uint4(0, 0, 0, 0);
    if (tid >= 256) {
      const int t0 = tid - 256;
      if (((t0 & 15) >> 2) < ((t0 >> 4) & 3))
        *reinterpret_cast<uint4*>(&sm.z[t0 >> 6][(t0 >> 4) & 3][(t0 & 15) * 4]) = make_uint4(0, 0, 0, 0);
    }
  }
  STAMP(1);

  const int wg = __shfl_sync(0xffffffffu, tid >> 7, 0);
  const int wtid = tid & 127;
  uint4* tile = reinterpret_cast<uint4*>(&sm.tabB[0][0][0]);
  bf16* qn_s = reinterpret_cast<bf16*>(&sm.tabA[1][0][0]);
  if (wg < 2) {
    asm volatile("setmaxnreg.inc.sync.aligned.u32 224;");
    const int w = (tid >> 5) & 3, g = lane >> 2, tq = lane & 3;
    float* zw = sm.z[wg][w];
    const int sw = 3 * (((tq + w) >> 1) & 1);
    const int off_even = 16 * (tq + w) + 4 * ((0 + (g >> 2)) ^ sw) + (g & 3);
    const int off_odd = 16 * (tq + w) + 4 * ((2 + (g >> 2)) ^ sw) + (g & 3);
    uint32_t a[8][8];
    const uint32_t* tp0 = &sm.tabA[0][g & 1][1019 - 8 * w - (g >> 1) + tq];
    load_a_all(a, tp0 + tab_off(wg));
    float acc[8][16];
#pragma unroll
    for (int b = 0; b < 8; b++)
#pragma unroll
      for (int i = 0; i < 16; i++) acc[b][i] = 0.f;
#pragma unroll 1
    for (int c = wg; c < CPC; c += 2) {
      const uint64_t desc = (uint64_t)((smem_u32(&sm.u[c][UPAD - 8]) & 0x3FFFF) >> 4) | ((uint64_t)1 << 16) | ((uint64_t)8 << 32);
      CST(c, 0);
      if (c > 0) bar_sync(1 + wg, 256);
      issue_g<0>(acc, a[0], desc);
      CST(c, 1);
      issue_g<1>(acc, a[1], desc);
      issue_g<2>(acc, a[2], desc);
      issue_g<3>(acc, a[3], desc);
      issue_g<4>(acc, a[4], desc);
      issue_g<5>(acc, a[5], desc);
      if (c + 1 < CPC) bar_arrive(1 + (wg ^ 1), 256);
      issue_g<6>(acc, a[6], desc);
      issue_g<7>(acc, a[7], desc);
      CST(c, 2);
      if (c >= 2) bar_sync(5 + wg, 256);
      wg_wait<4>();
      fence_blk<0>(acc); fence_blk<1>(acc); fence_blk<2>(acc); fence_blk<3>(acc);
      sts_blk<0>(acc, zw, off_even, off_odd);
      sts_blk<1>(acc, zw, off_even, off_odd);
      sts_blk<2>(acc, zw, off_even, off_odd);
      sts_blk<3>(acc, zw, off_even, off_odd);
      CST(c, 3);
      wg_wait<0>();
      fence_blk<4>(acc); fence_blk<5>(acc); fence_blk<6>(acc); fence_blk<7>(acc);
#pragma unroll
      for (int i = 0; i < 8; i++) fence_a(a[i]);
      sts_blk<4>(acc, zw, off_even, off_odd);
      sts_blk<5>(acc, zw, off_even, off_odd);
      sts_blk<6>(acc, zw, off_even, off_odd);
      sts_blk<7>(acc, zw, off_even, off_odd);
      bar_arrive(3 + wg, 256);
      CST(c, 4);
      if (c + 2 < CPC) load_a_all(a, tp0 + tab_off(c + 2));
    }
    STAMP(2 + wg);
    asm volatile("setmaxnreg.dec.sync.aligned.u32 168;");
    if (wg == 1) {
      mbar_wait(&sm.mbar);
      ln_q_row(sm, qn_s, 8 + 2 * w, lane);
      ln_q_row(sm, qn_s, 9 + 2 * w, lane);
#pragma unroll 1
      for (int cc = 0; cc < 4; cc++) {
        const int ch = wtid * 5 + cc;
        const uint4* src = g_y2 + cta * 1280 + ch * 2;
        uint4 v0 = ld_poll4(src), v1 = ld_poll4(src + 1);
        int it = 0;
        while (!ready4(v0) && ++it < SPIN_LIMIT) v0 = ld_poll4(src);
        while (!ready4(v1) && ++it < SPIN_LIMIT) v1 = ld_poll4(src + 1);
        const int pc = tile_perm(ch);
        tile[pc] = make_uint4(~v0.x, ~v0.y, ~v0.z, ~v0.w);
        tile[640 + pc] = make_uint4(~v1.x, ~v1.y, ~v1.z, ~v1.w);
      }
    }
  } else {
    asm volatile("setmaxnreg.dec.sync.aligned.u32 56;");
    if (wtid == 32) {
      const uint32_t mw = smem_u32(&sm.mbarw);
      mbar_expect(&sm.mbar, 17 * D_ * 2);
#pragma unroll 1
      for (int r = 0; r < 16; r++) bulk_g2s(&sm.q[r][0], gq + (size_t)(cta * 16 + r) * D_, D_ * 2, &sm.mbar);
      bulk_g2s(&sm.wr[0], gwr, D_ * 2, &sm.mbar);
      if (cta < N1) {
        asm volatile("mbarrier.arrive.expect_tx.shared.b64 _, [%0], %1;" ::"r"(mw), "r"(3840 * 16) : "memory");
#pragma unroll 1
        for (int i = 0; i < 4; i++) {
          asm volatile("cp.async.bulk.tensor.2d.shared::cluster.global.mbarrier::complete_tx::bytes [%0], [%1, {%3, %4}], [%2];" ::"r"(smem_u32(&sm.w[i * 480])),
                       "l"(&tmg), "r"(mw), "r"(cta * 24), "r"(i * 160) : "memory");
          asm volatile("cp.async.bulk.tensor.2d.shared::cluster.global.mbarrier::complete_tx::bytes [%0], [%1, {%3, %4}], [%2];" ::"r"(smem_u32(&sm.w[1920 + i * 480])),
                       "l"(&tmu), "r"(mw), "r"(cta * 24), "r"(i * 160) : "memory");
        }
      } else if (cta < N1 + N2) {
        asm volatile("mbarrier.arrive.expect_tx.shared.b64 _, [%0], %1;" ::"r"(mw), "r"(3072 * 16) : "memory");
#pragma unroll 1
        for (int i = 0; i < 6; i++)
          asm volatile("cp.async.bulk.tensor.2d.shared::cluster.global.mbarrier::complete_tx::bytes [%0], [%1, {%3, %4}], [%2];" ::"r"(smem_u32(&sm.w[i * 512])),
                       "l"(&tmd), "r"(mw), "r"((cta - N1) * 16), "r"(i * 256) : "memory");
      }
    }
    if (wtid == 0) wait_ctr(&g_ctr, sm.target);
    const int rpb = wtid >> 1, re2 = wtid & 1;
    const int rsw = 3 * ((rpb >> 1) & 1);
    const int roff0 = 16 * rpb + 4 * ((2 * re2 + 0) ^ rsw);
    const int roff1 = 16 * rpb + 4 * ((2 * re2 + 1) ^ rsw);
    const uint32_t dvl = reinterpret_cast<const unsigned short*>(gD)[c0 + (lane < CPC ? lane : 0)];
#pragma unroll 1
    for (int c = 0; c < CPC; c++) {
      const int zg = c & 1;
      const uint32_t dvc = __shfl_sync(0xffffffffu, dvl, c);
      const bf162 d2 = u2b(dvc | (dvc << 16));
      CST(c, 5);
      bar_sync(3 + zg, 256);
#pragma unroll
      for (int half = 0; half < 2; half++) {
        const float* zb = sm.z[zg][0] + half * 1024;
        float4 x[4][2];
#pragma unroll
        for (int ww = 0; ww < 4; ww++) {
          x[ww][0] = *reinterpret_cast<const float4*>(zb + ww * ZPB * 16 + roff0);
          x[ww][1] = *reinterpret_cast<const float4*>(zb + ww * ZPB * 16 + roff1);
        }
        const int sidx = half * 1024 + wtid * 8;
        const uint4 kvv = *reinterpret_cast<const uint4*>(&sm.u[c][UPAD + sidx]);
        if (half == 1 && c + 2 < CPC) bar_arrive(5 + zg, 256);
        uint4 o;
        o.x = pack2((x[0][0].x + x[1][0].x) + (x[2][0].x + x[3][0].x), (x[0][0].y + x[1][0].y) + (x[2][0].y + x[3][0].y));
        o.y = pack2((x[0][0].z + x[1][0].z) + (x[2][0].z + x[3][0].z), (x[0][0].w + x[1][0].w) + (x[2][0].w + x[3][0].w));
        o.z = pack2((x[0][1].x + x[1][1].x) + (x[2][1].x + x[3][1].x), (x[0][1].y + x[1][1].y) + (x[2][1].y + x[3][1].y));
        o.w = pack2((x[0][1].z + x[1][1].z) + (x[2][1].z + x[3][1].z), (x[0][1].w + x[1][1].w) + (x[2][1].w + x[3][1].w));
        o.x = b2u(__hadd2_rn(u2b(o.x), __hmul2_rn(u2b(kvv.x), d2)));
        o.y = b2u(__hadd2_rn(u2b(o.y), __hmul2_rn(u2b(kvv.y), d2)));
        o.z = b2u(__hadd2_rn(u2b(o.z), __hmul2_rn(u2b(kvv.z), d2)));
        o.w = b2u(__hadd2_rn(u2b(o.w), __hmul2_rn(u2b(kvv.w), d2)));
        st_pub4(g_y2 + ((64 * half + rpb) * 640 + c0 + c) * 2 + re2, enc4(o));
        CST(c, 6 + half);
      }
    }
    STAMP(4);
    asm volatile("setmaxnreg.inc.sync.aligned.u32 168;");
  }

  if (tid < 128 || tid >= 256) {
    const int t = tid < 128 ? tid : tid - 128;
    const int ch = (t >> 1) * 5 + 4, hh = t & 1;
    mbar_wait(&sm.mbar);
    ln_q_row(sm, qn_s, t >> 5, lane);
    const uint4 v = poll4(g_y2 + cta * 1280 + ch * 2 + hh);
    tile[hh * 640 + tile_perm(ch)] = v;
  }
  __syncthreads();
  STAMP(5);

  const int g = lane >> 2, tq = lane & 3;
  const int hh = wid & 1, gqi = wid >> 1;
  const int row = hh * 8 + g;
  uint32_t hreg[16], hnreg[16];
  if (wid < 10) {
    float cs[4] = {0.f, 0.f, 0.f, 0.f};
#pragma unroll
    for (int k = 0; k < 4; k++) {
      const int base = 32 * (4 * gqi + k);
      const int lch = base + 8 * ((lane & 7) >> 1) + 2 * (lane >> 3) + (lane & 1);
      uint32_t y[4];
      asm volatile("ldmatrix.sync.aligned.m8n8.x4.trans.shared.b16 {%0,%1,%2,%3}, [%4];"
                   : "=r"(y[0]), "=r"(y[1]), "=r"(y[2]), "=r"(y[3]) : "r"(smem_u32(&tile[hh * 640 + tile_perm(lch)])) : "memory");
      const uint4 qv4 = *reinterpret_cast<const uint4*>(&sm.q[row][base + 8 * tq]);
      const uint4 qn4 = *reinterpret_cast<const uint4*>(qn_s + row * QSTR + base + 8 * tq);
      hreg[4 * k + 0] = b2u(__hadd2_rn(u2b(qv4.x), __hmul2_rn(u2b(qn4.x), u2b(y[0]))));
      hreg[4 * k + 1] = b2u(__hadd2_rn(u2b(qv4.y), __hmul2_rn(u2b(qn4.y), u2b(y[1]))));
      hreg[4 * k + 2] = b2u(__hadd2_rn(u2b(qv4.z), __hmul2_rn(u2b(qn4.z), u2b(y[2]))));
      hreg[4 * k + 3] = b2u(__hadd2_rn(u2b(qv4.w), __hmul2_rn(u2b(qn4.w), u2b(y[3]))));
      mma_bf16(cs, hreg[4 * k + 0], hreg[4 * k + 1], 0x3F803F80u, 0x3F803F80u);
      mma_bf16(cs, hreg[4 * k + 2], hreg[4 * k + 3], 0x3F803F80u, 0x3F803F80u);
    }
    const float mean = cs[0] * (1.f / 128.f);
    float m2a = 0.f, m2b = 0.f;
#pragma unroll
    for (int i = 0; i < 16; i++) {
      const float a = lo_f(hreg[i]) - mean, b = hi_f(hreg[i]) - mean;
      m2a = fmaf(a, a, m2a); m2b = fmaf(b, b, m2b);
    }
    float m2 = m2a + m2b;
    m2 += __shfl_xor_sync(0xffffffffu, m2, 1);
    m2 += __shfl_xor_sync(0xffffffffu, m2, 2);
    if (tq == 0) sm.st[row][gqi] = make_float2(mean, m2);
  }
  STAMP(13);
  __syncthreads();
  if (wid < 10) {
    float mean = 0.f, m2 = 0.f;
    float2 p[5];
#pragma unroll
    for (int i = 0; i < 5; i++) { p[i] = sm.st[row][i]; mean += p[i].x; }
    mean *= 0.2f;
#pragma unroll
    for (int i = 0; i < 5; i++) { const float dl = p[i].x - mean; m2 += p[i].y + 128.f * dl * dl; }
    const float hd = rbf(sqrtf(rbf(rbf(m2 * (1.f / D_)) + 1e-5f)));
    const float hr = 1.f / hd;
    const bf162 hm2 = __float2bfloat162_rn(mean);
    float cr[4] = {0.f, 0.f, 0.f, 0.f};
#pragma unroll
    for (int k = 0; k < 4; k++) {
      const uint4 w4 = sm.wr[4 * (4 * gqi + k) + tq];
#pragma unroll
      for (int i = 0; i < 4; i++) {
        const uint32_t d = b2u(__hsub2_rn(u2b(hreg[4 * k + i]), hm2));
        hnreg[4 * k + i] = pack2(fdivr(lo_f(d), hd, hr), fdivr(hi_f(d), hd, hr));
      }
      mma_bf16(cr, hnreg[4 * k + 0], hnreg[4 * k + 1], w4.x, w4.y);
      mma_bf16(cr, hnreg[4 * k + 2], hnreg[4 * k + 3], w4.z, w4.w);
    }
    if (tq == 0) sm.rp[row][gqi] = cr[0];
  }
  STAMP(14);
  __syncthreads();
  uint32_t best;
  {
    const int rr = lane & 15;
    const float r = ((sm.rp[rr][0] + sm.rp[rr][1]) + (sm.rp[rr][2] + sm.rp[rr][3])) + sm.rp[rr][4];
    const uint32_t bits = __bfloat16_as_ushort(__float2bfloat16_rn(r));
    const uint32_t ord = (bits & 0x8000u) ? (bits ^ 0xFFFFu) : (bits ^ 0x8000u);
    const uint32_t key = (ord << 16) | 0x8000u | (uint32_t)(2047 - (cta * 16 + rr));
    best = __reduce_max_sync(0xffffffffu, key);
  }
  if (tid == 352) asm volatile("st.relaxed.gpu.global.u32 [%0], %1;" ::"l"(&g_keys[cta]), "r"(best) : "memory");
  STAMP(15);
  const int brow = (2047 - (int)(best & 0x7FFu)) - cta * 16;
  uint4 outv[4];
  if (wid < 10) {
#pragma unroll
    for (int k = 0; k < 4; k++) {
      outv[k].x = b2u(__hadd2_rn(u2b(hreg[4 * k + 0]), u2b(hnreg[4 * k + 0])));
      outv[k].y = b2u(__hadd2_rn(u2b(hreg[4 * k + 1]), u2b(hnreg[4 * k + 1])));
      outv[k].z = b2u(__hadd2_rn(u2b(hreg[4 * k + 2]), u2b(hnreg[4 * k + 2])));
      outv[k].w = b2u(__hadd2_rn(u2b(hreg[4 * k + 3]), u2b(hnreg[4 * k + 3])));
      const int chunk = 4 * (4 * gqi + k) + tq;
      if (row == brow) {
        st_pub4(&g_cand[cta][0][chunk], enc4(make_uint4(hnreg[4 * k], hnreg[4 * k + 1], hnreg[4 * k + 2], hnreg[4 * k + 3])));
        st_pub4(&g_cand[cta][1][chunk], enc4(make_uint4(hreg[4 * k], hreg[4 * k + 1], hreg[4 * k + 2], hreg[4 * k + 3])));
      } else {
        *reinterpret_cast<uint4*>(gout + (size_t)(cta * 16 + row) * D_ + chunk * 8) = outv[k];
      }
    }
  }
  STAMP(6);
  if (wid == 11) {
    const uint4* kp = reinterpret_cast<const uint4*>(g_keys) + lane;
    uint4 v = ld_poll4(kp);
    int it = 0;
    while (!ready4(v) && ++it < SPIN_LIMIT) v = ld_poll4(kp);
    const uint32_t m = max(max(v.x, v.y), max(v.z, v.w));
    const uint32_t wk = __reduce_max_sync(0xffffffffu, m);
    if (lane == 0) sm.win = wk;
  }
  __syncthreads();
  const uint32_t win = sm.win;
  const int wrow = 2047 - (int)(win & 0x7FFu);
  const int wcta = wrow >> 4;
  if (wid < 10 && row == brow && wcta != cta) {
#pragma unroll
    for (int k = 0; k < 4; k++)
      *reinterpret_cast<uint4*>(gout + (size_t)(cta * 16 + row) * D_ + (4 * (4 * gqi + k) + tq) * 8) = outv[k];
  }
  STAMP(7);
  if (cta < N1 + N2) mbar_wait(&sm.mbarw);
  float* xs = &sm.z[0][0][0];
  float* part = xs + 2048;
  if (cta < N1) {
    if (tid < 80) {
      const uint4 v = poll4(&g_cand[wcta][0][tid]);
      float4* xp = reinterpret_cast<float4*>(xs + tid * 8);
      xp[0] = make_float4(lo_f(v.x), hi_f(v.x), lo_f(v.y), hi_f(v.y));
      xp[1] = make_float4(lo_f(v.z), hi_f(v.z), lo_f(v.w), hi_f(v.w));
    }
    __syncthreads();
    const int m = wid / 6, hc = (wid % 6) >> 1, rs = (wid & 1) * 32 + lane;
    float a[8];
#pragma unroll
    for (int j = 0; j < 8; j++) a[j] = 0.f;
#pragma unroll
    for (int it = 0; it < 10; it++) {
      const int r = rs + 64 * it;
      const uint4 wv = sm.w[m * 1920 + r * 3 + hc];
      const float x = xs[r];
      a[0] = fmaf(x, lo_f(wv.x), a[0]); a[1] = fmaf(x, hi_f(wv.x), a[1]);
      a[2] = fmaf(x, lo_f(wv.y), a[2]); a[3] = fmaf(x, hi_f(wv.y), a[3]);
      a[4] = fmaf(x, lo_f(wv.z), a[4]); a[5] = fmaf(x, hi_f(wv.z), a[5]);
      a[6] = fmaf(x, lo_f(wv.w), a[6]); a[7] = fmaf(x, hi_f(wv.w), a[7]);
    }
    {
      const bool up = lane & 16;
#pragma unroll
      for (int j = 0; j < 4; j++) {
        const float send = up ? a[j] : a[j + 4], keep = up ? a[j + 4] : a[j];
        a[j] = keep + __shfl_xor_sync(0xffffffffu, send, 16);
      }
      const bool up2 = lane & 8;
#pragma unroll
      for (int j = 0; j < 2; j++) {
        const float send = up2 ? a[j] : a[j + 2], keep = up2 ? a[j + 2] : a[j];
        a[j] = keep + __shfl_xor_sync(0xffffffffu, send, 8);
      }
      const bool up3 = lane & 4;
      const float send = up3 ? a[0] : a[1], keep = up3 ? a[1] : a[0];
      a[0] = keep + __shfl_xor_sync(0xffffffffu, send, 4);
      a[0] += __shfl_xor_sync(0xffffffffu, a[0], 2);
      a[0] += __shfl_xor_sync(0xffffffffu, a[0], 1);
      if ((lane & 3) == 0) part[wid * 8 + (lane >> 2)] = a[0];
    }
    __syncthreads();
    if (wid == 0) {
      uint32_t bits = 0;
      if (lane < 24) {
        const int hc2 = lane >> 3, j = lane & 7;
        const float gt = rbf(part[(2 * hc2) * 8 + j] + part[(2 * hc2 + 1) * 8 + j]);
        const float up = rbf(part[(6 + 2 * hc2) * 8 + j] + part[(6 + 2 * hc2 + 1) * 8 + j]);
        const float sg = rbf(gt / (1.f + __expf(-gt)));
        bits = __bfloat16_as_ushort(__float2bfloat16_rn(sg * up));
      }
      const uint32_t nb = __shfl_down_sync(0xffffffffu, bits, 1);
      const uint32_t pw = bits | (nb << 16);
      const uint32_t w1 = __shfl_down_sync(0xffffffffu, pw, 2), w2 = __shfl_down_sync(0xffffffffu, pw, 4), w3 = __shfl_down_sync(0xffffffffu, pw, 6);
      if (lane < 24 && (lane & 7) == 0) st_pub4(&g_act[cta * 3 + (lane >> 3)], enc4(make_uint4(pw, w1, w2, w3)));
    }
  } else if (cta < N1 + N2) {
    const int j2 = cta - N1;
    uint4 rowv = make_uint4(0, 0, 0, 0);
    if (tid < 192) {
      const uint4 v = poll4(&g_act[tid]);
      float4* xp = reinterpret_cast<float4*>(xs + tid * 8);
      xp[0] = make_float4(lo_f(v.x), hi_f(v.x), lo_f(v.y), hi_f(v.y));
      xp[1] = make_float4(lo_f(v.z), hi_f(v.z), lo_f(v.w), hi_f(v.w));
    } else if (tid < 196) {
      const int t = tid - 192;
      rowv = poll4(&g_cand[wcta][t >> 1][j2 * 2 + (t & 1)]);
      reinterpret_cast<uint4*>(part + 256)[t] = rowv;
    }
    __syncthreads();
    const int hc = lane & 1, rs = wid * 16 + (lane >> 1);
    float a[8];
#pragma unroll
    for (int j = 0; j < 8; j++) a[j] = 0.f;
#pragma unroll
    for (int it = 0; it < 8; it++) {
      const int r = rs + 192 * it;
      const uint4 wv = sm.w[r * 2 + hc];
      const float x = xs[r];
      a[0] = fmaf(x, lo_f(wv.x), a[0]); a[1] = fmaf(x, hi_f(wv.x), a[1]);
      a[2] = fmaf(x, lo_f(wv.y), a[2]); a[3] = fmaf(x, hi_f(wv.y), a[3]);
      a[4] = fmaf(x, lo_f(wv.z), a[4]); a[5] = fmaf(x, hi_f(wv.z), a[5]);
      a[6] = fmaf(x, lo_f(wv.w), a[6]); a[7] = fmaf(x, hi_f(wv.w), a[7]);
    }
    {
      const bool up = lane & 16;
#pragma unroll
      for (int j = 0; j < 4; j++) {
        const float send = up ? a[j] : a[j + 4], keep = up ? a[j + 4] : a[j];
        a[j] = keep + __shfl_xor_sync(0xffffffffu, send, 16);
      }
      const bool up2 = lane & 8;
#pragma unroll
      for (int j = 0; j < 2; j++) {
        const float send = up2 ? a[j] : a[j + 2], keep = up2 ? a[j + 2] : a[j];
        a[j] = keep + __shfl_xor_sync(0xffffffffu, send, 8);
      }
      const bool up3 = lane & 4;
      const float send = up3 ? a[0] : a[1], keep = up3 ? a[1] : a[0];
      a[0] = keep + __shfl_xor_sync(0xffffffffu, send, 4);
      a[0] += __shfl_xor_sync(0xffffffffu, a[0], 2);
      if ((lane & 2) == 0) part[wid * 16 + hc * 8 + (lane >> 2)] = a[0];
    }
    __syncthreads();
    if (tid < 16) {
      float y = 0.f;
#pragma unroll
      for (int i = 0; i < 12; i++) y += part[i * 16 + tid];
      const uint32_t ord = win >> 16;
      const uint32_t rb = (ord & 0x8000u) ? (ord ^ 0x8000u) : (ord ^ 0xFFFFu);
      const float r = __uint_as_float(rb << 16);
      const float sg = rbf(1.f / (1.f + __expf(-r)));
      const float yy = rbf(rbf(y) * sg);
      const unsigned short* rv = reinterpret_cast<const unsigned short*>(part + 256);
      const float hn = __uint_as_float((uint32_t)rv[tid] << 16), h = __uint_as_float((uint32_t)rv[16 + tid] << 16);
      gout[(size_t)wrow * D_ + j2 * 16 + tid] = __float2bfloat16_rn(h + rbf(hn + yy));
    }
  }
  STAMP(8);
}

}

typedef CUresult (*EncodeFn)(CUtensorMap*, CUtensorMapDataType, cuuint32_t, void*, const cuuint64_t*, const cuuint64_t*,
                             const cuuint32_t*, const cuuint32_t*, CUtensorMapInterleave, CUtensorMapSwizzle,
                             CUtensorMapL2promotion, CUtensorMapFloatOOBfill);

extern "C" void kernel_launch(void* const* d_in, const int* in_sizes, int n_in, void* d_out, int out_size) {
  (void)in_sizes; (void)n_in; (void)out_size;
  static EncodeFn encode = nullptr;
  static CUtensorMap tmg, tmu, tmd;
  static void* cached[3] = {nullptr, nullptr, nullptr};
  if (!encode) {
    cudaFuncSetAttribute(fused_kernel, cudaFuncAttributeMaxDynamicSharedMemorySize, (int)sizeof(Smem));
    void* fn = nullptr;
    cudaDriverEntryPointQueryResult qr;
    cudaGetDriverEntryPoint("cuTensorMapEncodeTiled", &fn, cudaEnableDefault, &qr);
    encode = (EncodeFn)fn;
  }
  if (cached[0] != d_in[8] || cached[1] != d_in[9] || cached[2] != d_in[10]) {
    const cuuint32_t es[2] = {1, 1};
    {
      const cuuint64_t dims[2] = {F_, D_}, strides[1] = {F_ * 2};
      const cuuint32_t box[2] = {24, 160};
      encode(&tmg, CU_TENSOR_MAP_DATA_TYPE_BFLOAT16, 2, d_in[8], dims, strides, box, es, CU_TENSOR_MAP_INTERLEAVE_NONE,
             CU_TENSOR_MAP_SWIZZLE_NONE, CU_TENSOR_MAP_L2_PROMOTION_NONE, CU_TENSOR_MAP_FLOAT_OOB_FILL_NONE);
      encode(&tmu, CU_TENSOR_MAP_DATA_TYPE_BFLOAT16, 2, d_in[9], dims, strides, box, es, CU_TENSOR_MAP_INTERLEAVE_NONE,
             CU_TENSOR_MAP_SWIZZLE_NONE, CU_TENSOR_MAP_L2_PROMOTION_NONE, CU_TENSOR_MAP_FLOAT_OOB_FILL_NONE);
    }
    {
      const cuuint64_t dims[2] = {D_, F_}, strides[1] = {D_ * 2};
      const cuuint32_t box[2] = {16, 256};
      encode(&tmd, CU_TENSOR_MAP_DATA_TYPE_BFLOAT16, 2, d_in[10], dims, strides, box, es, CU_TENSOR_MAP_INTERLEAVE_NONE,
             CU_TENSOR_MAP_SWIZZLE_NONE, CU_TENSOR_MAP_L2_PROMOTION_NONE, CU_TENSOR_MAP_FLOAT_OOB_FILL_NONE);
    }
    cached[0] = d_in[8]; cached[1] = d_in[9]; cached[2] = d_in[10];
  }
  fused_kernel<<<NCTA, NTHR, sizeof(Smem), cudaStreamPerThread>>>(
      tmg, tmu, tmd, (const bf16*)d_in[0], (const bf16*)d_in[1], (const bf16*)d_in[2], (const bf16*)d_in[3],
      (const bf16*)d_in[4], (const bf16*)d_in[5], (const bf16*)d_in[7], (bf16*)d_out);
}
```

```cpp
#include <cuda_runtime.h>
#include <cuda_bf16.h>
#include <cuda.h>
#include <stdint.h>

namespace {

typedef __nv_bfloat16 bf16;
typedef __nv_bfloat162 bf162;

constexpr int S_ = 2048, D_ = 640, F_ = 1536;
constexpr int NCTA = 128, CPC = 5, NTHR = 384;
constexpr int UPAD = 136, USTR = 2192;
constexpr int TABW = 1040;
constexpr int ZPB = 132;
constexpr int QSTR = 648;
constexpr int N1 = 64;
constexpr int N2 = 40;
constexpr int SPIN_LIMIT = 1 << 19;
#define POLL_NS 100
#define H_DELAY 0
#define Q_DELAY 4500

struct __align__(128) Smem {
  uint32_t tabA[3][2][TABW];
  uint32_t extra[1024];
  uint32_t tabB[2][2][TABW];
  bf16 u[CPC][USTR];
  float z[2][4][ZPB * 16];
  bf16 q[16][QSTR];
  alignas(128) uint4 w[3840];
  uint4 wr[80];
  float2 st[16][5];
  float rp[16][5];
  unsigned long long mbar;
  unsigned long long mbarw;
  unsigned long long mbarc;
  unsigned long long mbarh;
  uint32_t target;
  uint32_t best;
  uint32_t win;
};

__device__ uint4 g_kv[D_ * S_ / 8];
__device__ uint4 g_y2[D_ * S_ / 8];
__device__ uint32_t g_keys[NCTA];
__device__ uint4 g_cand[NCTA][2][80];
__device__ uint4 g_act[F_ / 8];
__device__ unsigned int g_ctr;
__device__ unsigned int g_ctr2;
#define STAMP(i)
#define CST(c, i)

__device__ __forceinline__ uint32_t smem_u32(const void* p) { return (uint32_t)__cvta_generic_to_shared(p); }
__device__ __forceinline__ void wg_fence() { asm volatile("wgmma.fence.sync.aligned;" ::: "memory"); }
__device__ __forceinline__ void wg_commit() { asm volatile("wgmma.commit_group.sync.aligned;" ::: "memory"); }
template <int N> __device__ __forceinline__ void wg_wait() { asm volatile("wgmma.wait_group.sync.aligned %0;" ::"n"(N) : "memory"); }
__device__ __forceinline__ void bar_sync(int id, int n) { asm volatile("bar.sync %0, %1;" ::"r"(id), "r"(n) : "memory"); }
__device__ __forceinline__ void bar_arrive(int id, int n) { asm volatile("bar.arrive %0, %1;" ::"r"(id), "r"(n) : "memory"); }
__device__ __forceinline__ bf162 u2b(uint32_t u) { return *reinterpret_cast<bf162*>(&u); }
__device__ __forceinline__ uint32_t b2u(bf162 b) { return *reinterpret_cast<uint32_t*>(&b); }
__device__ __forceinline__ float lo_f(uint32_t u) { return __uint_as_float(u << 16); }
__device__ __forceinline__ float hi_f(uint32_t u) { return __uint_as_float(u & 0xFFFF0000u); }
__device__ __forceinline__ float rbf(float x) { return __bfloat162float(__float2bfloat16_rn(x)); }
__device__ __forceinline__ uint32_t pack2(float a, float b) { return b2u(__floats2bfloat162_rn(a, b)); }
__device__ __forceinline__ uint32_t enc(uint32_t w) { return max(~w, 1u); }
__device__ __forceinline__ uint4 enc4(uint4 v) { return make_uint4(enc(v.x), enc(v.y), enc(v.z), enc(v.w)); }
__device__ __forceinline__ uint4 ld_poll4(const uint4* p) {
  uint4 v;
  asm volatile("ld.relaxed.gpu.global.v4.u32 {%0,%1,%2,%3}, [%4];" : "=r"(v.x), "=r"(v.y), "=r"(v.z), "=r"(v.w) : "l"(p) : "memory");
  return v;
}
__device__ __forceinline__ bool ready4(uint4 v) { return v.x != 0u && v.y != 0u && v.z != 0u && v.w != 0u; }
__device__ __forceinline__ uint4 poll4(const uint4* p) {
  uint4 v = ld_poll4(p);
  int it = 0;
  while (!ready4(v) && ++it < SPIN_LIMIT) v = ld_poll4(p);
  return make_uint4(~v.x, ~v.y, ~v.z, ~v.w);
}
__device__ __forceinline__ void st_pub4(uint4* p, uint4 v) {
  asm volatile("st.relaxed.gpu.global.v4.u32 [%0], {%1,%2,%3,%4};" ::"l"(p), "r"(v.x), "r"(v.y), "r"(v.z), "r"(v.w) : "memory");
}
__device__ __forceinline__ void st_pub2(uint2* p, uint32_t a, uint32_t b) {
  asm volatile("st.relaxed.gpu.global.v2.u32 [%0], {%1,%2};" ::"l"(p), "r"(a), "r"(b) : "memory");
}
__device__ __forceinline__ void mma_bf16(float (&c)[4], uint32_t a0, uint32_t a2, uint32_t b0, uint32_t b1) {
  asm volatile("mma.sync.aligned.m16n8k16.row.col.f32.bf16.bf16.f32 {%0,%1,%2,%3}, {%4,%5,%6,%5}, {%7,%8}, {%0,%1,%2,%3};"
               : "+f"(c[0]), "+f"(c[1]), "+f"(c[2]), "+f"(c[3]) : "r"(a0), "r"(0u), "r"(a2), "r"(b0), "r"(b1));
}
__device__ __forceinline__ void mbar_wait(const unsigned long long* bar) {
  const uint32_t mb = smem_u32(bar);
  uint32_t ok = 0;
  int it = 0;
  while (!ok && ++it < SPIN_LIMIT)
    asm volatile("{ .reg .pred p; mbarrier.try_wait.parity.shared.b64 p, [%1], 0; selp.u32 %0, 1, 0, p; }" : "=r"(ok) : "r"(mb) : "memory");
}
__device__ __forceinline__ void bulk_g2s(void* dst, const void* src, uint32_t bytes, const unsigned long long* bar) {
  asm volatile("cp.async.bulk.shared::cluster.global.mbarrier::complete_tx::bytes [%0], [%1], %2, [%3];" ::"r"(smem_u32(dst)),
               "l"(src), "r"(bytes), "r"(smem_u32(bar)) : "memory");
}
__device__ __forceinline__ void mbar_expect(const unsigned long long* bar, uint32_t bytes) {
  asm volatile("mbarrier.arrive.expect_tx.shared.b64 _, [%0], %1;" ::"r"(smem_u32(bar)), "r"(bytes) : "memory");
}
__device__ __forceinline__ void mma_bf16x(float (&c)[4], uint32_t a0, uint32_t a1, uint32_t a2, uint32_t a3, uint32_t b0, uint32_t b1) {
  asm volatile("mma.sync.aligned.m16n8k16.row.col.f32.bf16.bf16.f32 {%0,%1,%2,%3}, {%4,%5,%6,%7}, {%8,%9}, {%0,%1,%2,%3};"
               : "+f"(c[0]), "+f"(c[1]), "+f"(c[2]), "+f"(c[3]) : "r"(a0), "r"(a1), "r"(a2), "r"(a3), "r"(b0), "r"(b1));
}
__device__ __forceinline__ float fdivr(float a, float d, float r) {
  float q = a * r;
  float e = fmaf(-q, d, a);
  return fmaf(e, r, q);
}

template <bool FIRST> __device__ __forceinline__ void wgmma32(float (&d)[16], const uint32_t* a, uint64_t desc) {
  if (FIRST) {
    asm volatile("wgmma.mma_async.sync.aligned.m64n32k16.f32.bf16.bf16 {%0,%1,%2,%3,%4,%5,%6,%7,%8,%9,%10,%11,%12,%13,%14,%15}, {%16,%17,%18,%19}, %20, 0, 1, 1, 0;"
                 : "+f"(d[0]), "+f"(d[1]), "+f"(d[2]), "+f"(d[3]), "+f"(d[4]), "+f"(d[5]), "+f"(d[6]), "+f"(d[7]),
                   "+f"(d[8]), "+f"(d[9]), "+f"(d[10]), "+f"(d[11]), "+f"(d[12]), "+f"(d[13]), "+f"(d[14]), "+f"(d[15])
                 : "r"(a[0]), "r"(a[1]), "r"(a[2]), "r"(a[3]), "l"(desc));
  } else {
    asm volatile("wgmma.mma_async.sync.aligned.m64n32k16.f32.bf16.bf16 {%0,%1,%2,%3,%4,%5,%6,%7,%8,%9,%10,%11,%12,%13,%14,%15}, {%16,%17,%18,%19}, %20, 1, 1, 1, 0;"
                 : "+f"(d[0]), "+f"(d[1]), "+f"(d[2]), "+f"(d[3]), "+f"(d[4]), "+f"(d[5]), "+f"(d[6]), "+f"(d[7]),
                   "+f"(d[8]), "+f"(d[9]), "+f"(d[10]), "+f"(d[11]), "+f"(d[12]), "+f"(d[13]), "+f"(d[14]), "+f"(d[15])
                 : "r"(a[0]), "r"(a[1]), "r"(a[2]), "r"(a[3]), "l"(desc));
  }
}

template <int G> __device__ __forceinline__ void load_a(uint32_t (&a)[8], const uint32_t* tp) {
#pragma unroll
  for (int q = 0; q < 2; q++) {
    const int e = 2 * G + q;
    a[4 * q + 0] = tp[-64 * e];
    a[4 * q + 1] = tp[-64 * e - 32];
    a[4 * q + 2] = tp[-64 * e + 4];
    a[4 * q + 3] = tp[-64 * e - 28];
  }
}
__device__ __forceinline__ void load_a_all(uint32_t (&a)[8][8], const uint32_t* tp) {
  load_a<0>(a[0], tp); load_a<1>(a[1], tp); load_a<2>(a[2], tp); load_a<3>(a[3], tp);
  load_a<4>(a[4], tp); load_a<5>(a[5], tp); load_a<6>(a[6], tp); load_a<7>(a[7], tp);
}
template <int G> __device__ __forceinline__ void issue_g(float (&acc)[8][16], uint32_t (&a)[8], uint64_t desc0) {
  wg_fence();
#pragma unroll
  for (int q = 0; q < 2; q++) {
#pragma unroll
    for (int b = G; b < 8; b++) {
      const int delta = 2 * b - (2 * G + q);
      if (G == 0 && q == 0) wgmma32<true>(acc[b], &a[4 * q], desc0 + (uint64_t)(int64_t)(16 * delta));
      else wgmma32<false>(acc[b], &a[4 * q], desc0 + (uint64_t)(int64_t)(16 * delta));
    }
  }
  wg_commit();
}
template <int B> __device__ __forceinline__ void fence_blk(float (&acc)[8][16]) {
#pragma unroll
  for (int i = 0; i < 16; i++) asm volatile("" : "+f"(acc[B][i])::"memory");
}
__device__ __forceinline__ void fence_a(uint32_t (&a)[8]) {
#pragma unroll
  for (int i = 0; i < 8; i++) asm volatile("" : "+r"(a[i])::"memory");
}
template <int B> __device__ __forceinline__ void sts_blk(float (&acc)[8][16], float* zw, int off_even, int off_odd) {
#pragma unroll
  for (int jj = 0; jj < 4; jj++) {
    const int j = 4 * B + jj;
    float p0 = acc[B][4 * jj + 0], p1 = acc[B][4 * jj + 1];
    if (jj > 0) { p0 += acc[B][4 * (jj - 1) + 2]; p1 += acc[B][4 * (jj - 1) + 3]; }
    else if (B > 0) { p0 += acc[B > 0 ? B - 1 : 0][14]; p1 += acc[B > 0 ? B - 1 : 0][15]; }
    zw[64 * j + off_even] = p0;
    zw[64 * j + off_odd] = p1;
  }
}
__device__ __forceinline__ int tab_off(int c) { return c == 4 ? 0 : (c + 1) * 2 * TABW + (c >= 2 ? 1024 : 0); }
__device__ __forceinline__ int tile_perm(int ch) { return ch ^ (((ch >> 3) & 3) << 1); }

__device__ __forceinline__ void wait_ctr(const unsigned int* ctr, uint32_t target) {
  uint32_t v;
  int it = 0;
  do {
    asm volatile("ld.acquire.gpu.global.u32 %0, [%1];" : "=r"(v) : "l"(ctr) : "memory");
  } while ((int)(v - target) < 0 && ++it < SPIN_LIMIT);
}

__device__ __forceinline__ void ln_q_row(Smem& sm, bf16* qn_s, int row, int lane) {
  const uint32_t* qp = reinterpret_cast<const uint32_t*>(&sm.q[row][0]);
  uint32_t qa[10];
  float s0 = 0.f, s1 = 0.f;
#pragma unroll
  for (int i = 0; i < 10; i++) { qa[i] = qp[lane + 32 * i]; s0 += lo_f(qa[i]); s1 += hi_f(qa[i]); }
  float sa = s0 + s1;
#pragma unroll
  for (int o = 16; o > 0; o >>= 1) sa += __shfl_xor_sync(0xffffffffu, sa, o);
  sa *= (1.f / D_);
  float m0 = 0.f, m1 = 0.f;
#pragma unroll
  for (int i = 0; i < 10; i++) {
    const float x = lo_f(qa[i]) - sa, y = hi_f(qa[i]) - sa;
    m0 = fmaf(x, x, m0); m1 = fmaf(y, y, m1);
  }
  float ma = m0 + m1;
#pragma unroll
  for (int o = 16; o > 0; o >>= 1) ma += __shfl_xor_sync(0xffffffffu, ma, o);
  const float d = rbf(sqrtf(rbf(rbf(ma * (1.f / D_)) + 1e-5f)));
  const float r = 1.f / d;
  const bf162 m2 = __float2bfloat162_rn(sa);
  uint32_t* np = reinterpret_cast<uint32_t*>(qn_s + row * QSTR);
#pragma unroll
  for (int i = 0; i < 10; i++) {
    const uint32_t e = b2u(__hsub2_rn(u2b(qa[i]), m2));
    np[lane + 32 * i] = pack2(fdivr(lo_f(e), d, r), fdivr(hi_f(e), d, r));
  }
}

__global__ void __launch_bounds__(NTHR, 1)
fused_kernel(const __grid_constant__ CUtensorMap tmg, const __grid_constant__ CUtensorMap tmu,
             const __grid_constant__ CUtensorMap tmd, const bf16* __restrict__ gq, const bf16* __restrict__ gk, const bf16* __restrict__ gv,
             const bf16* __restrict__ gsk, const bf16* __restrict__ gh, const bf16* __restrict__ gD,
             const bf16* __restrict__ gwr, bf16* __restrict__ gout) {
  extern __shared__ __align__(128) unsigned char smraw[];
  Smem& sm = *reinterpret_cast<Smem*>(smraw);
  const int tid = threadIdx.x;
  const int cta = blockIdx.x;
  const int c0 = cta * CPC;
  const int lane = tid & 31;
  const int wid = tid >> 5;
  STAMP(0);
  const long long tstart = clock64();

  {
    uint4* hs = reinterpret_cast<uint4*>(&sm.z[0][0][0]);
    const int oc = tid >> 2;
    const int r0 = cta * 16 + (tid & 3) * 4;
    uint4 kk[7], vv[4], sk[4];
    if (tid < 320) {
      const uint4* kp = reinterpret_cast<const uint4*>(gk) + (size_t)r0 * 80 + oc;
      const uint4* vp = reinterpret_cast<const uint4*>(gv) + (size_t)r0 * 80 + oc;
#pragma unroll
      for (int i = 0; i < 7; i++) kk[i] = (i >= 3 || r0 > 0) ? __ldg(kp + (i - 3) * 80) : make_uint4(0, 0, 0, 0);
#pragma unroll
      for (int i = 0; i < 4; i++) vv[i] = __ldg(vp + i * 80);
#pragma unroll
      for (int i = 0; i < 4; i++) sk[i] = __ldg(reinterpret_cast<const uint4*>(gsk) + oc * 4 + i);
    } else if (tid == 320) {
      asm volatile("mbarrier.init.shared.b64 [%0], 1;" ::"r"(smem_u32(&sm.mbarh)) : "memory");
      asm volatile("mbarrier.init.shared.b64 [%0], 1;" ::"r"(smem_u32(&sm.mbar)) : "memory");
      asm volatile("mbarrier.init.shared.b64 [%0], 1;" ::"r"(smem_u32(&sm.mbarw)) : "memory");
      asm volatile("mbarrier.init.shared.b64 [%0], 1;" ::"r"(smem_u32(&sm.mbarc)) : "memory");
      asm volatile("fence.proxy.async.shared::cta;" ::: "memory");
    }
    if (tid < 320) bar_sync(6, 384); else { bar_arrive(6, 384); bar_sync(5, 64); }
    STAMP(9);
    if (tid < 320) {
      uint32_t o[4][4];
#pragma unroll
      for (int p = 0; p < 4; p++) {
        const bf162 w0 = u2b(__byte_perm(sk[p].x, sk[p].z, 0x5410)), w1 = u2b(__byte_perm(sk[p].x, sk[p].z, 0x7632));
        const bf162 w2 = u2b(__byte_perm(sk[p].y, sk[p].w, 0x5410)), w3 = u2b(__byte_perm(sk[p].y, sk[p].w, 0x7632));
        uint32_t kv[4];
#pragma unroll
        for (int i = 0; i < 4; i++) {
          const uint32_t k0 = p == 0 ? kk[i].x : p == 1 ? kk[i].y : p == 2 ? kk[i].z : kk[i].w;
          const uint32_t k1 = p == 0 ? kk[i + 1].x : p == 1 ? kk[i + 1].y : p == 2 ? kk[i + 1].z : kk[i + 1].w;
          const uint32_t k2 = p == 0 ? kk[i + 2].x : p == 1 ? kk[i + 2].y : p == 2 ? kk[i + 2].z : kk[i + 2].w;
          const uint32_t k3 = p == 0 ? kk[i + 3].x : p == 1 ? kk[i + 3].y : p == 2 ? kk[i + 3].z : kk[i + 3].w;
          const uint32_t vx = p == 0 ? vv[i].x : p == 1 ? vv[i].y : p == 2 ? vv[i].z : vv[i].w;
          bf162 a = __hmul2_rn(u2b(k0), w3);
          a = __hadd2_rn(a, __hmul2_rn(u2b(k1), w2));
          a = __hadd2_rn(a, __hmul2_rn(u2b(k2), w1));
          a = __hadd2_rn(a, __hmul2_rn(u2b(k3), w0));
          kv[i] = b2u(__hmul2_rn(a, u2b(vx)));
        }
        o[p][0] = enc(__byte_perm(kv[0], kv[1], 0x5410)); o[p][1] = enc(__byte_perm(kv[2], kv[3], 0x5410));
        o[p][2] = enc(__byte_perm(kv[0], kv[1], 0x7632)); o[p][3] = enc(__byte_perm(kv[2], kv[3], 0x7632));
      }
      uint2* dst = reinterpret_cast<uint2*>(g_kv) + (size_t)(oc * 8) * 512 + (r0 >> 2);
#pragma unroll
      for (int p = 0; p < 4; p++) {
        st_pub2(dst + (2 * p) * 512, o[p][0], o[p][1]);
        st_pub2(dst + (2 * p + 1) * 512, o[p][2], o[p][3]);
      }
      STAMP(10);
      if (wid == 0) bar_sync(4, 320); else bar_arrive(4, 320);
      if (tid == 0) {
        const unsigned old = atomicAdd(&g_ctr2, 1u);
        const unsigned target = (old / NCTA + 1u) * NCTA;
        uint32_t v;
        int it = 0;
        do {
          asm volatile("ld.relaxed.gpu.global.u32 %0, [%1];" : "=r"(v) : "l"(&g_ctr2) : "memory");
        } while ((int)(v - target) < 0 && ++it < SPIN_LIMIT);
        asm volatile("mbarrier.arrive.shared.b64 _, [%0];" ::"r"(smem_u32(&sm.mbarc)) : "memory");
      }
      __syncwarp();
    } else {
      const int t0 = tid - 320;
      const uint4 zz = make_uint4(0, 0, 0, 0);
      if (tid == 320) {
        while (clock64() - tstart < H_DELAY) {}
        mbar_expect(&sm.mbarh, CPC * S_ * 2);
        bulk_g2s(hs, gh + (size_t)c0 * S_, CPC * S_ * 2, &sm.mbarh);
      }
      __syncwarp();
      for (int t = t0; t < CPC * 17; t += 64) *reinterpret_cast<uint4*>(&sm.u[t / 17][(t % 17) * 8]) = zz;
      if (t0 < 40) *reinterpret_cast<uint4*>(&sm.tabA[0][0][0] + tab_off(t0 >> 3) + ((t0 >> 2) & 1) * TABW + 1024 + 4 * (t0 & 3)) = zz;
#pragma unroll 4
      for (int i = 0; i < 20; i++) g_y2[cta * 1280 + t0 + 64 * i] = zz;
      (&g_cand[cta][0][0])[t0] = zz;
      (&g_cand[cta][0][0])[64 + t0] = zz;
      if (t0 < 32) (&g_cand[cta][0][0])[128 + t0] = zz;
      else if (t0 < 35) { if (cta < N1) g_act[cta * 3 + (t0 - 32)] = zz; }
      else if (t0 == 35) g_keys[cta] = 0u;
      bar_sync(5, 64);
      if (tid == 352) {
        __threadfence();
        const unsigned old = atomicAdd(&g_ctr, 1u);
        sm.target = (old / NCTA + 1u) * NCTA;
      }
      __syncwarp();
    }
    mbar_wait(&sm.mbarh);
#pragma unroll
    for (int i = 0; i < 4; i++) {
      const int t = (NTHR - 1 - tid) + NTHR * i;
      if (t < CPC * 256) {
        uint32_t* tb = &sm.tabA[0][0][0] + tab_off(t >> 8) + (255 - (t & 255)) * 4;
        const uint4 h = hs[t];
        const uint32_t hp = (t & 255) ? reinterpret_cast<const uint32_t*>(hs)[4 * t - 1] : 0u;
        uint4 r1, rr;
        r1.x = __byte_perm(h.w, 0, 0x1032); r1.y = __byte_perm(h.z, 0, 0x1032);
        r1.z = __byte_perm(h.y, 0, 0x1032); r1.w = __byte_perm(h.x, 0, 0x1032);
        rr.x = __byte_perm(h.w, h.z, 0x7610); rr.y = __byte_perm(h.z, h.y, 0x7610);
        rr.z = __byte_perm(h.y, h.x, 0x7610); rr.w = __byte_perm(h.x, hp, 0x7610);
        *reinterpret_cast<uint4*>(tb) = rr;
        *reinterpret_cast<uint4*>(tb + TABW) = r1;
      }
    }
    STAMP(12);
  }
  mbar_wait(&sm.mbarc);
  {
    uint4 v[4];
    uint4* src = g_kv + c0 * 256 + tid;
#pragma unroll
    for (int i = 0; i < 4; i++) if (i < 3 || tid < 128) v[i] = ld_poll4(src + NTHR * i);
#pragma unroll
    for (int i = 0; i < 4; i++) {
      if (i < 3 || tid < 128) {
        int it = 0;
        while (!ready4(v[i]) && ++it < SPIN_LIMIT) { __nanosleep(POLL_NS); v[i] = ld_poll4(src + NTHR * i); }
        const int t = tid + NTHR * i;
        *reinterpret_cast<uint4*>(&sm.u[t >> 8][UPAD + (t & 255) * 8]) = make_uint4(~v[i].x, ~v[i].y, ~v[i].z, ~v[i].w);
      }
    }
    STAMP(11);
    asm volatile("fence.proxy.async.shared::cta;" ::: "memory");
    __syncthreads();
#pragma unroll
    for (int i = 0; i < 4; i++) if (i < 3 || tid < 128) src[NTHR * i] = make_uint4(0, 0, 0, 0);
    if (tid >= 256) {
      const int t0 = tid - 256;
      if (((t0 & 15) >> 2) < ((t0 >> 4) & 3))
        *reinterpret_cast<uint4*>(&sm.z[t0 >> 6][(t0 >> 4) & 3][(t0 & 15) * 4]) = make_uint4(0, 0, 0, 0);
    }
  }
  STAMP(1);

  const int wg = __shfl_sync(0xffffffffu, tid >> 7, 0);
  const int wtid = tid & 127;
  uint4* tile = reinterpret_cast<uint4*>(&sm.tabB[0][0][0]);
  bf16* qn_s = reinterpret_cast<bf16*>(&sm.tabA[1][0][0]);
  if (wg < 2) {
    asm volatile("setmaxnreg.inc.sync.aligned.u32 224;");
    const int w = (tid >> 5) & 3, g = lane >> 2, tq = lane & 3;
    float* zw = sm.z[wg][w];
    const int sw = 3 * (((tq + w) >> 1) & 1);
    const int off_even = 16 * (tq + w) + 4 * ((0 + (g >> 2)) ^ sw) + (g & 3);
    const int off_odd = 16 * (tq + w) + 4 * ((2 + (g >> 2)) ^ sw) + (g & 3);
    uint32_t a[8][8];
    const uint32_t* tp0 = &sm.tabA[0][g & 1][1019 - 8 * w - (g >> 1) + tq];
    load_a_all(a, tp0 + tab_off(wg));
    float acc[8][16];
#pragma unroll
    for (int b = 0; b < 8; b++)
#pragma unroll
      for (int i = 0; i < 16; i++) acc[b][i] = 0.f;
#pragma unroll 1
    for (int c = wg; c < CPC; c += 2) {
      const uint64_t desc = (uint64_t)((smem_u32(&sm.u[c][UPAD - 8]) & 0x3FFFF) >> 4) | ((uint64_t)1 << 16) | ((uint64_t)8 << 32);
      CST(c, 0);
      if (c > 0) bar_sync(1 + wg, 256);
      issue_g<0>(acc, a[0], desc);
      CST(c, 1);
      issue_g<1>(acc, a[1], desc);
      issue_g<2>(acc, a[2], desc);
      issue_g<3>(acc, a[3], desc);
      issue_g<4>(acc, a[4], desc);
      issue_g<5>(acc, a[5], desc);
      if (c + 1 < CPC) bar_arrive(1 + (wg ^ 1), 256);
      issue_g<6>(acc, a[6], desc);
      issue_g<7>(acc, a[7], desc);
      CST(c, 2);
      if (c >= 2) bar_sync(5 + wg, 256);
      wg_wait<4>();
      fence_blk<0>(acc); fence_blk<1>(acc); fence_blk<2>(acc); fence_blk<3>(acc);
      sts_blk<0>(acc, zw, off_even, off_odd);
      sts_blk<1>(acc, zw, off_even, off_odd);
      sts_blk<2>(acc, zw, off_even, off_odd);
      sts_blk<3>(acc, zw, off_even, off_odd);
      CST(c, 3);
      wg_wait<0>();
      fence_blk<4>(acc); fence_blk<5>(acc); fence_blk<6>(acc); fence_blk<7>(acc);
#pragma unroll
      for (int i = 0; i < 8; i++) fence_a(a[i]);
      sts_blk<4>(acc, zw, off_even, off_odd);
      sts_blk<5>(acc, zw, off_even, off_odd);
      sts_blk<6>(acc, zw, off_even, off_odd);
      sts_blk<7>(acc, zw, off_even, off_odd);
      bar_arrive(3 + wg, 256);
      CST(c, 4);
      if (c + 2 < CPC) load_a_all(a, tp0 + tab_off(c + 2));
    }
    STAMP(2 + wg);
    asm volatile("setmaxnreg.dec.sync.aligned.u32 168;");
  } else {
    asm volatile("setmaxnreg.dec.sync.aligned.u32 56;");
    if (wtid == 32) {
      const uint32_t mw = smem_u32(&sm.mbarw);
      mbar_expect(&sm.mbar, 17 * D_ * 2);
#pragma unroll 1
      for (int r = 0; r < 16; r++) bulk_g2s(&sm.q[r][0], gq + (size_t)(cta * 16 + r) * D_, D_ * 2, &sm.mbar);
      bulk_g2s(&sm.wr[0], gwr, D_ * 2, &sm.mbar);
      if (cta < N1) {
        asm volatile("mbarrier.arrive.expect_tx.shared.b64 _, [%0], %1;" ::"r"(mw), "r"(3840 * 16) : "memory");
#pragma unroll 1
        for (int i = 0; i < 4; i++) {
          asm volatile("cp.async.bulk.tensor.2d.shared::cluster.global.mbarrier::complete_tx::bytes [%0], [%1, {%3, %4}], [%2];" ::"r"(smem_u32(&sm.w[i * 480])),
                       "l"(&tmg), "r"(mw), "r"(cta * 24), "r"(i * 160) : "memory");
          asm volatile("cp.async.bulk.tensor.2d.shared::cluster.global.mbarrier::complete_tx::bytes [%0], [%1, {%3, %4}], [%2];" ::"r"(smem_u32(&sm.w[1920 + i * 480])),
                       "l"(&tmu), "r"(mw), "r"(cta * 24), "r"(i * 160) : "memory");
        }
      } else if (cta < N1 + N2) {
        asm volatile("mbarrier.arrive.expect_tx.shared.b64 _, [%0], %1;" ::"r"(mw), "r"(3072 * 16) : "memory");
#pragma unroll 1
        for (int i = 0; i < 6; i++)
          asm volatile("cp.async.bulk.tensor.2d.shared::cluster.global.mbarrier::complete_tx::bytes [%0], [%1, {%3, %4}], [%2];" ::"r"(smem_u32(&sm.w[i * 512])),
                       "l"(&tmd), "r"(mw), "r"((cta - N1) * 16), "r"(i * 256) : "memory");
      }
    }
    if (wtid == 0) wait_ctr(&g_ctr, sm.target);
    const int rpb = wtid >> 1, re2 = wtid & 1;
    const int rsw = 3 * ((rpb >> 1) & 1);
    const int roff0 = 16 * rpb + 4 * ((2 * re2 + 0) ^ rsw);
    const int roff1 = 16 * rpb + 4 * ((2 * re2 + 1) ^ rsw);
    const uint32_t dvl = reinterpret_cast<const unsigned short*>(gD)[c0 + (lane < CPC ? lane : 0)];
#pragma unroll 1
    for (int c = 0; c < CPC; c++) {
      const int zg = c & 1;
      const uint32_t dvc = __shfl_sync(0xffffffffu, dvl, c);
      const bf162 d2 = u2b(dvc | (dvc << 16));
      CST(c, 5);
      bar_sync(3 + zg, 256);
#pragma unroll
      for (int half = 0; half < 2; half++) {
        const float* zb = sm.z[zg][0] + half * 1024;
        float4 x[4][2];
#pragma unroll
        for (int ww = 0; ww < 4; ww++) {
          x[ww][0] = *reinterpret_cast<const float4*>(zb + ww * ZPB * 16 + roff0);
          x[ww][1] = *reinterpret_cast<const float4*>(zb + ww * ZPB * 16 + roff1);
        }
        const int sidx = half * 1024 + wtid * 8;
        const uint4 kvv = *reinterpret_cast<const uint4*>(&sm.u[c][UPAD + sidx]);
        if (half == 1 && c + 2 < CPC) bar_arrive(5 + zg, 256);
        uint4 o;
        o.x = pack2((x[0][0].x + x[1][0].x) + (x[2][0].x + x[3][0].x), (x[0][0].y + x[1][0].y) + (x[2][0].y + x[3][0].y));
        o.y = pack2((x[0][0].z + x[1][0].z) + (x[2][0].z + x[3][0].z), (x[0][0].w + x[1][0].w) + (x[2][0].w + x[3][0].w));
        o.z = pack2((x[0][1].x + x[1][1].x) + (x[2][1].x + x[3][1].x), (x[0][1].y + x[1][1].y) + (x[2][1].y + x[3][1].y));
        o.w = pack2((x[0][1].z + x[1][1].z) + (x[2][1].z + x[3][1].z), (x[0][1].w + x[1][1].w) + (x[2][1].w + x[3][1].w));
        o.x = b2u(__hadd2_rn(u2b(o.x), __hmul2_rn(u2b(kvv.x), d2)));
        o.y = b2u(__hadd2_rn(u2b(o.y), __hmul2_rn(u2b(kvv.y), d2)));
        o.z = b2u(__hadd2_rn(u2b(o.z), __hmul2_rn(u2b(kvv.z), d2)));
        o.w = b2u(__hadd2_rn(u2b(o.w), __hmul2_rn(u2b(kvv.w), d2)));
        st_pub4(g_y2 + ((64 * half + rpb) * 640 + c0 + c) * 2 + re2, enc4(o));
        CST(c, 6 + half);
      }
    }
    STAMP(4);
    asm volatile("setmaxnreg.inc.sync.aligned.u32 168;");
  }

  {
    const uint4* src = g_y2 + cta * 1280 + tid;
    uint4 v[4];
#pragma unroll
    for (int i = 0; i < 4; i++) if (i < 3 || tid < 128) v[i] = ld_poll4(src + NTHR * i);
    mbar_wait(&sm.mbar);
    if (wg == 1) { ln_q_row(sm, qn_s, 2 * wid, lane); ln_q_row(sm, qn_s, 2 * wid + 1, lane); }
    else ln_q_row(sm, qn_s, wid < 4 ? wid : wid - 4, lane);
    int it = 0;
    bool all;
    do {
      all = true;
#pragma unroll
      for (int i = 0; i < 4; i++)
        if ((i < 3 || tid < 128) && !ready4(v[i])) { v[i] = ld_poll4(src + NTHR * i); all = false; }
    } while (!all && ++it < SPIN_LIMIT);
#pragma unroll
    for (int i = 0; i < 4; i++) {
      if (i < 3 || tid < 128) {
        const int t = tid + NTHR * i;
        tile[(t & 1) * 640 + tile_perm(t >> 1)] = make_uint4(~v[i].x, ~v[i].y, ~v[i].z, ~v[i].w);
      }
    }
  }
  __syncthreads();
  STAMP(5);

  const int g = lane >> 2, tq = lane & 3;
  const int hh = wid & 1, gqi = wid >> 1;
  const int row = hh * 8 + g;
  uint32_t hreg[16], hnreg[16];
  if (wid < 10) {
    float cs[4][4];
#pragma unroll
    for (int k = 0; k < 4; k++) {
      cs[k][0] = cs[k][1] = cs[k][2] = cs[k][3] = 0.f;
      const int base = 32 * (4 * gqi + k);
      const int lch = base + 8 * ((lane & 7) >> 1) + 2 * (lane >> 3) + (lane & 1);
      uint32_t y[4];
      asm volatile("ldmatrix.sync.aligned.m8n8.x4.trans.shared.b16 {%0,%1,%2,%3}, [%4];"
                   : "=r"(y[0]), "=r"(y[1]), "=r"(y[2]), "=r"(y[3]) : "r"(smem_u32(&tile[hh * 640 + tile_perm(lch)])) : "memory");
      const uint4 qv4 = *reinterpret_cast<const uint4*>(&sm.q[row][base + 8 * tq]);
      const uint4 qn4 = *reinterpret_cast<const uint4*>(qn_s + row * QSTR + base + 8 * tq);
      hreg[4 * k + 0] = b2u(__hadd2_rn(u2b(qv4.x), __hmul2_rn(u2b(qn4.x), u2b(y[0]))));
      hreg[4 * k + 1] = b2u(__hadd2_rn(u2b(qv4.y), __hmul2_rn(u2b(qn4.y), u2b(y[1]))));
      hreg[4 * k + 2] = b2u(__hadd2_rn(u2b(qv4.z), __hmul2_rn(u2b(qn4.z), u2b(y[2]))));
      hreg[4 * k + 3] = b2u(__hadd2_rn(u2b(qv4.w), __hmul2_rn(u2b(qn4.w), u2b(y[3]))));
      mma_bf16x(cs[k], hreg[4 * k + 0], hreg[4 * k + 2], hreg[4 * k + 1], hreg[4 * k + 3], 0x3F803F80u, 0x3F803F80u);
    }
    const float mean = (((cs[0][0] + cs[0][2]) + (cs[1][0] + cs[1][2])) + ((cs[2][0] + cs[2][2]) + (cs[3][0] + cs[3][2]))) * (1.f / 128.f);
    float m2a = 0.f, m2b = 0.f, m2c = 0.f, m2d = 0.f;
#pragma unroll
    for (int i = 0; i < 16; i += 2) {
      const float a = lo_f(hreg[i]) - mean, b = hi_f(hreg[i]) - mean, c = lo_f(hreg[i + 1]) - mean, d = hi_f(hreg[i + 1]) - mean;
      m2a = fmaf(a, a, m2a); m2b = fmaf(b, b, m2b); m2c = fmaf(c, c, m2c); m2d = fmaf(d, d, m2d);
    }
    float m2 = (m2a + m2b) + (m2c + m2d);
    m2 += __shfl_xor_sync(0xffffffffu, m2, 1);
    m2 += __shfl_xor_sync(0xffffffffu, m2, 2);
    if (tq == 0) sm.st[row][gqi] = make_float2(mean, m2);
  }
  STAMP(13);
  __syncthreads();
  if (wid < 10) {
    float mean = 0.f, m2 = 0.f;
    float2 p[5];
#pragma unroll
    for (int i = 0; i < 5; i++) { p[i] = sm.st[row][i]; mean += p[i].x; }
    mean *= 0.2f;
#pragma unroll
    for (int i = 0; i < 5; i++) { const float dl = p[i].x - mean; m2 += p[i].y + 128.f * dl * dl; }
    const float hd = rbf(sqrtf(rbf(rbf(m2 * (1.f / D_)) + 1e-5f)));
    const float hr = 1.f / hd;
    const bf162 hm2 = __float2bfloat162_rn(mean);
    float cr[4][4];
#pragma unroll
    for (int k = 0; k < 4; k++) {
      cr[k][0] = cr[k][1] = cr[k][2] = cr[k][3] = 0.f;
      const uint4 w4 = sm.wr[4 * (4 * gqi + k) + tq];
      uint32_t o[4];
#pragma unroll
      for (int i = 0; i < 4; i++) {
        const uint32_t d = b2u(__hsub2_rn(u2b(hreg[4 * k + i]), hm2));
        hnreg[4 * k + i] = pack2(fdivr(lo_f(d), hd, hr), fdivr(hi_f(d), hd, hr));
        o[i] = b2u(__hadd2_rn(u2b(hreg[4 * k + i]), u2b(hnreg[4 * k + i])));
      }
      mma_bf16(cr[k], hnreg[4 * k + 0], hnreg[4 * k + 1], w4.x, w4.y);
      mma_bf16(cr[k], hnreg[4 * k + 2], hnreg[4 * k + 3], w4.z, w4.w);
      *reinterpret_cast<uint4*>(gout + (size_t)(cta * 16 + row) * D_ + (4 * (4 * gqi + k) + tq) * 8) = make_uint4(o[0], o[1], o[2], o[3]);
    }
    if (tq == 0) sm.rp[row][gqi] = (cr[0][0] + cr[1][0]) + (cr[2][0] + cr[3][0]);
  }
  STAMP(14);
  __syncthreads();
  uint32_t best;
  {
    const int rr = lane & 15;
    const float r = ((sm.rp[rr][0] + sm.rp[rr][1]) + (sm.rp[rr][2] + sm.rp[rr][3])) + sm.rp[rr][4];
    const uint32_t bits = __bfloat16_as_ushort(__float2bfloat16_rn(r));
    const uint32_t ord = (bits & 0x8000u) ? (bits ^ 0xFFFFu) : (bits ^ 0x8000u);
    const uint32_t key = (ord << 16) | 0x8000u | (uint32_t)(2047 - (cta * 16 + rr));
    best = __reduce_max_sync(0xffffffffu, key);
  }
  if (tid == 352) asm volatile("st.relaxed.gpu.global.u32 [%0], %1;" ::"l"(&g_keys[cta]), "r"(best) : "memory");
  STAMP(15);
  const int brow = (2047 - (int)(best & 0x7FFu)) - cta * 16;
  if (wid < 10 && row == brow) {
#pragma unroll
    for (int k = 0; k < 4; k++)
      st_pub4(&g_cand[cta][0][4 * (4 * gqi + k) + tq], enc4(make_uint4(hnreg[4 * k], hnreg[4 * k + 1], hnreg[4 * k + 2], hnreg[4 * k + 3])));
  }
  STAMP(6);
  if (wid == 11) {
    const uint4* kp = reinterpret_cast<const uint4*>(g_keys) + lane;
    uint4 v = ld_poll4(kp);
    int it = 0;
    while (!ready4(v) && ++it < SPIN_LIMIT) v = ld_poll4(kp);
    const uint32_t m = max(max(v.x, v.y), max(v.z, v.w));
    const uint32_t wk = __reduce_max_sync(0xffffffffu, m);
    if (lane == 0) sm.win = wk;
  }
  __syncthreads();
  const uint32_t win = sm.win;
  const int wrow = 2047 - (int)(win & 0x7FFu);
  const int wcta = wrow >> 4;
  if (wcta == cta && wid < 10 && row == brow) {
    __threadfence();
#pragma unroll
    for (int k = 0; k < 4; k++)
      st_pub4(&g_cand[cta][1][4 * (4 * gqi + k) + tq], enc4(make_uint4(hreg[4 * k], hreg[4 * k + 1], hreg[4 * k + 2], hreg[4 * k + 3])));
  }
  STAMP(7);
  if (cta < N1 + N2) mbar_wait(&sm.mbarw);
  float* xs = &sm.z[0][0][0];
  float* part = xs + 2048;
  if (cta < N1) {
    if (tid < 80) {
      const uint4 v = poll4(&g_cand[wcta][0][tid]);
      float4* xp = reinterpret_cast<float4*>(xs + tid * 8);
      xp[0] = make_float4(lo_f(v.x), hi_f(v.x), lo_f(v.y), hi_f(v.y));
      xp[1] = make_float4(lo_f(v.z), hi_f(v.z), lo_f(v.w), hi_f(v.w));
    }
    __syncthreads();
    const int m = wid / 6, hc = (wid % 6) >> 1, rs = (wid & 1) * 32 + lane;
    float a[8];
#pragma unroll
    for (int j = 0; j < 8; j++) a[j] = 0.f;
#pragma unroll
    for (int it = 0; it < 10; it++) {
      const int r = rs + 64 * it;
      const uint4 wv = sm.w[m * 1920 + r * 3 + hc];
      const float x = xs[r];
      a[0] = fmaf(x, lo_f(wv.x), a[0]); a[1] = fmaf(x, hi_f(wv.x), a[1]);
      a[2] = fmaf(x, lo_f(wv.y), a[2]); a[3] = fmaf(x, hi_f(wv.y), a[3]);
      a[4] = fmaf(x, lo_f(wv.z), a[4]); a[5] = fmaf(x, hi_f(wv.z), a[5]);
      a[6] = fmaf(x, lo_f(wv.w), a[6]); a[7] = fmaf(x, hi_f(wv.w), a[7]);
    }
    {
      const bool up = lane & 16;
#pragma unroll
      for (int j = 0; j < 4; j++) {
        const float send = up ? a[j] : a[j + 4], keep = up ? a[j + 4] : a[j];
        a[j] = keep + __shfl_xor_sync(0xffffffffu, send, 16);
      }
      const bool up2 = lane & 8;
#pragma unroll
      for (int j = 0; j < 2; j++) {
        const float send = up2 ? a[j] : a[j + 2], keep = up2 ? a[j + 2] : a[j];
        a[j] = keep + __shfl_xor_sync(0xffffffffu, send, 8);
      }
      const bool up3 = lane & 4;
      const float send = up3 ? a[0] : a[1], keep = up3 ? a[1] : a[0];
      a[0] = keep + __shfl_xor_sync(0xffffffffu, send, 4);
      a[0] += __shfl_xor_sync(0xffffffffu, a[0], 2);
      a[0] += __shfl_xor_sync(0xffffffffu, a[0], 1);
      if ((lane & 3) == 0) part[wid * 8 + (lane >> 2)] = a[0];
    }
    __syncthreads();
    if (wid == 0) {
      uint32_t bits = 0;
      if (lane < 24) {
        const int hc2 = lane >> 3, j = lane & 7;
        const float gt = rbf(part[(2 * hc2) * 8 + j] + part[(2 * hc2 + 1) * 8 + j]);
        const float up = rbf(part[(6 + 2 * hc2) * 8 + j] + part[(6 + 2 * hc2 + 1) * 8 + j]);
        const float sg = rbf(gt / (1.f + __expf(-gt)));
        bits = __bfloat16_as_ushort(__float2bfloat16_rn(sg * up));
      }
      const uint32_t nb = __shfl_down_sync(0xffffffffu, bits, 1);
      const uint32_t pw = bits | (nb << 16);
      const uint32_t w1 = __shfl_down_sync(0xffffffffu, pw, 2), w2 = __shfl_down_sync(0xffffffffu, pw, 4), w3 = __shfl_down_sync(0xffffffffu, pw, 6);
      if (lane < 24 && (lane & 7) == 0) st_pub4(&g_act[cta * 3 + (lane >> 3)], enc4(make_uint4(pw, w1, w2, w3)));
    }
  } else if (cta < N1 + N2) {
    const int j2 = cta - N1;
    uint4 rowv = make_uint4(0, 0, 0, 0);
    if (tid < 192) {
      const uint4 v = poll4(&g_act[tid]);
      float4* xp = reinterpret_cast<float4*>(xs + tid * 8);
      xp[0] = make_float4(lo_f(v.x), hi_f(v.x), lo_f(v.y), hi_f(v.y));
      xp[1] = make_float4(lo_f(v.z), hi_f(v.z), lo_f(v.w), hi_f(v.w));
    } else if (tid < 196) {
      const int t = tid - 192;
      rowv = poll4(&g_cand[wcta][t >> 1][j2 * 2 + (t & 1)]);
      __threadfence();
      reinterpret_cast<uint4*>(part + 256)[t] = rowv;
    }
    __syncthreads();
    const int hc = lane & 1, rs = wid * 16 + (lane >> 1);
    float a[8];
#pragma unroll
    for (int j = 0; j < 8; j++) a[j] = 0.f;
#pragma unroll
    for (int it = 0; it < 8; it++) {
      const int r = rs + 192 * it;
      const uint4 wv = sm.w[r * 2 + hc];
      const float x = xs[r];
      a[0] = fmaf(x, lo_f(wv.x), a[0]); a[1] = fmaf(x, hi_f(wv.x), a[1]);
      a[2] = fmaf(x, lo_f(wv.y), a[2]); a[3] = fmaf(x, hi_f(wv.y), a[3]);
      a[4] = fmaf(x, lo_f(wv.z), a[4]); a[5] = fmaf(x, hi_f(wv.z), a[5]);
      a[6] = fmaf(x, lo_f(wv.w), a[6]); a[7] = fmaf(x, hi_f(wv.w), a[7]);
    }
    {
      const bool up = lane & 16;
#pragma unroll
      for (int j = 0; j < 4; j++) {
        const float send = up ? a[j] : a[j + 4], keep = up ? a[j + 4] : a[j];
        a[j] = keep + __shfl_xor_sync(0xffffffffu, send, 16);
      }
      const bool up2 = lane & 8;
#pragma unroll
      for (int j = 0; j < 2; j++) {
        const float send = up2 ? a[j] : a[j + 2], keep = up2 ? a[j + 2] : a[j];
        a[j] = keep + __shfl_xor_sync(0xffffffffu, send, 8);
      }
      const bool up3 = lane & 4;
      const float send = up3 ? a[0] : a[1], keep = up3 ? a[1] : a[0];
      a[0] = keep + __shfl_xor_sync(0xffffffffu, send, 4);
      a[0] += __shfl_xor_sync(0xffffffffu, a[0], 2);
      if ((lane & 2) == 0) part[wid * 16 + hc * 8 + (lane >> 2)] = a[0];
    }
    __syncthreads();
    if (tid < 16) {
      float y = 0.f;
#pragma unroll
      for (int i = 0; i < 12; i++) y += part[i * 16 + tid];
      const uint32_t ord = win >> 16;
      const uint32_t rb = (ord & 0x8000u) ? (ord ^ 0x8000u) : (ord ^ 0xFFFFu);
      const float r = __uint_as_float(rb << 16);
      const float sg = rbf(1.f / (1.f + __expf(-r)));
      const float yy = rbf(rbf(y) * sg);
      const unsigned short* rv = reinterpret_cast<const unsigned short*>(part + 256);
      const float hn = __uint_as_float((uint32_t)rv[tid] << 16), h = __uint_as_float((uint32_t)rv[16 + tid] << 16);
      gout[(size_t)wrow * D_ + j2 * 16 + tid] = __float2bfloat16_rn(h + rbf(hn + yy));
    }
  }
  STAMP(8);
}

}

typedef CUresult (*EncodeFn)(CUtensorMap*, CUtensorMapDataType, cuuint32_t, void*, const cuuint64_t*, const cuuint64_t*,
                             const cuuint32_t*, const cuuint32_t*, CUtensorMapInterleave, CUtensorMapSwizzle,
                             CUtensorMapL2promotion, CUtensorMapFloatOOBfill);

extern "C" void kernel_launch(void* const* d_in, const int* in_sizes, int n_in, void* d_out, int out_size) {
  (void)in_sizes; (void)n_in; (void)out_size;
  static EncodeFn encode = nullptr;
  static CUtensorMap tmg, tmu, tmd;
  static void* cached[3] = {nullptr, nullptr, nullptr};
  if (!encode) {
    cudaFuncSetAttribute(fused_kernel, cudaFuncAttributeMaxDynamicSharedMemorySize, (int)sizeof(Smem));
    void* fn = nullptr;
    cudaDriverEntryPointQueryResult qr;
    cudaGetDriverEntryPoint("cuTensorMapEncodeTiled", &fn, cudaEnableDefault, &qr);
    encode = (EncodeFn)fn;
  }
  if (cached[0] != d_in[8] || cached[1] != d_in[9] || cached[2] != d_in[10]) {
    const cuuint32_t es[2] = {1, 1};
    {
      const cuuint64_t dims[2] = {F_, D_}, strides[1] = {F_ * 2};
      const cuuint32_t box[2] = {24, 160};
      encode(&tmg, CU_TENSOR_MAP_DATA_TYPE_BFLOAT16, 2, d_in[8], dims, strides, box, es, CU_TENSOR_MAP_INTERLEAVE_NONE,
             CU_TENSOR_MAP_SWIZZLE_NONE, CU_TENSOR_MAP_L2_PROMOTION_NONE, CU_TENSOR_MAP_FLOAT_OOB_FILL_NONE);
      encode(&tmu, CU_TENSOR_MAP_DATA_TYPE_BFLOAT16, 2, d_in[9], dims, strides, box, es, CU_TENSOR_MAP_INTERLEAVE_NONE,
             CU_TENSOR_MAP_SWIZZLE_NONE, CU_TENSOR_MAP_L2_PROMOTION_NONE, CU_TENSOR_MAP_FLOAT_OOB_FILL_NONE);
    }
    {
      const cuuint64_t dims[2] = {D_, F_}, strides[1] = {D_ * 2};
      const cuuint32_t box[2] = {16, 256};
      encode(&tmd, CU_TENSOR_MAP_DATA_TYPE_BFLOAT16, 2, d_in[10], dims, strides, box, es, CU_TENSOR_MAP_INTERLEAVE_NONE,
             CU_TENSOR_MAP_SWIZZLE_NONE, CU_TENSOR_MAP_L2_PROMOTION_NONE, CU_TENSOR_MAP_FLOAT_OOB_FILL_NONE);
    }
    cached[0] = d_in[8]; cached[1] = d_in[9]; cached[2] = d_in[10];
  }
  fused_kernel<<<NCTA, NTHR, sizeof(Smem), cudaStreamPerThread>>>(
      tmg, tmu, tmd, (const bf16*)d_in[0], (const bf16*)d_in[1], (const bf16*)d_in[2], (const bf16*)d_in[3],
      (const bf16*)d_in[4], (const bf16*)d_in[5], (const bf16*)d_in[7], (bf16*)d_out);
}
```

```cpp
#include <cuda_runtime.h>
#include <cuda_bf16.h>
#include <cuda.h>
#include <stdint.h>

namespace {

typedef __nv_bfloat16 bf16;
typedef __nv_bfloat162 bf162;

constexpr int S_ = 2048, D_ = 640, F_ = 1536;
constexpr int NCTA = 128, CPC = 5, NTHR = 384;
constexpr int UPAD = 136, USTR = 2192;
constexpr int TABW = 1040;
constexpr int ZPB = 132;
constexpr int QSTR = 648;
constexpr int N1 = 64;
constexpr int N2 = 40;
constexpr int SPIN_LIMIT = 1 << 19;
#define LN2_EXACT 1
#define ABL 0
#define POLL_NS 100
#define H_DELAY 0
#define Q_DELAY 4500

struct __align__(128) Smem {
  uint32_t tabA[3][2][TABW];
  uint32_t extra[1024];
  uint32_t tabB[2][2][TABW];
  bf16 u[CPC][USTR];
  float z[2][4][ZPB * 16];
  bf16 q[16][QSTR];
  alignas(128) uint4 w[3840];
  uint4 wr[80];
  float2 st[16][5];
  float2 stq[16][5];
  float rp[16][5];
  unsigned long long mbar;
  unsigned long long mbarw;
  unsigned long long mbarc;
  unsigned long long mbarh;
  uint32_t target;
  uint32_t best;
  uint32_t win;
};

__device__ uint4 g_kv[D_ * S_ / 8];
__device__ uint4 g_y2[D_ * S_ / 8];
__device__ uint32_t g_keys[NCTA];
__device__ uint4 g_cand[NCTA][2][80];
__device__ uint4 g_act[F_ / 8];
__device__ unsigned int g_ctr;
__device__ unsigned int g_ctr2;
#define STAMP(i)
#define CST(c, i)

__device__ __forceinline__ uint32_t smem_u32(const void* p) { return (uint32_t)__cvta_generic_to_shared(p); }
__device__ __forceinline__ void wg_fence() { asm volatile("wgmma.fence.sync.aligned;" ::: "memory"); }
__device__ __forceinline__ void wg_commit() { asm volatile("wgmma.commit_group.sync.aligned;" ::: "memory"); }
template <int N> __device__ __forceinline__ void wg_wait() { asm volatile("wgmma.wait_group.sync.aligned %0;" ::"n"(N) : "memory"); }
__device__ __forceinline__ void bar_sync(int id, int n) { asm volatile("bar.sync %0, %1;" ::"r"(id), "r"(n) : "memory"); }
__device__ __forceinline__ void bar_arrive(int id, int n) { asm volatile("bar.arrive %0, %1;" ::"r"(id), "r"(n) : "memory"); }
__device__ __forceinline__ bf162 u2b(uint32_t u) { return *reinterpret_cast<bf162*>(&u); }
__device__ __forceinline__ uint32_t b2u(bf162 b) { return *reinterpret_cast<uint32_t*>(&b); }
__device__ __forceinline__ float lo_f(uint32_t u) { return __uint_as_float(u << 16); }
__device__ __forceinline__ float hi_f(uint32_t u) { return __uint_as_float(u & 0xFFFF0000u); }
__device__ __forceinline__ float rbf(float x) { return __bfloat162float(__float2bfloat16_rn(x)); }
__device__ __forceinline__ uint32_t pack2(float a, float b) { return b2u(__floats2bfloat162_rn(a, b)); }
__device__ __forceinline__ uint32_t enc(uint32_t w) { return max(~w, 1u); }
__device__ __forceinline__ uint4 enc4(uint4 v) { return make_uint4(enc(v.x), enc(v.y), enc(v.z), enc(v.w)); }
__device__ __forceinline__ uint4 ld_poll4(const uint4* p) {
  uint4 v;
  asm volatile("ld.relaxed.gpu.global.v4.u32 {%0,%1,%2,%3}, [%4];" : "=r"(v.x), "=r"(v.y), "=r"(v.z), "=r"(v.w) : "l"(p) : "memory");
  return v;
}
__device__ __forceinline__ bool ready4(uint4 v) { return v.x != 0u && v.y != 0u && v.z != 0u && v.w != 0u; }
__device__ __forceinline__ uint4 poll4(const uint4* p) {
  uint4 v = ld_poll4(p);
  int it = 0;
  while (!ready4(v) && ++it < SPIN_LIMIT) v = ld_poll4(p);
  return make_uint4(~v.x, ~v.y, ~v.z, ~v.w);
}
__device__ __forceinline__ void st_pub4(uint4* p, uint4 v) {
  asm volatile("st.relaxed.gpu.global.v4.u32 [%0], {%1,%2,%3,%4};" ::"l"(p), "r"(v.x), "r"(v.y), "r"(v.z), "r"(v.w) : "memory");
}
__device__ __forceinline__ void st_pub2(uint2* p, uint32_t a, uint32_t b) {
  asm volatile("st.relaxed.gpu.global.v2.u32 [%0], {%1,%2};" ::"l"(p), "r"(a), "r"(b) : "memory");
}
__device__ __forceinline__ void mma_bf16(float (&c)[4], uint32_t a0, uint32_t a2, uint32_t b0, uint32_t b1) {
  asm volatile("mma.sync.aligned.m16n8k16.row.col.f32.bf16.bf16.f32 {%0,%1,%2,%3}, {%4,%5,%6,%5}, {%7,%8}, {%0,%1,%2,%3};"
               : "+f"(c[0]), "+f"(c[1]), "+f"(c[2]), "+f"(c[3]) : "r"(a0), "r"(0u), "r"(a2), "r"(b0), "r"(b1));
}
__device__ __forceinline__ void mbar_wait(const unsigned long long* bar) {
  const uint32_t mb = smem_u32(bar);
  uint32_t ok = 0;
  int it = 0;
  while (!ok && ++it < SPIN_LIMIT)
    asm volatile("{ .reg .pred p; mbarrier.try_wait.parity.shared.b64 p, [%1], 0; selp.u32 %0, 1, 0, p; }" : "=r"(ok) : "r"(mb) : "memory");
}
__device__ __forceinline__ void bulk_g2s(void* dst, const void* src, uint32_t bytes, const unsigned long long* bar) {
  asm volatile("cp.async.bulk.shared::cluster.global.mbarrier::complete_tx::bytes [%0], [%1], %2, [%3];" ::"r"(smem_u32(dst)),
               "l"(src), "r"(bytes), "r"(smem_u32(bar)) : "memory");
}
__device__ __forceinline__ void mbar_expect(const unsigned long long* bar, uint32_t bytes) {
  asm volatile("mbarrier.arrive.expect_tx.shared.b64 _, [%0], %1;" ::"r"(smem_u32(bar)), "r"(bytes) : "memory");
}
__device__ __forceinline__ void mma_bf16x(float (&c)[4], uint32_t a0, uint32_t a1, uint32_t a2, uint32_t a3, uint32_t b0, uint32_t b1) {
  asm volatile("mma.sync.aligned.m16n8k16.row.col.f32.bf16.bf16.f32 {%0,%1,%2,%3}, {%4,%5,%6,%7}, {%8,%9}, {%0,%1,%2,%3};"
               : "+f"(c[0]), "+f"(c[1]), "+f"(c[2]), "+f"(c[3]) : "r"(a0), "r"(a1), "r"(a2), "r"(a3), "r"(b0), "r"(b1));
}
__device__ __forceinline__ float fdivr(float a, float d, float r) {
  float q = a * r;
  float e = fmaf(-q, d, a);
  return fmaf(e, r, q);
}

template <bool FIRST> __device__ __forceinline__ void wgmma32(float (&d)[16], const uint32_t* a, uint64_t desc) {
  if (FIRST) {
    asm volatile("wgmma.mma_async.sync.aligned.m64n32k16.f32.bf16.bf16 {%0,%1,%2,%3,%4,%5,%6,%7,%8,%9,%10,%11,%12,%13,%14,%15}, {%16,%17,%18,%19}, %20, 0, 1, 1, 0;"
                 : "+f"(d[0]), "+f"(d[1]), "+f"(d[2]), "+f"(d[3]), "+f"(d[4]), "+f"(d[5]), "+f"(d[6]), "+f"(d[7]),
                   "+f"(d[8]), "+f"(d[9]), "+f"(d[10]), "+f"(d[11]), "+f"(d[12]), "+f"(d[13]), "+f"(d[14]), "+f"(d[15])
                 : "r"(a[0]), "r"(a[1]), "r"(a[2]), "r"(a[3]), "l"(desc));
  } else {
    asm volatile("wgmma.mma_async.sync.aligned.m64n32k16.f32.bf16.bf16 {%0,%1,%2,%3,%4,%5,%6,%7,%8,%9,%10,%11,%12,%13,%14,%15}, {%16,%17,%18,%19}, %20, 1, 1, 1, 0;"
                 : "+f"(d[0]), "+f"(d[1]), "+f"(d[2]), "+f"(d[3]), "+f"(d[4]), "+f"(d[5]), "+f"(d[6]), "+f"(d[7]),
                   "+f"(d[8]), "+f"(d[9]), "+f"(d[10]), "+f"(d[11]), "+f"(d[12]), "+f"(d[13]), "+f"(d[14]), "+f"(d[15])
                 : "r"(a[0]), "r"(a[1]), "r"(a[2]), "r"(a[3]), "l"(desc));
  }
}

template <int G> __device__ __forceinline__ void load_a(uint32_t (&a)[8], const uint32_t* tp) {
#pragma unroll
  for (int q = 0; q < 2; q++) {
    const int e = 2 * G + q;
    a[4 * q + 0] = tp[-64 * e];
    a[4 * q + 1] = tp[-64 * e - 32];
    a[4 * q + 2] = tp[-64 * e + 4];
    a[4 * q + 3] = tp[-64 * e - 28];
  }
}
__device__ __forceinline__ void load_a_all(uint32_t (&a)[8][8], const uint32_t* tp) {
  load_a<0>(a[0], tp); load_a<1>(a[1], tp); load_a<2>(a[2], tp); load_a<3>(a[3], tp);
  load_a<4>(a[4], tp); load_a<5>(a[5], tp); load_a<6>(a[6], tp); load_a<7>(a[7], tp);
}
template <int G> __device__ __forceinline__ void issue_g(float (&acc)[8][16], uint32_t (&a)[8], uint64_t desc0) {
  wg_fence();
#pragma unroll
  for (int q = 0; q < 2; q++) {
#pragma unroll
    for (int b = G; b < 8; b++) {
      const int delta = 2 * b - (2 * G + q);
      if (G == 0 && q == 0) wgmma32<true>(acc[b], &a[4 * q], desc0 + (uint64_t)(int64_t)(16 * delta));
      else wgmma32<false>(acc[b], &a[4 * q], desc0 + (uint64_t)(int64_t)(16 * delta));
    }
  }
  wg_commit();
}
template <int B> __device__ __forceinline__ void fence_blk(float (&acc)[8][16]) {
#pragma unroll
  for (int i = 0; i < 16; i++) asm volatile("" : "+f"(acc[B][i])::"memory");
}
__device__ __forceinline__ void fence_a(uint32_t (&a)[8]) {
#pragma unroll
  for (int i = 0; i < 8; i++) asm volatile("" : "+r"(a[i])::"memory");
}
template <int B> __device__ __forceinline__ void sts_blk(float (&acc)[8][16], float* zw, int off_even, int off_odd) {
#pragma unroll
  for (int jj = 0; jj < 4; jj++) {
    const int j = 4 * B + jj;
    float p0 = acc[B][4 * jj + 0], p1 = acc[B][4 * jj + 1];
    if (jj > 0) { p0 += acc[B][4 * (jj - 1) + 2]; p1 += acc[B][4 * (jj - 1) + 3]; }
    else if (B > 0) { p0 += acc[B > 0 ? B - 1 : 0][14]; p1 += acc[B > 0 ? B - 1 : 0][15]; }
    zw[64 * j + off_even] = p0;
    zw[64 * j + off_odd] = p1;
  }
}
__device__ __forceinline__ int tab_off(int c) { return c == 4 ? 0 : (c + 1) * 2 * TABW + (c >= 2 ? 1024 : 0); }
__device__ __forceinline__ int tile_perm(int ch) { return ch ^ (((ch >> 3) & 3) << 1); }

__device__ __forceinline__ void wait_ctr(const unsigned int* ctr, uint32_t target) {
  uint32_t v;
  int it = 0;
  do {
    asm volatile("ld.acquire.gpu.global.u32 %0, [%1];" : "=r"(v) : "l"(ctr) : "memory");
  } while ((int)(v - target) < 0 && ++it < SPIN_LIMIT);
}

__device__ __forceinline__ float2 row_part_stats(const uint32_t (&x)[16]) {
  float cs[4][4];
#pragma unroll
  for (int k = 0; k < 4; k++) {
    cs[k][0] = cs[k][1] = cs[k][2] = cs[k][3] = 0.f;
    mma_bf16x(cs[k], x[4 * k + 0], x[4 * k + 2], x[4 * k + 1], x[4 * k + 3], 0x3F803F80u, 0x3F803F80u);
  }
  const float mean = (((cs[0][0] + cs[0][2]) + (cs[1][0] + cs[1][2])) + ((cs[2][0] + cs[2][2]) + (cs[3][0] + cs[3][2]))) * (1.f / 128.f);
  float m2a = 0.f, m2b = 0.f, m2c = 0.f, m2d = 0.f;
#pragma unroll
  for (int i = 0; i < 16; i += 2) {
    const float a = lo_f(x[i]) - mean, b = hi_f(x[i]) - mean, c = lo_f(x[i + 1]) - mean, d = hi_f(x[i + 1]) - mean;
    m2a = fmaf(a, a, m2a); m2b = fmaf(b, b, m2b); m2c = fmaf(c, c, m2c); m2d = fmaf(d, d, m2d);
  }
  float m2 = (m2a + m2b) + (m2c + m2d);
  m2 += __shfl_xor_sync(0xffffffffu, m2, 1);
  m2 += __shfl_xor_sync(0xffffffffu, m2, 2);
  return make_float2(mean, m2);
}
__device__ __forceinline__ void row_normalize(const float2* st, const uint32_t (&x)[16], uint32_t (&y)[16]) {
  float mean = 0.f, m2 = 0.f;
  float2 p[5];
#pragma unroll
  for (int i = 0; i < 5; i++) { p[i] = st[i]; mean += p[i].x; }
  mean *= 0.2f;
#pragma unroll
  for (int i = 0; i < 5; i++) { const float dl = p[i].x - mean; m2 += p[i].y + 128.f * dl * dl; }
  const float hd = rbf(sqrtf(rbf(rbf(m2 * (1.f / D_)) + 1e-5f)));
  const float hr = 1.f / hd;
  const bf162 hm2 = __float2bfloat162_rn(mean);
#pragma unroll
  for (int i = 0; i < 16; i++) {
    const uint32_t d = b2u(__hsub2_rn(u2b(x[i]), hm2));
    y[i] = pack2(fdivr(lo_f(d), hd, hr), fdivr(hi_f(d), hd, hr));
  }
}

__global__ void __launch_bounds__(NTHR, 1)
fused_kernel(const __grid_constant__ CUtensorMap tmg, const __grid_constant__ CUtensorMap tmu,
             const __grid_constant__ CUtensorMap tmd, const bf16* __restrict__ gq, const bf16* __restrict__ gk, const bf16* __restrict__ gv,
             const bf16* __restrict__ gsk, const bf16* __restrict__ gh, const bf16* __restrict__ gD,
             const bf16* __restrict__ gwr, bf16* __restrict__ gout) {
  extern __shared__ __align__(128) unsigned char smraw[];
  Smem& sm = *reinterpret_cast<Smem*>(smraw);
  const int tid = threadIdx.x;
  const int cta = blockIdx.x;
  const int c0 = cta * CPC;
  const int lane = tid & 31;
  const int wid = tid >> 5;
  STAMP(0);
  const long long tstart = clock64();

  {
    uint4* hs = reinterpret_cast<uint4*>(&sm.z[0][0][0]);
    const int oc = tid >> 2;
    const int r0 = cta * 16 + (tid & 3) * 4;
    uint4 kk[7], vv[4], sk[4];
    if (tid < 320) {
      const uint4* kp = reinterpret_cast<const uint4*>(gk) + (size_t)r0 * 80 + oc;
      const uint4* vp = reinterpret_cast<const uint4*>(gv) + (size_t)r0 * 80 + oc;
#pragma unroll
      for (int i = 0; i < 7; i++) kk[i] = (i >= 3 || r0 > 0) ? __ldg(kp + (i - 3) * 80) : make_uint4(0, 0, 0, 0);
#pragma unroll
      for (int i = 0; i < 4; i++) vv[i] = __ldg(vp + i * 80);
#pragma unroll
      for (int i = 0; i < 4; i++) sk[i] = __ldg(reinterpret_cast<const uint4*>(gsk) + oc * 4 + i);
    } else if (tid == 320) {
      asm volatile("mbarrier.init.shared.b64 [%0], 1;" ::"r"(smem_u32(&sm.mbarh)) : "memory");
      asm volatile("mbarrier.init.shared.b64 [%0], 1;" ::"r"(smem_u32(&sm.mbar)) : "memory");
      asm volatile("mbarrier.init.shared.b64 [%0], 1;" ::"r"(smem_u32(&sm.mbarw)) : "memory");
      asm volatile("mbarrier.init.shared.b64 [%0], 1;" ::"r"(smem_u32(&sm.mbarc)) : "memory");
      asm volatile("fence.proxy.async.shared::cta;" ::: "memory");
    }
    if (tid < 320) bar_sync(6, 384); else { bar_arrive(6, 384); bar_sync(5, 64); }
    STAMP(9);
    if (tid < 320) {
      uint32_t o[4][4];
#pragma unroll
      for (int p = 0; p < 4; p++) {
        const bf162 w0 = u2b(__byte_perm(sk[p].x, sk[p].z, 0x5410)), w1 = u2b(__byte_perm(sk[p].x, sk[p].z, 0x7632));
        const bf162 w2 = u2b(__byte_perm(sk[p].y, sk[p].w, 0x5410)), w3 = u2b(__byte_perm(sk[p].y, sk[p].w, 0x7632));
        uint32_t kv[4];
#pragma unroll
        for (int i = 0; i < 4; i++) {
          const uint32_t k0 = p == 0 ? kk[i].x : p == 1 ? kk[i].y : p == 2 ? kk[i].z : kk[i].w;
          const uint32_t k1 = p == 0 ? kk[i + 1].x : p == 1 ? kk[i + 1].y : p == 2 ? kk[i + 1].z : kk[i + 1].w;
          const uint32_t k2 = p == 0 ? kk[i + 2].x : p == 1 ? kk[i + 2].y : p == 2 ? kk[i + 2].z : kk[i + 2].w;
          const uint32_t k3 = p == 0 ? kk[i + 3].x : p == 1 ? kk[i + 3].y : p == 2 ? kk[i + 3].z : kk[i + 3].w;
          const uint32_t vx = p == 0 ? vv[i].x : p == 1 ? vv[i].y : p == 2 ? vv[i].z : vv[i].w;
          bf162 a = __hmul2_rn(u2b(k0), w3);
          a = __hadd2_rn(a, __hmul2_rn(u2b(k1), w2));
          a = __hadd2_rn(a, __hmul2_rn(u2b(k2), w1));
          a = __hadd2_rn(a, __hmul2_rn(u2b(k3), w0));
          kv[i] = b2u(__hmul2_rn(a, u2b(vx)));
        }
        o[p][0] = enc(__byte_perm(kv[0], kv[1], 0x5410)); o[p][1] = enc(__byte_perm(kv[2], kv[3], 0x5410));
        o[p][2] = enc(__byte_perm(kv[0], kv[1], 0x7632)); o[p][3] = enc(__byte_perm(kv[2], kv[3], 0x7632));
      }
      uint2* dst = reinterpret_cast<uint2*>(g_kv) + (size_t)(oc * 8) * 512 + (r0 >> 2);
#pragma unroll
      for (int p = 0; p < 4; p++) {
        st_pub2(dst + (2 * p) * 512, o[p][0], o[p][1]);
        st_pub2(dst + (2 * p + 1) * 512, o[p][2], o[p][3]);
      }
      STAMP(10);
      if (wid == 0) bar_sync(4, 320); else bar_arrive(4, 320);
      if (tid == 0) {
        const unsigned old = atomicAdd(&g_ctr2, 1u);
        const unsigned target = (old / NCTA + 1u) * NCTA;
        uint32_t v;
        int it = 0;
        do {
          asm volatile("ld.relaxed.gpu.global.u32 %0, [%1];" : "=r"(v) : "l"(&g_ctr2) : "memory");
        } while ((int)(v - target) < 0 && ++it < SPIN_LIMIT);
        asm volatile("mbarrier.arrive.shared.b64 _, [%0];" ::"r"(smem_u32(&sm.mbarc)) : "memory");
      }
      __syncwarp();
    } else {
      const int t0 = tid - 320;
      const uint4 zz = make_uint4(0, 0, 0, 0);
      if (tid == 320) {
        while (clock64() - tstart < H_DELAY) {}
        mbar_expect(&sm.mbarh, CPC * S_ * 2);
        bulk_g2s(hs, gh + (size_t)c0 * S_, CPC * S_ * 2, &sm.mbarh);
      }
      __syncwarp();
      for (int t = t0; t < CPC * 17; t += 64) *reinterpret_cast<uint4*>(&sm.u[t / 17][(t % 17) * 8]) = zz;
      if (t0 < 40) *reinterpret_cast<uint4*>(&sm.tabA[0][0][0] + tab_off(t0 >> 3) + ((t0 >> 2) & 1) * TABW + 1024 + 4 * (t0 & 3)) = zz;
#pragma unroll 4
      for (int i = 0; i < 20; i++) g_y2[cta * 1280 + t0 + 64 * i] = zz;
      (&g_cand[cta][0][0])[t0] = zz;
      (&g_cand[cta][0][0])[64 + t0] = zz;
      if (t0 < 32) (&g_cand[cta][0][0])[128 + t0] = zz;
      else if (t0 < 35) { if (cta < N1) g_act[cta * 3 + (t0 - 32)] = zz; }
      else if (t0 == 35) g_keys[cta] = 0u;
      bar_sync(5, 64);
      if (tid == 352) {
        __threadfence();
        const unsigned old = atomicAdd(&g_ctr, 1u);
        sm.target = (old / NCTA + 1u) * NCTA;
      }
      __syncwarp();
    }
    mbar_wait(&sm.mbarh);
#pragma unroll
    for (int i = 0; i < 4; i++) {
      const int t = (NTHR - 1 - tid) + NTHR * i;
      if (t < CPC * 256) {
        uint32_t* tb = &sm.tabA[0][0][0] + tab_off(t >> 8) + (255 - (t & 255)) * 4;
        const uint4 h = hs[t];
        const uint32_t hp = (t & 255) ? reinterpret_cast<const uint32_t*>(hs)[4 * t - 1] : 0u;
        uint4 r1, rr;
        r1.x = __byte_perm(h.w, 0, 0x1032); r1.y = __byte_perm(h.z, 0, 0x1032);
        r1.z = __byte_perm(h.y, 0, 0x1032); r1.w = __byte_perm(h.x, 0, 0x1032);
        rr.x = __byte_perm(h.w, h.z, 0x7610); rr.y = __byte_perm(h.z, h.y, 0x7610);
        rr.z = __byte_perm(h.y, h.x, 0x7610); rr.w = __byte_perm(h.x, hp, 0x7610);
        *reinterpret_cast<uint4*>(tb) = rr;
        *reinterpret_cast<uint4*>(tb + TABW) = r1;
      }
    }
    STAMP(12);
  }
  mbar_wait(&sm.mbarc);
  {
    uint4 v[4];
    uint4* src = g_kv + c0 * 256 + tid;
#pragma unroll
    for (int i = 0; i < 4; i++) if (i < 3 || tid < 128) v[i] = ld_poll4(src + NTHR * i);
#pragma unroll
    for (int i = 0; i < 4; i++) {
      if (i < 3 || tid < 128) {
        int it = 0;
        while (!ready4(v[i]) && ++it < SPIN_LIMIT) { __nanosleep(POLL_NS); v[i] = ld_poll4(src + NTHR * i); }
        const int t = tid + NTHR * i;
        *reinterpret_cast<uint4*>(&sm.u[t >> 8][UPAD + (t & 255) * 8]) = make_uint4(~v[i].x, ~v[i].y, ~v[i].z, ~v[i].w);
      }
    }
    STAMP(11);
    asm volatile("fence.proxy.async.shared::cta;" ::: "memory");
    __syncthreads();
#pragma unroll
    for (int i = 0; i < 4; i++) if (i < 3 || tid < 128) src[NTHR * i] = make_uint4(0, 0, 0, 0);
    if (tid >= 256) {
      const int t0 = tid - 256;
      if (((t0 & 15) >> 2) < ((t0 >> 4) & 3))
        *reinterpret_cast<uint4*>(&sm.z[t0 >> 6][(t0 >> 4) & 3][(t0 & 15) * 4]) = make_uint4(0, 0, 0, 0);
    }
  }
  STAMP(1);
  if (ABL == 5) return;

  const int wg = __shfl_sync(0xffffffffu, tid >> 7, 0);
  const int wtid = tid & 127;
  uint4* tile = reinterpret_cast<uint4*>(&sm.tabB[0][0][0]);
  if (wg < 2) {
    asm volatile("setmaxnreg.inc.sync.aligned.u32 224;");
    const int w = (tid >> 5) & 3, g = lane >> 2, tq = lane & 3;
    float* zw = sm.z[wg][w];
    const int sw = 3 * (((tq + w) >> 1) & 1);
    const int off_even = 16 * (tq + w) + 4 * ((0 + (g >> 2)) ^ sw) + (g & 3);
    const int off_odd = 16 * (tq + w) + 4 * ((2 + (g >> 2)) ^ sw) + (g & 3);
    uint32_t a[8][8];
    const uint32_t* tp0 = &sm.tabA[0][g & 1][1019 - 8 * w - (g >> 1) + tq];
    load_a_all(a, tp0 + tab_off(wg));
    float acc[8][16];
#pragma unroll
    for (int b = 0; b < 8; b++)
#pragma unroll
      for (int i = 0; i < 16; i++) acc[b][i] = 0.f;
#pragma unroll 1
    for (int c = wg; c < CPC; c += 2) {
      const uint64_t desc = (uint64_t)((smem_u32(&sm.u[c][UPAD - 8]) & 0x3FFFF) >> 4) | ((uint64_t)1 << 16) | ((uint64_t)8 << 32);
      CST(c, 0);
      if (c > 0) bar_sync(1 + wg, 256);
      issue_g<0>(acc, a[0], desc);
      CST(c, 1);
      issue_g<1>(acc, a[1], desc);
      issue_g<2>(acc, a[2], desc);
      issue_g<3>(acc, a[3], desc);
      issue_g<4>(acc, a[4], desc);
      issue_g<5>(acc, a[5], desc);
      if (c + 1 < CPC) bar_arrive(1 + (wg ^ 1), 256);
      issue_g<6>(acc, a[6], desc);
      issue_g<7>(acc, a[7], desc);
      CST(c, 2);
      if (c >= 2) bar_sync(5 + wg, 256);
      wg_wait<4>();
      fence_blk<0>(acc); fence_blk<1>(acc); fence_blk<2>(acc); fence_blk<3>(acc);
      sts_blk<0>(acc, zw, off_even, off_odd);
      sts_blk<1>(acc, zw, off_even, off_odd);
      sts_blk<2>(acc, zw, off_even, off_odd);
      sts_blk<3>(acc, zw, off_even, off_odd);
      CST(c, 3);
      wg_wait<0>();
      fence_blk<4>(acc); fence_blk<5>(acc); fence_blk<6>(acc); fence_blk<7>(acc);
#pragma unroll
      for (int i = 0; i < 8; i++) fence_a(a[i]);
      sts_blk<4>(acc, zw, off_even, off_odd);
      sts_blk<5>(acc, zw, off_even, off_odd);
      sts_blk<6>(acc, zw, off_even, off_odd);
      sts_blk<7>(acc, zw, off_even, off_odd);
      bar_arrive(3 + wg, 256);
      CST(c, 4);
      if (c + 2 < CPC) load_a_all(a, tp0 + tab_off(c + 2));
    }
    STAMP(2 + wg);
    asm volatile("setmaxnreg.dec.sync.aligned.u32 168;");
  } else {
    asm volatile("setmaxnreg.dec.sync.aligned.u32 56;");
    if (wtid == 32) {
      const uint32_t mw = smem_u32(&sm.mbarw);
      mbar_expect(&sm.mbar, 17 * D_ * 2);
#pragma unroll 1
      for (int r = 0; r < 16; r++) bulk_g2s(&sm.q[r][0], gq + (size_t)(cta * 16 + r) * D_, D_ * 2, &sm.mbar);
      bulk_g2s(&sm.wr[0], gwr, D_ * 2, &sm.mbar);
      if (cta < N1) {
        asm volatile("mbarrier.arrive.expect_tx.shared.b64 _, [%0], %1;" ::"r"(mw), "r"(3840 * 16) : "memory");
#pragma unroll 1
        for (int i = 0; i < 4; i++) {
          asm volatile("cp.async.bulk.tensor.2d.shared::cluster.global.mbarrier::complete_tx::bytes [%0], [%1, {%3, %4}], [%2];" ::"r"(smem_u32(&sm.w[i * 480])),
                       "l"(&tmg), "r"(mw), "r"(cta * 24), "r"(i * 160) : "memory");
          asm volatile("cp.async.bulk.tensor.2d.shared::cluster.global.mbarrier::complete_tx::bytes [%0], [%1, {%3, %4}], [%2];" ::"r"(smem_u32(&sm.w[1920 + i * 480])),
                       "l"(&tmu), "r"(mw), "r"(cta * 24), "r"(i * 160) : "memory");
        }
      } else if (cta < N1 + N2) {
        asm volatile("mbarrier.arrive.expect_tx.shared.b64 _, [%0], %1;" ::"r"(mw), "r"(3072 * 16) : "memory");
#pragma unroll 1
        for (int i = 0; i < 6; i++)
          asm volatile("cp.async.bulk.tensor.2d.shared::cluster.global.mbarrier::complete_tx::bytes [%0], [%1, {%3, %4}], [%2];" ::"r"(smem_u32(&sm.w[i * 512])),
                       "l"(&tmd), "r"(mw), "r"((cta - N1) * 16), "r"(i * 256) : "memory");
      }
    }
    if (wtid == 0) wait_ctr(&g_ctr, sm.target);
    const int rpb = wtid >> 1, re2 = wtid & 1;
    const int rsw = 3 * ((rpb >> 1) & 1);
    const int roff0 = 16 * rpb + 4 * ((2 * re2 + 0) ^ rsw);
    const int roff1 = 16 * rpb + 4 * ((2 * re2 + 1) ^ rsw);
    const uint32_t dvl = reinterpret_cast<const unsigned short*>(gD)[c0 + (lane < CPC ? lane : 0)];
#pragma unroll 1
    for (int c = 0; c < CPC; c++) {
      const int zg = c & 1;
      const uint32_t dvc = __shfl_sync(0xffffffffu, dvl, c);
      const bf162 d2 = u2b(dvc | (dvc << 16));
      CST(c, 5);
      bar_sync(3 + zg, 256);
#pragma unroll
      for (int half = 0; half < 2; half++) {
        const float* zb = sm.z[zg][0] + half * 1024;
        float4 x[4][2];
#pragma unroll
        for (int ww = 0; ww < 4; ww++) {
          x[ww][0] = *reinterpret_cast<const float4*>(zb + ww * ZPB * 16 + roff0);
          x[ww][1] = *reinterpret_cast<const float4*>(zb + ww * ZPB * 16 + roff1);
        }
        const int sidx = half * 1024 + wtid * 8;
        const uint4 kvv = *reinterpret_cast<const uint4*>(&sm.u[c][UPAD + sidx]);
        if (half == 1 && c + 2 < CPC) bar_arrive(5 + zg, 256);
        uint4 o;
        o.x = pack2((x[0][0].x + x[1][0].x) + (x[2][0].x + x[3][0].x), (x[0][0].y + x[1][0].y) + (x[2][0].y + x[3][0].y));
        o.y = pack2((x[0][0].z + x[1][0].z) + (x[2][0].z + x[3][0].z), (x[0][0].w + x[1][0].w) + (x[2][0].w + x[3][0].w));
        o.z = pack2((x[0][1].x + x[1][1].x) + (x[2][1].x + x[3][1].x), (x[0][1].y + x[1][1].y) + (x[2][1].y + x[3][1].y));
        o.w = pack2((x[0][1].z + x[1][1].z) + (x[2][1].z + x[3][1].z), (x[0][1].w + x[1][1].w) + (x[2][1].w + x[3][1].w));
        o.x = b2u(__hadd2_rn(u2b(o.x), __hmul2_rn(u2b(kvv.x), d2)));
        o.y = b2u(__hadd2_rn(u2b(o.y), __hmul2_rn(u2b(kvv.y), d2)));
        o.z = b2u(__hadd2_rn(u2b(o.z), __hmul2_rn(u2b(kvv.z), d2)));
        o.w = b2u(__hadd2_rn(u2b(o.w), __hmul2_rn(u2b(kvv.w), d2)));
        st_pub4(g_y2 + ((64 * half + rpb) * 640 + c0 + c) * 2 + re2, enc4(o));
        CST(c, 6 + half);
      }
    }
    STAMP(4);
    asm volatile("setmaxnreg.inc.sync.aligned.u32 168;");
  }

  if (ABL == 4) { if (cta < N1 + N2) mbar_wait(&sm.mbarw); mbar_wait(&sm.mbar); return; }
  const int g = lane >> 2, tq = lane & 3;
  const int hh = wid & 1, gqi = wid >> 1;
  const int row = hh * 8 + g;
  uint32_t hreg[16], hnreg[16];
  {
    const uint4* src = g_y2 + cta * 1280 + tid;
    uint4 v[4];
#pragma unroll
    for (int i = 0; i < 4; i++) if (i < 3 || tid < 128) v[i] = ld_poll4(src + NTHR * i);
    if (wid < 10) {
      mbar_wait(&sm.mbar);
#pragma unroll
      for (int k = 0; k < 4; k++) {
        const uint4 qv4 = *reinterpret_cast<const uint4*>(&sm.q[row][32 * (4 * gqi + k) + 8 * tq]);
        hreg[4 * k] = qv4.x; hreg[4 * k + 1] = qv4.y; hreg[4 * k + 2] = qv4.z; hreg[4 * k + 3] = qv4.w;
      }
      const float2 ps = row_part_stats(hreg);
      if (tq == 0) sm.stq[row][gqi] = ps;
      bar_sync(7, 320);
      row_normalize(sm.stq[row], hreg, hnreg);
    }
    int it = 0;
    bool all;
    do {
      all = true;
#pragma unroll
      for (int i = 0; i < 4; i++)
        if ((i < 3 || tid < 128) && !ready4(v[i])) { v[i] = ld_poll4(src + NTHR * i); all = false; }
    } while (!all && ++it < SPIN_LIMIT);
#pragma unroll
    for (int i = 0; i < 4; i++) {
      if (i < 3 || tid < 128) {
        const int t = tid + NTHR * i;
        tile[(t & 1) * 640 + tile_perm(t >> 1)] = make_uint4(~v[i].x, ~v[i].y, ~v[i].z, ~v[i].w);
      }
    }
  }
  __syncthreads();
  STAMP(5);
  if (ABL == 3) { if (cta < N1 + N2) mbar_wait(&sm.mbarw); return; }

  if (wid < 10) {
#pragma unroll
    for (int k = 0; k < 4; k++) {
      const int base = 32 * (4 * gqi + k);
      const int lch = base + 8 * ((lane & 7) >> 1) + 2 * (lane >> 3) + (lane & 1);
      uint32_t y[4];
      asm volatile("ldmatrix.sync.aligned.m8n8.x4.trans.shared.b16 {%0,%1,%2,%3}, [%4];"
                   : "=r"(y[0]), "=r"(y[1]), "=r"(y[2]), "=r"(y[3]) : "r"(smem_u32(&tile[hh * 640 + tile_perm(lch)])) : "memory");
#pragma unroll
      for (int i = 0; i < 4; i++)
        hreg[4 * k + i] = b2u(__hadd2_rn(u2b(hreg[4 * k + i]), __hmul2_rn(u2b(hnreg[4 * k + i]), u2b(y[i]))));
    }
    const float2 ps = row_part_stats(hreg);
    if (tq == 0) sm.st[row][gqi] = ps;
    STAMP(13);
    bar_sync(7, 320);
    row_normalize(sm.st[row], hreg, hnreg);
    float cr[4][4];
#pragma unroll
    for (int k = 0; k < 4; k++) {
      cr[k][0] = cr[k][1] = cr[k][2] = cr[k][3] = 0.f;
      const uint4 w4 = sm.wr[4 * (4 * gqi + k) + tq];
      uint32_t o[4];
#pragma unroll
      for (int i = 0; i < 4; i++) o[i] = b2u(__hadd2_rn(u2b(hreg[4 * k + i]), u2b(hnreg[4 * k + i])));
      mma_bf16(cr[k], hnreg[4 * k + 0], hnreg[4 * k + 1], w4.x, w4.y);
      mma_bf16(cr[k], hnreg[4 * k + 2], hnreg[4 * k + 3], w4.z, w4.w);
      *reinterpret_cast<uint4*>(gout + (size_t)(cta * 16 + row) * D_ + (4 * (4 * gqi + k) + tq) * 8) = make_uint4(o[0], o[1], o[2], o[3]);
    }
    if (tq == 0) sm.rp[row][gqi] = (cr[0][0] + cr[1][0]) + (cr[2][0] + cr[3][0]);
  }
  STAMP(14);
  __syncthreads();
  uint32_t best;
  {
    const int rr = lane & 15;
    const float r = ((sm.rp[rr][0] + sm.rp[rr][1]) + (sm.rp[rr][2] + sm.rp[rr][3])) + sm.rp[rr][4];
    const uint32_t bits = __bfloat16_as_ushort(__float2bfloat16_rn(r));
    const uint32_t ord = (bits & 0x8000u) ? (bits ^ 0xFFFFu) : (bits ^ 0x8000u);
    const uint32_t key = (ord << 16) | 0x8000u | (uint32_t)(2047 - (cta * 16 + rr));
    best = __reduce_max_sync(0xffffffffu, key);
  }
  if (tid == 352) asm volatile("st.relaxed.gpu.global.u32 [%0], %1;" ::"l"(&g_keys[cta]), "r"(best) : "memory");
  STAMP(15);
  const int brow = (2047 - (int)(best & 0x7FFu)) - cta * 16;
  if (wid < 10 && row == brow) {
#pragma unroll
    for (int k = 0; k < 4; k++)
      st_pub4(&g_cand[cta][0][4 * (4 * gqi + k) + tq], enc4(make_uint4(hnreg[4 * k], hnreg[4 * k + 1], hnreg[4 * k + 2], hnreg[4 * k + 3])));
  }
  STAMP(6);
  if (ABL == 2) { if (cta < N1 + N2) mbar_wait(&sm.mbarw); return; }
  if (wid == 11) {
    const uint4* kp = reinterpret_cast<const uint4*>(g_keys) + lane;
    uint4 v = ld_poll4(kp);
    int it = 0;
    while (!ready4(v) && ++it < SPIN_LIMIT) v = ld_poll4(kp);
    const uint32_t m = max(max(v.x, v.y), max(v.z, v.w));
    const uint32_t wk = __reduce_max_sync(0xffffffffu, m);
    if (lane == 0) sm.win = wk;
  }
  __syncthreads();
  const uint32_t win = sm.win;
  const int wrow = 2047 - (int)(win & 0x7FFu);
  const int wcta = wrow >> 4;
  if (wcta == cta && wid < 10 && row == brow) {
    __threadfence();
#pragma unroll
    for (int k = 0; k < 4; k++)
      st_pub4(&g_cand[cta][1][4 * (4 * gqi + k) + tq], enc4(make_uint4(hreg[4 * k], hreg[4 * k + 1], hreg[4 * k + 2], hreg[4 * k + 3])));
  }
  STAMP(7);
  if (ABL == 1) { if (cta < N1 + N2) mbar_wait(&sm.mbarw); return; }
  if (cta < N1 + N2) mbar_wait(&sm.mbarw);
  float* xs = &sm.z[0][0][0];
  float* part = xs + 2048;
  if (cta < N1) {
    if (tid < 80) {
      const uint4 v = poll4(&g_cand[wcta][0][tid]);
      float4* xp = reinterpret_cast<float4*>(xs + tid * 8);
      xp[0] = make_float4(lo_f(v.x), hi_f(v.x), lo_f(v.y), hi_f(v.y));
      xp[1] = make_float4(lo_f(v.z), hi_f(v.z), lo_f(v.w), hi_f(v.w));
    }
    __syncthreads();
    const int m = wid / 6, hc = (wid % 6) >> 1, rs = (wid & 1) * 32 + lane;
    float a[8];
#pragma unroll
    for (int j = 0; j < 8; j++) a[j] = 0.f;
#pragma unroll
    for (int it = 0; it < 10; it++) {
      const int r = rs + 64 * it;
      const uint4 wv = sm.w[m * 1920 + r * 3 + hc];
      const float x = xs[r];
      a[0] = fmaf(x, lo_f(wv.x), a[0]); a[1] = fmaf(x, hi_f(wv.x), a[1]);
      a[2] = fmaf(x, lo_f(wv.y), a[2]); a[3] = fmaf(x, hi_f(wv.y), a[3]);
      a[4] = fmaf(x, lo_f(wv.z), a[4]); a[5] = fmaf(x, hi_f(wv.z), a[5]);
      a[6] = fmaf(x, lo_f(wv.w), a[6]); a[7] = fmaf(x, hi_f(wv.w), a[7]);
    }
    {
      const bool up = lane & 16;
#pragma unroll
      for (int j = 0; j < 4; j++) {
        const float send = up ? a[j] : a[j + 4], keep = up ? a[j + 4] : a[j];
        a[j] = keep + __shfl_xor_sync(0xffffffffu, send, 16);
      }
      const bool up2 = lane & 8;
#pragma unroll
      for (int j = 0; j < 2; j++) {
        const float send = up2 ? a[j] : a[j + 2], keep = up2 ? a[j + 2] : a[j];
        a[j] = keep + __shfl_xor_sync(0xffffffffu, send, 8);
      }
      const bool up3 = lane & 4;
      const float send = up3 ? a[0] : a[1], keep = up3 ? a[1] : a[0];
      a[0] = keep + __shfl_xor_sync(0xffffffffu, send, 4);
      a[0] += __shfl_xor_sync(0xffffffffu, a[0], 2);
      a[0] += __shfl_xor_sync(0xffffffffu, a[0], 1);
      if ((lane & 3) == 0) part[wid * 8 + (lane >> 2)] = a[0];
    }
    __syncthreads();
    if (wid == 0) {
      uint32_t bits = 0;
      if (lane < 24) {
        const int hc2 = lane >> 3, j = lane & 7;
        const float gt = rbf(part[(2 * hc2) * 8 + j] + part[(2 * hc2 + 1) * 8 + j]);
        const float up = rbf(part[(6 + 2 * hc2) * 8 + j] + part[(6 + 2 * hc2 + 1) * 8 + j]);
        const float sg = rbf(gt / (1.f + __expf(-gt)));
        bits = __bfloat16_as_ushort(__float2bfloat16_rn(sg * up));
      }
      const uint32_t nb = __shfl_down_sync(0xffffffffu, bits, 1);
      const uint32_t pw = bits | (nb << 16);
      const uint32_t w1 = __shfl_down_sync(0xffffffffu, pw, 2), w2 = __shfl_down_sync(0xffffffffu, pw, 4), w3 = __shfl_down_sync(0xffffffffu, pw, 6);
      if (lane < 24 && (lane & 7) == 0) st_pub4(&g_act[cta * 3 + (lane >> 3)], enc4(make_uint4(pw, w1, w2, w3)));
    }
  } else if (cta < N1 + N2) {
    const int j2 = cta - N1;
    uint4 rowv = make_uint4(0, 0, 0, 0);
    if (tid < 192) {
      const uint4 v = poll4(&g_act[tid]);
      float4* xp = reinterpret_cast<float4*>(xs + tid * 8);
      xp[0] = make_float4(lo_f(v.x), hi_f(v.x), lo_f(v.y), hi_f(v.y));
      xp[1] = make_float4(lo_f(v.z), hi_f(v.z), lo_f(v.w), hi_f(v.w));
    } else if (tid < 196) {
      const int t = tid - 192;
      rowv = poll4(&g_cand[wcta][t >> 1][j2 * 2 + (t & 1)]);
      __threadfence();
      reinterpret_cast<uint4*>(part + 256)[t] = rowv;
    }
    __syncthreads();
    const int hc = lane & 1, rs = wid * 16 + (lane >> 1);
    float a[8];
#pragma unroll
    for (int j = 0; j < 8; j++) a[j] = 0.f;
#pragma unroll
    for (int it = 0; it < 8; it++) {
      const int r = rs + 192 * it;
      const uint4 wv = sm.w[r * 2 + hc];
      const float x = xs[r];
      a[0] = fmaf(x, lo_f(wv.x), a[0]); a[1] = fmaf(x, hi_f(wv.x), a[1]);
      a[2] = fmaf(x, lo_f(wv.y), a[2]); a[3] = fmaf(x, hi_f(wv.y), a[3]);
      a[4] = fmaf(x, lo_f(wv.z), a[4]); a[5] = fmaf(x, hi_f(wv.z), a[5]);
      a[6] = fmaf(x, lo_f(wv.w), a[6]); a[7] = fmaf(x, hi_f(wv.w), a[7]);
    }
    {
      const bool up = lane & 16;
#pragma unroll
      for (int j = 0; j < 4; j++) {
        const float send = up ? a[j] : a[j + 4], keep = up ? a[j + 4] : a[j];
        a[j] = keep + __shfl_xor_sync(0xffffffffu, send, 16);
      }
      const bool up2 = lane & 8;
#pragma unroll
      for (int j = 0; j < 2; j++) {
        const float send = up2 ? a[j] : a[j + 2], keep = up2 ? a[j + 2] : a[j];
        a[j] = keep + __shfl_xor_sync(0xffffffffu, send, 8);
      }
      const bool up3 = lane & 4;
      const float send = up3 ? a[0] : a[1], keep = up3 ? a[1] : a[0];
      a[0] = keep + __shfl_xor_sync(0xffffffffu, send, 4);
      a[0] += __shfl_xor_sync(0xffffffffu, a[0], 2);
      if ((lane & 2) == 0) part[wid * 16 + hc * 8 + (lane >> 2)] = a[0];
    }
    __syncthreads();
    if (tid < 16) {
      float y = 0.f;
#pragma unroll
      for (int i = 0; i < 12; i++) y += part[i * 16 + tid];
      const uint32_t ord = win >> 16;
      const uint32_t rb = (ord & 0x8000u) ? (ord ^ 0x8000u) : (ord ^ 0xFFFFu);
      const float r = __uint_as_float(rb << 16);
      const float sg = rbf(1.f / (1.f + __expf(-r)));
      const float yy = rbf(rbf(y) * sg);
      const unsigned short* rv = reinterpret_cast<const unsigned short*>(part + 256);
      const float hn = __uint_as_float((uint32_t)rv[tid] << 16), h = __uint_as_float((uint32_t)rv[16 + tid] << 16);
      gout[(size_t)wrow * D_ + j2 * 16 + tid] = __float2bfloat16_rn(h + rbf(hn + yy));
    }
  }
  STAMP(8);
}

}

typedef CUresult (*EncodeFn)(CUtensorMap*, CUtensorMapDataType, cuuint32_t, void*, const cuuint64_t*, const cuuint64_t*,
                             const cuuint32_t*, const cuuint32_t*, CUtensorMapInterleave, CUtensorMapSwizzle,
                             CUtensorMapL2promotion, CUtensorMapFloatOOBfill);

extern "C" void kernel_launch(void* const* d_in, const int* in_sizes, int n_in, void* d_out, int out_size) {
  (void)in_sizes; (void)n_in; (void)out_size;
  static EncodeFn encode = nullptr;
  static CUtensorMap tmg, tmu, tmd;
  static void* cached[3] = {nullptr, nullptr, nullptr};
  if (!encode) {
    cudaFuncSetAttribute(fused_kernel, cudaFuncAttributeMaxDynamicSharedMemorySize, (int)sizeof(Smem));
    void* fn = nullptr;
    cudaDriverEntryPointQueryResult qr;
    cudaGetDriverEntryPoint("cuTensorMapEncodeTiled", &fn, cudaEnableDefault, &qr);
    encode = (EncodeFn)fn;
  }
  if (cached[0] != d_in[8] || cached[1] != d_in[9] || cached[2] != d_in[10]) {
    const cuuint32_t es[2] = {1, 1};
    {
      const cuuint64_t dims[2] = {F_, D_}, strides[1] = {F_ * 2};
      const cuuint32_t box[2] = {24, 160};
      encode(&tmg, CU_TENSOR_MAP_DATA_TYPE_BFLOAT16, 2, d_in[8], dims, strides, box, es, CU_TENSOR_MAP_INTERLEAVE_NONE,
             CU_TENSOR_MAP_SWIZZLE_NONE, CU_TENSOR_MAP_L2_PROMOTION_NONE, CU_TENSOR_MAP_FLOAT_OOB_FILL_NONE);
      encode(&tmu, CU_TENSOR_MAP_DATA_TYPE_BFLOAT16, 2, d_in[9], dims, strides, box, es, CU_TENSOR_MAP_INTERLEAVE_NONE,
             CU_TENSOR_MAP_SWIZZLE_NONE, CU_TENSOR_MAP_L2_PROMOTION_NONE, CU_TENSOR_MAP_FLOAT_OOB_FILL_NONE);
    }
    {
      const cuuint64_t dims[2] = {D_, F_}, strides[1] = {D_ * 2};
      const cuuint32_t box[2] = {16, 256};
      encode(&tmd, CU_TENSOR_MAP_DATA_TYPE_BFLOAT16, 2, d_in[10], dims, strides, box, es, CU_TENSOR_MAP_INTERLEAVE_NONE,
             CU_TENSOR_MAP_SWIZZLE_NONE, CU_TENSOR_MAP_L2_PROMOTION_NONE, CU_TENSOR_MAP_FLOAT_OOB_FILL_NONE);
    }
    cached[0] = d_in[8]; cached[1] = d_in[9]; cached[2] = d_in[10];
  }
  fused_kernel<<<NCTA, NTHR, sizeof(Smem), cudaStreamPerThread>>>(
      tmg, tmu, tmd, (const bf16*)d_in[0], (const bf16*)d_in[1], (const bf16*)d_in[2], (const bf16*)d_in[3],
      (const bf16*)d_in[4], (const bf16*)d_in[5], (const bf16*)d_in[7], (bf16*)d_out);
}
```

```cpp
#include <cuda_runtime.h>
#include <cuda_bf16.h>
#include <cuda.h>
#include <stdint.h>

namespace {

typedef __nv_bfloat16 bf16;
typedef __nv_bfloat162 bf162;

constexpr int S_ = 2048, D_ = 640, F_ = 1536;
constexpr int NCTA = 128, CPC = 5, NTHR = 384;
constexpr int UPAD = 136, USTR = 2192;
constexpr int TABW = 1040;
constexpr int ZPB = 132;
constexpr int QSTR = 648;
constexpr int N1 = 64;
constexpr int N2 = 40;
constexpr int SPIN_LIMIT = 1 << 19;
#define LN2_EXACT 1
#define ABL 0
#define POLL_NS 100
#define H_DELAY 0
#define Q_DELAY 4500

struct __align__(128) Smem {
  uint32_t tabA[3][2][TABW];
  uint32_t extra[1024];
  uint32_t tabB[2][2][TABW];
  bf16 u[CPC][USTR];
  float z[2][4][ZPB * 16];
  bf16 q[16][QSTR];
  alignas(128) uint4 w[3840];
  uint4 wr[80];
  float2 st[16][5];
  float2 stq[16][5];
  float rp[16][5];
  unsigned long long mbar;
  unsigned long long mbarw;
  unsigned long long mbarc;
  unsigned long long mbarh;
  uint32_t target;
  uint32_t best;
  uint32_t win;
};

__device__ uint4 g_kv[D_ * S_ / 8];
__device__ uint4 g_y2[D_ * S_ / 8];
__device__ uint32_t g_keys[NCTA];
__device__ uint4 g_cand[NCTA][2][80];
__device__ uint4 g_act[F_ / 8];
__device__ unsigned int g_ctr;
__device__ unsigned int g_ctr2;
#define STAMP(i)
#define CST(c, i)

__device__ __forceinline__ uint32_t smem_u32(const void* p) { return (uint32_t)__cvta_generic_to_shared(p); }
__device__ __forceinline__ void wg_fence() { asm volatile("wgmma.fence.sync.aligned;" ::: "memory"); }
__device__ __forceinline__ void wg_commit() { asm volatile("wgmma.commit_group.sync.aligned;" ::: "memory"); }
template <int N> __device__ __forceinline__ void wg_wait() { asm volatile("wgmma.wait_group.sync.aligned %0;" ::"n"(N) : "memory"); }
__device__ __forceinline__ void bar_sync(int id, int n) { asm volatile("bar.sync %0, %1;" ::"r"(id), "r"(n) : "memory"); }
__device__ __forceinline__ void bar_arrive(int id, int n) { asm volatile("bar.arrive %0, %1;" ::"r"(id), "r"(n) : "memory"); }
__device__ __forceinline__ bf162 u2b(uint32_t u) { return *reinterpret_cast<bf162*>(&u); }
__device__ __forceinline__ uint32_t b2u(bf162 b) { return *reinterpret_cast<uint32_t*>(&b); }
__device__ __forceinline__ float lo_f(uint32_t u) { return __uint_as_float(u << 16); }
__device__ __forceinline__ float hi_f(uint32_t u) { return __uint_as_float(u & 0xFFFF0000u); }
__device__ __forceinline__ float rbf(float x) { return __bfloat162float(__float2bfloat16_rn(x)); }
__device__ __forceinline__ uint32_t pack2(float a, float b) { return b2u(__floats2bfloat162_rn(a, b)); }
__device__ __forceinline__ uint32_t enc(uint32_t w) { return max(~w, 1u); }
__device__ __forceinline__ uint4 enc4(uint4 v) { return make_uint4(enc(v.x), enc(v.y), enc(v.z), enc(v.w)); }
__device__ __forceinline__ uint4 ld_poll4(const uint4* p) {
  uint4 v;
  asm volatile("ld.relaxed.gpu.global.v4.u32 {%0,%1,%2,%3}, [%4];" : "=r"(v.x), "=r"(v.y), "=r"(v.z), "=r"(v.w) : "l"(p) : "memory");
  return v;
}
__device__ __forceinline__ bool ready4(uint4 v) { return v.x != 0u && v.y != 0u && v.z != 0u && v.w != 0u; }
__device__ __forceinline__ uint4 poll4(const uint4* p) {
  uint4 v = ld_poll4(p);
  int it = 0;
  while (!ready4(v) && ++it < SPIN_LIMIT) v = ld_poll4(p);
  return make_uint4(~v.x, ~v.y, ~v.z, ~v.w);
}
__device__ __forceinline__ void st_pub4(uint4* p, uint4 v) {
  asm volatile("st.relaxed.gpu.global.v4.u32 [%0], {%1,%2,%3,%4};" ::"l"(p), "r"(v.x), "r"(v.y), "r"(v.z), "r"(v.w) : "memory");
}
__device__ __forceinline__ void st_pub2(uint2* p, uint32_t a, uint32_t b) {
  asm volatile("st.relaxed.gpu.global.v2.u32 [%0], {%1,%2};" ::"l"(p), "r"(a), "r"(b) : "memory");
}
__device__ __forceinline__ void mma_bf16(float (&c)[4], uint32_t a0, uint32_t a2, uint32_t b0, uint32_t b1) {
  asm volatile("mma.sync.aligned.m16n8k16.row.col.f32.bf16.bf16.f32 {%0,%1,%2,%3}, {%4,%5,%6,%5}, {%7,%8}, {%0,%1,%2,%3};"
               : "+f"(c[0]), "+f"(c[1]), "+f"(c[2]), "+f"(c[3]) : "r"(a0), "r"(0u), "r"(a2), "r"(b0), "r"(b1));
}
__device__ __forceinline__ void mbar_wait(const unsigned long long* bar) {
  const uint32_t mb = smem_u32(bar);
  uint32_t ok = 0;
  int it = 0;
  while (!ok && ++it < SPIN_LIMIT)
    asm volatile("{ .reg .pred p; mbarrier.try_wait.parity.shared.b64 p, [%1], 0; selp.u32 %0, 1, 0, p; }" : "=r"(ok) : "r"(mb) : "memory");
}
__device__ __forceinline__ void bulk_g2s(void* dst, const void* src, uint32_t bytes, const unsigned long long* bar) {
  asm volatile("cp.async.bulk.shared::cluster.global.mbarrier::complete_tx::bytes [%0], [%1], %2, [%3];" ::"r"(smem_u32(dst)),
               "l"(src), "r"(bytes), "r"(smem_u32(bar)) : "memory");
}
__device__ __forceinline__ void mbar_expect(const unsigned long long* bar, uint32_t bytes) {
  asm volatile("mbarrier.arrive.expect_tx.shared.b64 _, [%0], %1;" ::"r"(smem_u32(bar)), "r"(bytes) : "memory");
}
__device__ __forceinline__ void mma_bf16x(float (&c)[4], uint32_t a0, uint32_t a1, uint32_t a2, uint32_t a3, uint32_t b0, uint32_t b1) {
  asm volatile("mma.sync.aligned.m16n8k16.row.col.f32.bf16.bf16.f32 {%0,%1,%2,%3}, {%4,%5,%6,%7}, {%8,%9}, {%0,%1,%2,%3};"
               : "+f"(c[0]), "+f"(c[1]), "+f"(c[2]), "+f"(c[3]) : "r"(a0), "r"(a1), "r"(a2), "r"(a3), "r"(b0), "r"(b1));
}
__device__ __forceinline__ float fdivr(float a, float d, float r) {
  float q = a * r;
  float e = fmaf(-q, d, a);
  return fmaf(e, r, q);
}

template <bool FIRST> __device__ __forceinline__ void wgmma32(float (&d)[16], const uint32_t* a, uint64_t desc) {
  if (FIRST) {
    asm volatile("wgmma.mma_async.sync.aligned.m64n32k16.f32.bf16.bf16 {%0,%1,%2,%3,%4,%5,%6,%7,%8,%9,%10,%11,%12,%13,%14,%15}, {%16,%17,%18,%19}, %20, 0, 1, 1, 0;"
                 : "+f"(d[0]), "+f"(d[1]), "+f"(d[2]), "+f"(d[3]), "+f"(d[4]), "+f"(d[5]), "+f"(d[6]), "+f"(d[7]),
                   "+f"(d[8]), "+f"(d[9]), "+f"(d[10]), "+f"(d[11]), "+f"(d[12]), "+f"(d[13]), "+f"(d[14]), "+f"(d[15])
                 : "r"(a[0]), "r"(a[1]), "r"(a[2]), "r"(a[3]), "l"(desc));
  } else {
    asm volatile("wgmma.mma_async.sync.aligned.m64n32k16.f32.bf16.bf16 {%0,%1,%2,%3,%4,%5,%6,%7,%8,%9,%10,%11,%12,%13,%14,%15}, {%16,%17,%18,%19}, %20, 1, 1, 1, 0;"
                 : "+f"(d[0]), "+f"(d[1]), "+f"(d[2]), "+f"(d[3]), "+f"(d[4]), "+f"(d[5]), "+f"(d[6]), "+f"(d[7]),
                   "+f"(d[8]), "+f"(d[9]), "+f"(d[10]), "+f"(d[11]), "+f"(d[12]), "+f"(d[13]), "+f"(d[14]), "+f"(d[15])
                 : "r"(a[0]), "r"(a[1]), "r"(a[2]), "r"(a[3]), "l"(desc));
  }
}

template <int G> __device__ __forceinline__ void load_a(uint32_t (&a)[8], const uint32_t* tp) {
#pragma unroll
  for (int q = 0; q < 2; q++) {
    const int e = 2 * G + q;
    a[4 * q + 0] = tp[-64 * e];
    a[4 * q + 1] = tp[-64 * e - 32];
    a[4 * q + 2] = tp[-64 * e + 4];
    a[4 * q + 3] = tp[-64 * e - 28];
  }
}
__device__ __forceinline__ void load_a_all(uint32_t (&a)[8][8], const uint32_t* tp) {
  load_a<0>(a[0], tp); load_a<1>(a[1], tp); load_a<2>(a[2], tp); load_a<3>(a[3], tp);
  load_a<4>(a[4], tp); load_a<5>(a[5], tp); load_a<6>(a[6], tp); load_a<7>(a[7], tp);
}
template <int G> __device__ __forceinline__ void issue_g(float (&acc)[8][16], uint32_t (&a)[8], uint64_t desc0) {
  wg_fence();
#pragma unroll
  for (int q = 0; q < 2; q++) {
#pragma unroll
    for (int b = G; b < 8; b++) {
      const int delta = 2 * b - (2 * G + q);
      if (G == 0 && q == 0) wgmma32<true>(acc[b], &a[4 * q], desc0 + (uint64_t)(int64_t)(16 * delta));
      else wgmma32<false>(acc[b], &a[4 * q], desc0 + (uint64_t)(int64_t)(16 * delta));
    }
  }
  wg_commit();
}
template <int B> __device__ __forceinline__ void fence_blk(float (&acc)[8][16]) {
#pragma unroll
  for (int i = 0; i < 16; i++) asm volatile("" : "+f"(acc[B][i])::"memory");
}
__device__ __forceinline__ void fence_a(uint32_t (&a)[8]) {
#pragma unroll
  for (int i = 0; i < 8; i++) asm volatile("" : "+r"(a[i])::"memory");
}
template <int B> __device__ __forceinline__ void sts_blk(float (&acc)[8][16], float* zw, int off_even, int off_odd) {
#pragma unroll
  for (int jj = 0; jj < 4; jj++) {
    const int j = 4 * B + jj;
    float p0 = acc[B][4 * jj + 0], p1 = acc[B][4 * jj + 1];
    if (jj > 0) { p0 += acc[B][4 * (jj - 1) + 2]; p1 += acc[B][4 * (jj - 1) + 3]; }
    else if (B > 0) { p0 += acc[B > 0 ? B - 1 : 0][14]; p1 += acc[B > 0 ? B - 1 : 0][15]; }
    zw[64 * j + off_even] = p0;
    zw[64 * j + off_odd] = p1;
  }
}
__device__ __forceinline__ int tab_off(int c) { return c == 4 ? 0 : (c + 1) * 2 * TABW + (c >= 2 ? 1024 : 0); }
__device__ __forceinline__ int tile_perm(int ch) { return ch ^ (((ch >> 3) & 3) << 1); }

__device__ __forceinline__ void wait_ctr(const unsigned int* ctr, uint32_t target) {
  uint32_t v;
  int it = 0;
  do {
    asm volatile("ld.acquire.gpu.global.u32 %0, [%1];" : "=r"(v) : "l"(ctr) : "memory");
  } while ((int)(v - target) < 0 && ++it < SPIN_LIMIT);
}

__device__ __forceinline__ float2 row_part_stats(const uint32_t (&x)[16]) {
  float cs[4][4];
#pragma unroll
  for (int k = 0; k < 4; k++) {
    cs[k][0] = cs[k][1] = cs[k][2] = cs[k][3] = 0.f;
    mma_bf16x(cs[k], x[4 * k + 0], x[4 * k + 2], x[4 * k + 1], x[4 * k + 3], 0x3F803F80u, 0x3F803F80u);
  }
  const float mean = (((cs[0][0] + cs[0][2]) + (cs[1][0] + cs[1][2])) + ((cs[2][0] + cs[2][2]) + (cs[3][0] + cs[3][2]))) * (1.f / 128.f);
  float m2a = 0.f, m2b = 0.f, m2c = 0.f, m2d = 0.f;
#pragma unroll
  for (int i = 0; i < 16; i += 2) {
    const float a = lo_f(x[i]) - mean, b = hi_f(x[i]) - mean, c = lo_f(x[i + 1]) - mean, d = hi_f(x[i + 1]) - mean;
    m2a = fmaf(a, a, m2a); m2b = fmaf(b, b, m2b); m2c = fmaf(c, c, m2c); m2d = fmaf(d, d, m2d);
  }
  float m2 = (m2a + m2b) + (m2c + m2d);
  m2 += __shfl_xor_sync(0xffffffffu, m2, 1);
  m2 += __shfl_xor_sync(0xffffffffu, m2, 2);
  return make_float2(mean, m2);
}
__device__ __forceinline__ void row_normalize(const float2* st, const uint32_t (&x)[16], uint32_t (&y)[16]) {
  float mean = 0.f, m2 = 0.f;
  float2 p[5];
#pragma unroll
  for (int i = 0; i < 5; i++) { p[i] = st[i]; mean += p[i].x; }
  mean *= 0.2f;
#pragma unroll
  for (int i = 0; i < 5; i++) { const float dl = p[i].x - mean; m2 += p[i].y + 128.f * dl * dl; }
  const float hd = rbf(sqrtf(rbf(rbf(m2 * (1.f / D_)) + 1e-5f)));
  const float hr = 1.f / hd;
  const bf162 hm2 = __float2bfloat162_rn(mean);
#pragma unroll
  for (int i = 0; i < 16; i++) {
    const uint32_t d = b2u(__hsub2_rn(u2b(x[i]), hm2));
    y[i] = pack2(fdivr(lo_f(d), hd, hr), fdivr(hi_f(d), hd, hr));
  }
}

__global__ void __launch_bounds__(NTHR, 1)
fused_kernel(const __grid_constant__ CUtensorMap tmg, const __grid_constant__ CUtensorMap tmu,
             const __grid_constant__ CUtensorMap tmd, const bf16* __restrict__ gq, const bf16* __restrict__ gk, const bf16* __restrict__ gv,
             const bf16* __restrict__ gsk, const bf16* __restrict__ gh, const bf16* __restrict__ gD,
             const bf16* __restrict__ gwr, bf16* __restrict__ gout) {
  extern __shared__ __align__(128) unsigned char smraw[];
  Smem& sm = *reinterpret_cast<Smem*>(smraw);
  const int tid = threadIdx.x;
  const int cta = blockIdx.x;
  const int c0 = cta * CPC;
  const int lane = tid & 31;
  const int wid = tid >> 5;
  STAMP(0);
  const long long tstart = clock64();

  {
    uint4* hs = reinterpret_cast<uint4*>(&sm.z[0][0][0]);
    const int oc = tid >> 2;
    const int r0 = cta * 16 + (tid & 3) * 4;
    uint4 kk[7], vv[4], sk[4];
    if (tid < 320) {
      const uint4* kp = reinterpret_cast<const uint4*>(gk) + (size_t)r0 * 80 + oc;
      const uint4* vp = reinterpret_cast<const uint4*>(gv) + (size_t)r0 * 80 + oc;
#pragma unroll
      for (int i = 0; i < 7; i++) kk[i] = (i >= 3 || r0 > 0) ? __ldg(kp + (i - 3) * 80) : make_uint4(0, 0, 0, 0);
#pragma unroll
      for (int i = 0; i < 4; i++) vv[i] = __ldg(vp + i * 80);
#pragma unroll
      for (int i = 0; i < 4; i++) sk[i] = __ldg(reinterpret_cast<const uint4*>(gsk) + oc * 4 + i);
    } else if (tid == 320) {
      asm volatile("mbarrier.init.shared.b64 [%0], 1;" ::"r"(smem_u32(&sm.mbarh)) : "memory");
      asm volatile("mbarrier.init.shared.b64 [%0], 1;" ::"r"(smem_u32(&sm.mbar)) : "memory");
      asm volatile("mbarrier.init.shared.b64 [%0], 1;" ::"r"(smem_u32(&sm.mbarw)) : "memory");
      asm volatile("mbarrier.init.shared.b64 [%0], 1;" ::"r"(smem_u32(&sm.mbarc)) : "memory");
      asm volatile("fence.proxy.async.shared::cta;" ::: "memory");
    }
    if (tid < 320) bar_sync(6, 384); else { bar_arrive(6, 384); bar_sync(5, 64); }
    STAMP(9);
    if (tid < 320) {
      uint32_t o[4][4];
#pragma unroll
      for (int p = 0; p < 4; p++) {
        const bf162 w0 = u2b(__byte_perm(sk[p].x, sk[p].z, 0x5410)), w1 = u2b(__byte_perm(sk[p].x, sk[p].z, 0x7632));
        const bf162 w2 = u2b(__byte_perm(sk[p].y, sk[p].w, 0x5410)), w3 = u2b(__byte_perm(sk[p].y, sk[p].w, 0x7632));
        uint32_t kv[4];
#pragma unroll
        for (int i = 0; i < 4; i++) {
          const uint32_t k0 = p == 0 ? kk[i].x : p == 1 ? kk[i].y : p == 2 ? kk[i].z : kk[i].w;
          const uint32_t k1 = p == 0 ? kk[i + 1].x : p == 1 ? kk[i + 1].y : p == 2 ? kk[i + 1].z : kk[i + 1].w;
          const uint32_t k2 = p == 0 ? kk[i + 2].x : p == 1 ? kk[i + 2].y : p == 2 ? kk[i + 2].z : kk[i + 2].w;
          const uint32_t k3 = p == 0 ? kk[i + 3].x : p == 1 ? kk[i + 3].y : p == 2 ? kk[i + 3].z : kk[i + 3].w;
          const uint32_t vx = p == 0 ? vv[i].x : p == 1 ? vv[i].y : p == 2 ? vv[i].z : vv[i].w;
          bf162 a = __hmul2_rn(u2b(k0), w3);
          a = __hadd2_rn(a, __hmul2_rn(u2b(k1), w2));
          a = __hadd2_rn(a, __hmul2_rn(u2b(k2), w1));
          a = __hadd2_rn(a, __hmul2_rn(u2b(k3), w0));
          kv[i] = b2u(__hmul2_rn(a, u2b(vx)));
        }
        o[p][0] = enc(__byte_perm(kv[0], kv[1], 0x5410)); o[p][1] = enc(__byte_perm(kv[2], kv[3], 0x5410));
        o[p][2] = enc(__byte_perm(kv[0], kv[1], 0x7632)); o[p][3] = enc(__byte_perm(kv[2], kv[3], 0x7632));
      }
      uint2* dst = reinterpret_cast<uint2*>(g_kv) + (size_t)(oc * 8) * 512 + (r0 >> 2);
#pragma unroll
      for (int p = 0; p < 4; p++) {
        st_pub2(dst + (2 * p) * 512, o[p][0], o[p][1]);
        st_pub2(dst + (2 * p + 1) * 512, o[p][2], o[p][3]);
      }
      STAMP(10);
      if (wid == 0) bar_sync(4, 320); else bar_arrive(4, 320);
      if (tid == 0) {
        const unsigned old = atomicAdd(&g_ctr2, 1u);
        const unsigned target = (old / NCTA + 1u) * NCTA;
        uint32_t v;
        int it = 0;
        do {
          asm volatile("ld.relaxed.gpu.global.u32 %0, [%1];" : "=r"(v) : "l"(&g_ctr2) : "memory");
        } while ((int)(v - target) < 0 && ++it < SPIN_LIMIT);
        asm volatile("mbarrier.arrive.shared.b64 _, [%0];" ::"r"(smem_u32(&sm.mbarc)) : "memory");
      }
      __syncwarp();
    } else {
      const int t0 = tid - 320;
      const uint4 zz = make_uint4(0, 0, 0, 0);
      if (tid == 320) {
        while (clock64() - tstart < H_DELAY) {}
        mbar_expect(&sm.mbarh, CPC * S_ * 2);
        bulk_g2s(hs, gh + (size_t)c0 * S_, CPC * S_ * 2, &sm.mbarh);
      }
      __syncwarp();
      for (int t = t0; t < CPC * 17; t += 64) *reinterpret_cast<uint4*>(&sm.u[t / 17][(t % 17) * 8]) = zz;
      if (t0 < 40) *reinterpret_cast<uint4*>(&sm.tabA[0][0][0] + tab_off(t0 >> 3) + ((t0 >> 2) & 1) * TABW + 1024 + 4 * (t0 & 3)) = zz;
#pragma unroll 4
      for (int i = 0; i < 20; i++) g_y2[cta * 1280 + t0 + 64 * i] = zz;
      (&g_cand[cta][0][0])[t0] = zz;
      (&g_cand[cta][0][0])[64 + t0] = zz;
      if (t0 < 32) (&g_cand[cta][0][0])[128 + t0] = zz;
      else if (t0 < 35) { if (cta < N1) g_act[cta * 3 + (t0 - 32)] = zz; }
      else if (t0 == 35) g_keys[cta] = 0u;
      bar_sync(5, 64);
      if (tid == 352) {
        __threadfence();
        const unsigned old = atomicAdd(&g_ctr, 1u);
        sm.target = (old / NCTA + 1u) * NCTA;
      }
      __syncwarp();
    }
    mbar_wait(&sm.mbarh);
#pragma unroll
    for (int i = 0; i < 4; i++) {
      const int t = (NTHR - 1 - tid) + NTHR * i;
      if (t < CPC * 256) {
        uint32_t* tb = &sm.tabA[0][0][0] + tab_off(t >> 8) + (255 - (t & 255)) * 4;
        const uint4 h = hs[t];
        const uint32_t hp = (t & 255) ? reinterpret_cast<const uint32_t*>(hs)[4 * t - 1] : 0u;
        uint4 r1, rr;
        r1.x = __byte_perm(h.w, 0, 0x1032); r1.y = __byte_perm(h.z, 0, 0x1032);
        r1.z = __byte_perm(h.y, 0, 0x1032); r1.w = __byte_perm(h.x, 0, 0x1032);
        rr.x = __byte_perm(h.w, h.z, 0x7610); rr.y = __byte_perm(h.z, h.y, 0x7610);
        rr.z = __byte_perm(h.y, h.x, 0x7610); rr.w = __byte_perm(h.x, hp, 0x7610);
        *reinterpret_cast<uint4*>(tb) = rr;
        *reinterpret_cast<uint4*>(tb + TABW) = r1;
      }
    }
    STAMP(12);
  }
  mbar_wait(&sm.mbarc);
  {
    uint4 v[4];
    uint4* src = g_kv + c0 * 256 + tid;
#pragma unroll
    for (int i = 0; i < 4; i++) if (i < 3 || tid < 128) v[i] = ld_poll4(src + NTHR * i);
#pragma unroll
    for (int i = 0; i < 4; i++) {
      if (i < 3 || tid < 128) {
        int it = 0;
        while (!ready4(v[i]) && ++it < SPIN_LIMIT) { __nanosleep(POLL_NS); v[i] = ld_poll4(src + NTHR * i); }
        const int t = tid + NTHR * i;
        *reinterpret_cast<uint4*>(&sm.u[t >> 8][UPAD + (t & 255) * 8]) = make_uint4(~v[i].x, ~v[i].y, ~v[i].z, ~v[i].w);
      }
    }
    STAMP(11);
    asm volatile("fence.proxy.async.shared::cta;" ::: "memory");
    __syncthreads();
#pragma unroll
    for (int i = 0; i < 4; i++) if (i < 3 || tid < 128) src[NTHR * i] = make_uint4(0, 0, 0, 0);
    if (tid >= 256) {
      const int t0 = tid - 256;
      if (((t0 & 15) >> 2) < ((t0 >> 4) & 3))
        *reinterpret_cast<uint4*>(&sm.z[t0 >> 6][(t0 >> 4) & 3][(t0 & 15) * 4]) = make_uint4(0, 0, 0, 0);
    }
  }
  STAMP(1);
  if (ABL == 5) return;

  const int wg = __shfl_sync(0xffffffffu, tid >> 7, 0);
  const int wtid = tid & 127;
  uint4* tile = reinterpret_cast<uint4*>(&sm.tabB[0][0][0]);
  if (wg < 2) {
    asm volatile("setmaxnreg.inc.sync.aligned.u32 224;");
    const int w = (tid >> 5) & 3, g = lane >> 2, tq = lane & 3;
    float* zw = sm.z[wg][w];
    const int sw = 3 * (((tq + w) >> 1) & 1);
    const int off_even = 16 * (tq + w) + 4 * ((0 + (g >> 2)) ^ sw) + (g & 3);
    const int off_odd = 16 * (tq + w) + 4 * ((2 + (g >> 2)) ^ sw) + (g & 3);
    uint32_t a[8][8];
    const uint32_t* tp0 = &sm.tabA[0][g & 1][1019 - 8 * w - (g >> 1) + tq];
    load_a_all(a, tp0 + tab_off(wg));
    float acc[8][16];
#pragma unroll
    for (int b = 0; b < 8; b++)
#pragma unroll
      for (int i = 0; i < 16; i++) acc[b][i] = 0.f;
#pragma unroll 1
    for (int c = wg; c < CPC; c += 2) {
      const uint64_t desc = (uint64_t)((smem_u32(&sm.u[c][UPAD - 8]) & 0x3FFFF) >> 4) | ((uint64_t)1 << 16) | ((uint64_t)8 << 32);
      CST(c, 0);
      if (c > 0) bar_sync(1 + wg, 256);
      issue_g<0>(acc, a[0], desc);
      CST(c, 1);
      issue_g<1>(acc, a[1], desc);
      issue_g<2>(acc, a[2], desc);
      issue_g<3>(acc, a[3], desc);
      issue_g<4>(acc, a[4], desc);
      issue_g<5>(acc, a[5], desc);
      if (c + 1 < CPC) bar_arrive(1 + (wg ^ 1), 256);
      issue_g<6>(acc, a[6], desc);
      issue_g<7>(acc, a[7], desc);
      CST(c, 2);
      if (c >= 2) bar_sync(5 + wg, 256);
      wg_wait<4>();
      fence_blk<0>(acc); fence_blk<1>(acc); fence_blk<2>(acc); fence_blk<3>(acc);
      sts_blk<0>(acc, zw, off_even, off_odd);
      sts_blk<1>(acc, zw, off_even, off_odd);
      sts_blk<2>(acc, zw, off_even, off_odd);
      sts_blk<3>(acc, zw, off_even, off_odd);
      CST(c, 3);
      wg_wait<0>();
      fence_blk<4>(acc); fence_blk<5>(acc); fence_blk<6>(acc); fence_blk<7>(acc);
#pragma unroll
      for (int i = 0; i < 8; i++) fence_a(a[i]);
      sts_blk<4>(acc, zw, off_even, off_odd);
      sts_blk<5>(acc, zw, off_even, off_odd);
      sts_blk<6>(acc, zw, off_even, off_odd);
      sts_blk<7>(acc, zw, off_even, off_odd);
      bar_arrive(3 + wg, 256);
      CST(c, 4);
      if (c + 2 < CPC) load_a_all(a, tp0 + tab_off(c + 2));
    }
    STAMP(2 + wg);
    asm volatile("setmaxnreg.dec.sync.aligned.u32 168;");
  } else {
    asm volatile("setmaxnreg.dec.sync.aligned.u32 56;");
    if (wtid == 32) {
      const uint32_t mw = smem_u32(&sm.mbarw);
      mbar_expect(&sm.mbar, 17 * D_ * 2);
#pragma unroll 1
      for (int r = 0; r < 16; r++) bulk_g2s(&sm.q[r][0], gq + (size_t)(cta * 16 + r) * D_, D_ * 2, &sm.mbar);
      bulk_g2s(&sm.wr[0], gwr, D_ * 2, &sm.mbar);
      if (cta < N1) {
        asm volatile("mbarrier.arrive.expect_tx.shared.b64 _, [%0], %1;" ::"r"(mw), "r"(3840 * 16) : "memory");
#pragma unroll 1
        for (int i = 0; i < 4; i++) {
          asm volatile("cp.async.bulk.tensor.2d.shared::cluster.global.mbarrier::complete_tx::bytes [%0], [%1, {%3, %4}], [%2];" ::"r"(smem_u32(&sm.w[i * 480])),
                       "l"(&tmg), "r"(mw), "r"(cta * 24), "r"(i * 160) : "memory");
          asm volatile("cp.async.bulk.tensor.2d.shared::cluster.global.mbarrier::complete_tx::bytes [%0], [%1, {%3, %4}], [%2];" ::"r"(smem_u32(&sm.w[1920 + i * 480])),
                       "l"(&tmu), "r"(mw), "r"(cta * 24), "r"(i * 160) : "memory");
        }
      } else if (cta < N1 + N2) {
        asm volatile("mbarrier.arrive.expect_tx.shared.b64 _, [%0], %1;" ::"r"(mw), "r"(3072 * 16) : "memory");
#pragma unroll 1
        for (int i = 0; i < 6; i++)
          asm volatile("cp.async.bulk.tensor.2d.shared::cluster.global.mbarrier::complete_tx::bytes [%0], [%1, {%3, %4}], [%2];" ::"r"(smem_u32(&sm.w[i * 512])),
                       "l"(&tmd), "r"(mw), "r"((cta - N1) * 16), "r"(i * 256) : "memory");
      }
    }
    if (wtid == 0) wait_ctr(&g_ctr, sm.target);
    const int rpb = wtid >> 1, re2 = wtid & 1;
    const int rsw = 3 * ((rpb >> 1) & 1);
    const int roff0 = 16 * rpb + 4 * ((2 * re2 + 0) ^ rsw);
    const int roff1 = 16 * rpb + 4 * ((2 * re2 + 1) ^ rsw);
    const uint32_t dvl = reinterpret_cast<const unsigned short*>(gD)[c0 + (lane < CPC ? lane : 0)];
#pragma unroll 1
    for (int c = 0; c < CPC; c++) {
      const int zg = c & 1;
      const uint32_t dvc = __shfl_sync(0xffffffffu, dvl, c);
      const bf162 d2 = u2b(dvc | (dvc << 16));
      CST(c, 5);
      bar_sync(3 + zg, 256);
#pragma unroll
      for (int half = 0; half < 2; half++) {
        const float* zb = sm.z[zg][0] + half * 1024;
        float4 x[4][2];
#pragma unroll
        for (int ww = 0; ww < 4; ww++) {
          x[ww][0] = *reinterpret_cast<const float4*>(zb + ww * ZPB * 16 + roff0);
          x[ww][1] = *reinterpret_cast<const float4*>(zb + ww * ZPB * 16 + roff1);
        }
        const int sidx = half * 1024 + wtid * 8;
        const uint4 kvv = *reinterpret_cast<const uint4*>(&sm.u[c][UPAD + sidx]);
        if (half == 1 && c + 2 < CPC) bar_arrive(5 + zg, 256);
        uint4 o;
        o.x = pack2((x[0][0].x + x[1][0].x) + (x[2][0].x + x[3][0].x), (x[0][0].y + x[1][0].y) + (x[2][0].y + x[3][0].y));
        o.y = pack2((x[0][0].z + x[1][0].z) + (x[2][0].z + x[3][0].z), (x[0][0].w + x[1][0].w) + (x[2][0].w + x[3][0].w));
        o.z = pack2((x[0][1].x + x[1][1].x) + (x[2][1].x + x[3][1].x), (x[0][1].y + x[1][1].y) + (x[2][1].y + x[3][1].y));
        o.w = pack2((x[0][1].z + x[1][1].z) + (x[2][1].z + x[3][1].z), (x[0][1].w + x[1][1].w) + (x[2][1].w + x[3][1].w));
        o.x = b2u(__hadd2_rn(u2b(o.x), __hmul2_rn(u2b(kvv.x), d2)));
        o.y = b2u(__hadd2_rn(u2b(o.y), __hmul2_rn(u2b(kvv.y), d2)));
        o.z = b2u(__hadd2_rn(u2b(o.z), __hmul2_rn(u2b(kvv.z), d2)));
        o.w = b2u(__hadd2_rn(u2b(o.w), __hmul2_rn(u2b(kvv.w), d2)));
        st_pub4(g_y2 + ((64 * half + rpb) * 640 + c0 + c) * 2 + re2, enc4(o));
        CST(c, 6 + half);
      }
    }
    STAMP(4);
    asm volatile("setmaxnreg.inc.sync.aligned.u32 168;");
  }

  if (ABL == 4) { if (cta < N1 + N2) mbar_wait(&sm.mbarw); mbar_wait(&sm.mbar); return; }
  const int g = lane >> 2, tq = lane & 3;
  const int hh = wid & 1, gqi = wid >> 1;
  const int row = hh * 8 + g;
  uint32_t hreg[16], hnreg[16];
  {
    const uint4* src = g_y2 + cta * 1280 + tid;
    uint4 v[4];
#pragma unroll
    for (int i = 0; i < 4; i++) if (i < 3 || tid < 128) v[i] = ld_poll4(src + NTHR * i);
    if (wid < 10) {
      mbar_wait(&sm.mbar);
#pragma unroll
      for (int k = 0; k < 4; k++) {
        const uint4 qv4 = *reinterpret_cast<const uint4*>(&sm.q[row][32 * (4 * gqi + k) + 8 * tq]);
        hreg[4 * k] = qv4.x; hreg[4 * k + 1] = qv4.y; hreg[4 * k + 2] = qv4.z; hreg[4 * k + 3] = qv4.w;
      }
      const float2 ps = row_part_stats(hreg);
      if (tq == 0) sm.stq[row][gqi] = ps;
      bar_sync(7, 320);
      row_normalize(sm.stq[row], hreg, hnreg);
    }
    int it = 0;
    bool all;
    do {
      all = true;
#pragma unroll
      for (int i = 0; i < 4; i++)
        if ((i < 3 || tid < 128) && !ready4(v[i])) { v[i] = ld_poll4(src + NTHR * i); all = false; }
    } while (!all && ++it < SPIN_LIMIT);
#pragma unroll
    for (int i = 0; i < 4; i++) {
      if (i < 3 || tid < 128) {
        const int t = tid + NTHR * i;
        tile[(t & 1) * 640 + tile_perm(t >> 1)] = make_uint4(~v[i].x, ~v[i].y, ~v[i].z, ~v[i].w);
      }
    }
  }
  __syncthreads();
  STAMP(5);
  if (ABL == 3) { if (cta < N1 + N2) mbar_wait(&sm.mbarw); return; }

  if (wid < 10) {
#pragma unroll
    for (int k = 0; k < 4; k++) {
      const int base = 32 * (4 * gqi + k);
      const int lch = base + 8 * ((lane & 7) >> 1) + 2 * (lane >> 3) + (lane & 1);
      uint32_t y[4];
      asm volatile("ldmatrix.sync.aligned.m8n8.x4.trans.shared.b16 {%0,%1,%2,%3}, [%4];"
                   : "=r"(y[0]), "=r"(y[1]), "=r"(y[2]), "=r"(y[3]) : "r"(smem_u32(&tile[hh * 640 + tile_perm(lch)])) : "memory");
#pragma unroll
      for (int i = 0; i < 4; i++)
        hreg[4 * k + i] = b2u(__hadd2_rn(u2b(hreg[4 * k + i]), __hmul2_rn(u2b(hnreg[4 * k + i]), u2b(y[i]))));
    }
    const float2 ps = row_part_stats(hreg);
    if (tq == 0) sm.st[row][gqi] = ps;
    STAMP(13);
    bar_sync(7, 320);
    row_normalize(sm.st[row], hreg, hnreg);
    float cr[4][4];
#pragma unroll
    for (int k = 0; k < 4; k++) {
      cr[k][0] = cr[k][1] = cr[k][2] = cr[k][3] = 0.f;
      const uint4 w4 = sm.wr[4 * (4 * gqi + k) + tq];
      mma_bf16(cr[k], hnreg[4 * k + 0], hnreg[4 * k + 1], w4.x, w4.y);
      mma_bf16(cr[k], hnreg[4 * k + 2], hnreg[4 * k + 3], w4.z, w4.w);
    }
    if (tq == 0) sm.rp[row][gqi] = (cr[0][0] + cr[1][0]) + (cr[2][0] + cr[3][0]);
  }
  STAMP(14);
  __syncthreads();
  uint32_t best;
  {
    const int rr = lane & 15;
    const float r = ((sm.rp[rr][0] + sm.rp[rr][1]) + (sm.rp[rr][2] + sm.rp[rr][3])) + sm.rp[rr][4];
    const uint32_t bits = __bfloat16_as_ushort(__float2bfloat16_rn(r));
    const uint32_t ord = (bits & 0x8000u) ? (bits ^ 0xFFFFu) : (bits ^ 0x8000u);
    const uint32_t key = (ord << 16) | 0x8000u | (uint32_t)(2047 - (cta * 16 + rr));
    best = __reduce_max_sync(0xffffffffu, key);
  }
  if (tid == 352) asm volatile("st.relaxed.gpu.global.u32 [%0], %1;" ::"l"(&g_keys[cta]), "r"(best) : "memory");
  STAMP(15);
  const int brow = (2047 - (int)(best & 0x7FFu)) - cta * 16;
  if (wid < 10 && row == brow) {
#pragma unroll
    for (int k = 0; k < 4; k++)
      st_pub4(&g_cand[cta][0][4 * (4 * gqi + k) + tq], enc4(make_uint4(hnreg[4 * k], hnreg[4 * k + 1], hnreg[4 * k + 2], hnreg[4 * k + 3])));
#pragma unroll
    for (int k = 0; k < 4; k++)
      st_pub4(&g_cand[cta][1][4 * (4 * gqi + k) + tq], enc4(make_uint4(hreg[4 * k], hreg[4 * k + 1], hreg[4 * k + 2], hreg[4 * k + 3])));
  }
#pragma unroll
  for (int i = 0; i < 16; i++) hreg[i] = b2u(__hadd2_rn(u2b(hreg[i]), u2b(hnreg[i])));
  STAMP(6);
  if (ABL == 2) { if (cta < N1 + N2) mbar_wait(&sm.mbarw); return; }
  if (wid == 11) {
    const uint4* kp = reinterpret_cast<const uint4*>(g_keys) + lane;
    uint4 v = ld_poll4(kp);
    int it = 0;
    while (!ready4(v) && ++it < SPIN_LIMIT) v = ld_poll4(kp);
    const uint32_t m = max(max(v.x, v.y), max(v.z, v.w));
    const uint32_t wk = __reduce_max_sync(0xffffffffu, m);
    if (lane == 0) sm.win = wk;
  }
  __syncthreads();
  const uint32_t win = sm.win;
  const int wrow = 2047 - (int)(win & 0x7FFu);
  const int wcta = wrow >> 4;
  const bool st_out = wid < 10 && (cta * 16 + row) != wrow;
  uint4* outp = reinterpret_cast<uint4*>(gout + (size_t)(cta * 16 + row) * D_) + 16 * gqi + tq;
  if (cta >= N1 && st_out) {
#pragma unroll
    for (int k = 0; k < 4; k++) outp[4 * k] = make_uint4(hreg[4 * k], hreg[4 * k + 1], hreg[4 * k + 2], hreg[4 * k + 3]);
  }
  STAMP(7);
  if (ABL == 1) { if (cta < N1 + N2) mbar_wait(&sm.mbarw); return; }
  if (cta < N1 + N2) mbar_wait(&sm.mbarw);
  float* xs = &sm.z[0][0][0];
  float* part = xs + 2048;
  if (cta < N1) {
    if (tid < 80) {
      const uint4 v = poll4(&g_cand[wcta][0][tid]);
      float4* xp = reinterpret_cast<float4*>(xs + tid * 8);
      xp[0] = make_float4(lo_f(v.x), hi_f(v.x), lo_f(v.y), hi_f(v.y));
      xp[1] = make_float4(lo_f(v.z), hi_f(v.z), lo_f(v.w), hi_f(v.w));
    }
    __syncthreads();
    const int m = wid / 6, hc = (wid % 6) >> 1, rs = (wid & 1) * 32 + lane;
    float a[8];
#pragma unroll
    for (int j = 0; j < 8; j++) a[j] = 0.f;
#pragma unroll
    for (int it = 0; it < 10; it++) {
      const int r = rs + 64 * it;
      const uint4 wv = sm.w[m * 1920 + r * 3 + hc];
      const float x = xs[r];
      a[0] = fmaf(x, lo_f(wv.x), a[0]); a[1] = fmaf(x, hi_f(wv.x), a[1]);
      a[2] = fmaf(x, lo_f(wv.y), a[2]); a[3] = fmaf(x, hi_f(wv.y), a[3]);
      a[4] = fmaf(x, lo_f(wv.z), a[4]); a[5] = fmaf(x, hi_f(wv.z), a[5]);
      a[6] = fmaf(x, lo_f(wv.w), a[6]); a[7] = fmaf(x, hi_f(wv.w), a[7]);
    }
    {
      const bool up = lane & 16;
#pragma unroll
      for (int j = 0; j < 4; j++) {
        const float send = up ? a[j] : a[j + 4], keep = up ? a[j + 4] : a[j];
        a[j] = keep + __shfl_xor_sync(0xffffffffu, send, 16);
      }
      const bool up2 = lane & 8;
#pragma unroll
      for (int j = 0; j < 2; j++) {
        const float send = up2 ? a[j] : a[j + 2], keep = up2 ? a[j + 2] : a[j];
        a[j] = keep + __shfl_xor_sync(0xffffffffu, send, 8);
      }
      const bool up3 = lane & 4;
      const float send = up3 ? a[0] : a[1], keep = up3 ? a[1] : a[0];
      a[0] = keep + __shfl_xor_sync(0xffffffffu, send, 4);
      a[0] += __shfl_xor_sync(0xffffffffu, a[0], 2);
      a[0] += __shfl_xor_sync(0xffffffffu, a[0], 1);
      if ((lane & 3) == 0) part[wid * 8 + (lane >> 2)] = a[0];
    }
    __syncthreads();
    if (wid == 0) {
      uint32_t bits = 0;
      if (lane < 24) {
        const int hc2 = lane >> 3, j = lane & 7;
        const float gt = rbf(part[(2 * hc2) * 8 + j] + part[(2 * hc2 + 1) * 8 + j]);
        const float up = rbf(part[(6 + 2 * hc2) * 8 + j] + part[(6 + 2 * hc2 + 1) * 8 + j]);
        const float sg = rbf(gt / (1.f + __expf(-gt)));
        bits = __bfloat16_as_ushort(__float2bfloat16_rn(sg * up));
      }
      const uint32_t nb = __shfl_down_sync(0xffffffffu, bits, 1);
      const uint32_t pw = bits | (nb << 16);
      const uint32_t w1 = __shfl_down_sync(0xffffffffu, pw, 2), w2 = __shfl_down_sync(0xffffffffu, pw, 4), w3 = __shfl_down_sync(0xffffffffu, pw, 6);
      if (lane < 24 && (lane & 7) == 0) st_pub4(&g_act[cta * 3 + (lane >> 3)], enc4(make_uint4(pw, w1, w2, w3)));
      __syncwarp();
      bar_arrive(7, 320);
    } else if (wid < 10) {
      bar_sync(7, 320);
    }
    if (st_out) {
#pragma unroll
      for (int k = 0; k < 4; k++) outp[4 * k] = make_uint4(hreg[4 * k], hreg[4 * k + 1], hreg[4 * k + 2], hreg[4 * k + 3]);
    }
  } else if (cta < N1 + N2 && ABL != 6) {
    const int j2 = cta - N1;
    uint4 rowv = make_uint4(0, 0, 0, 0);
    if (tid < 192) {
      const uint4 v = poll4(&g_act[tid]);
      float4* xp = reinterpret_cast<float4*>(xs + tid * 8);
      xp[0] = make_float4(lo_f(v.x), hi_f(v.x), lo_f(v.y), hi_f(v.y));
      xp[1] = make_float4(lo_f(v.z), hi_f(v.z), lo_f(v.w), hi_f(v.w));
    } else if (tid < 196) {
      const int t = tid - 192;
      rowv = poll4(&g_cand[wcta][t >> 1][j2 * 2 + (t & 1)]);
      reinterpret_cast<uint4*>(part + 256)[t] = rowv;
    }
    __syncthreads();
    const int hc = lane & 1, rs = wid * 16 + (lane >> 1);
    float a[8];
#pragma unroll
    for (int j = 0; j < 8; j++) a[j] = 0.f;
#pragma unroll
    for (int it = 0; it < 8; it++) {
      const int r = rs + 192 * it;
      const uint4 wv = sm.w[r * 2 + hc];
      const float x = xs[r];
      a[0] = fmaf(x, lo_f(wv.x), a[0]); a[1] = fmaf(x, hi_f(wv.x), a[1]);
      a[2] = fmaf(x, lo_f(wv.y), a[2]); a[3] = fmaf(x, hi_f(wv.y), a[3]);
      a[4] = fmaf(x, lo_f(wv.z), a[4]); a[5] = fmaf(x, hi_f(wv.z), a[5]);
      a[6] = fmaf(x, lo_f(wv.w), a[6]); a[7] = fmaf(x, hi_f(wv.w), a[7]);
    }
    {
      const bool up = lane & 16;
#pragma unroll
      for (int j = 0; j < 4; j++) {
        const float send = up ? a[j] : a[j + 4], keep = up ? a[j + 4] : a[j];
        a[j] = keep + __shfl_xor_sync(0xffffffffu, send, 16);
      }
      const bool up2 = lane & 8;
#pragma unroll
      for (int j = 0; j < 2; j++) {
        const float send = up2 ? a[j] : a[j + 2], keep = up2 ? a[j + 2] : a[j];
        a[j] = keep + __shfl_xor_sync(0xffffffffu, send, 8);
      }
      const bool up3 = lane & 4;
      const float send = up3 ? a[0] : a[1], keep = up3 ? a[1] : a[0];
      a[0] = keep + __shfl_xor_sync(0xffffffffu, send, 4);
      a[0] += __shfl_xor_sync(0xffffffffu, a[0], 2);
      if ((lane & 2) == 0) part[wid * 16 + hc * 8 + (lane >> 2)] = a[0];
    }
    __syncthreads();
    if (tid < 16) {
      float y = 0.f;
#pragma unroll
      for (int i = 0; i < 12; i++) y += part[i * 16 + tid];
      const uint32_t ord = win >> 16;
      const uint32_t rb = (ord & 0x8000u) ? (ord ^ 0x8000u) : (ord ^ 0xFFFFu);
      const float r = __uint_as_float(rb << 16);
      const float sg = rbf(1.f / (1.f + __expf(-r)));
      const float yy = rbf(rbf(y) * sg);
      const unsigned short* rv = reinterpret_cast<const unsigned short*>(part + 256);
      const float hn = __uint_as_float((uint32_t)rv[tid] << 16), h = __uint_as_float((uint32_t)rv[16 + tid] << 16);
      gout[(size_t)wrow * D_ + j2 * 16 + tid] = __float2bfloat16_rn(h + rbf(hn + yy));
    }
  }
  STAMP(8);
}

}

typedef CUresult (*EncodeFn)(CUtensorMap*, CUtensorMapDataType, cuuint32_t, void*, const cuuint64_t*, const cuuint64_t*,
                             const cuuint32_t*, const cuuint32_t*, CUtensorMapInterleave, CUtensorMapSwizzle,
                             CUtensorMapL2promotion, CUtensorMapFloatOOBfill);

extern "C" void kernel_launch(void* const* d_in, const int* in_sizes, int n_in, void* d_out, int out_size) {
  (void)in_sizes; (void)n_in; (void)out_size;
  static EncodeFn encode = nullptr;
  static CUtensorMap tmg, tmu, tmd;
  static void* cached[3] = {nullptr, nullptr, nullptr};
  if (!encode) {
    cudaFuncSetAttribute(fused_kernel, cudaFuncAttributeMaxDynamicSharedMemorySize, (int)sizeof(Smem));
    void* fn = nullptr;
    cudaDriverEntryPointQueryResult qr;
    cudaGetDriverEntryPoint("cuTensorMapEncodeTiled", &fn, cudaEnableDefault, &qr);
    encode = (EncodeFn)fn;
  }
  if (cached[0] != d_in[8] || cached[1] != d_in[9] || cached[2] != d_in[10]) {
    const cuuint32_t es[2] = {1, 1};
    {
      const cuuint64_t dims[2] = {F_, D_}, strides[1] = {F_ * 2};
      const cuuint32_t box[2] = {24, 160};
      encode(&tmg, CU_TENSOR_MAP_DATA_TYPE_BFLOAT16, 2, d_in[8], dims, strides, box, es, CU_TENSOR_MAP_INTERLEAVE_NONE,
             CU_TENSOR_MAP_SWIZZLE_NONE, CU_TENSOR_MAP_L2_PROMOTION_NONE, CU_TENSOR_MAP_FLOAT_OOB_FILL_NONE);
      encode(&tmu, CU_TENSOR_MAP_DATA_TYPE_BFLOAT16, 2, d_in[9], dims, strides, box, es, CU_TENSOR_MAP_INTERLEAVE_NONE,
             CU_TENSOR_MAP_SWIZZLE_NONE, CU_TENSOR_MAP_L2_PROMOTION_NONE, CU_TENSOR_MAP_FLOAT_OOB_FILL_NONE);
    }
    {
      const cuuint64_t dims[2] = {D_, F_}, strides[1] = {D_ * 2};
      const cuuint32_t box[2] = {16, 256};
      encode(&tmd, CU_TENSOR_MAP_DATA_TYPE_BFLOAT16, 2, d_in[10], dims, strides, box, es, CU_TENSOR_MAP_INTERLEAVE_NONE,
             CU_TENSOR_MAP_SWIZZLE_NONE, CU_TENSOR_MAP_L2_PROMOTION_NONE, CU_TENSOR_MAP_FLOAT_OOB_FILL_NONE);
    }
    cached[0] = d_in[8]; cached[1] = d_in[9]; cached[2] = d_in[10];
  }
  fused_kernel<<<NCTA, NTHR, sizeof(Smem), cudaStreamPerThread>>>(
      tmg, tmu, tmd, (const bf16*)d_in[0], (const bf16*)d_in[1], (const bf16*)d_in[2], (const bf16*)d_in[3],
      (const bf16*)d_in[4], (const bf16*)d_in[5], (const bf16*)d_in[7], (bf16*)d_out);
}
```

```cpp
#include <cuda_runtime.h>
#include <cuda_bf16.h>
#include <cuda.h>
#include <stdint.h>

namespace {

typedef __nv_bfloat16 bf16;
typedef __nv_bfloat162 bf162;

constexpr int S_ = 2048, D_ = 640, F_ = 1536;
constexpr int NCTA = 128, CPC = 5, NTHR = 384;
constexpr int UPAD = 136, USTR = 2192;
constexpr int TABW = 1040;
constexpr int ZPB = 132;
constexpr int QSTR = 648;
constexpr int N1 = 64;
constexpr int N2 = 40;
constexpr int SPIN_LIMIT = 1 << 19;
#define LN2_EXACT 1
#define ABL 0
#define CTR_NS 0
#define POLL_NS 100
#define H_DELAY 0
#define Q_DELAY 4500

struct __align__(128) Smem {
  uint32_t tabA[3][2][TABW];
  uint32_t extra[1024];
  uint32_t tabB[2][2][TABW];
  bf16 u[CPC][USTR];
  float z[2][4][ZPB * 16];
  bf16 q[16][QSTR];
  alignas(128) uint4 w[3840];
  uint4 wr[80];
  float2 st[16][5];
  float2 stq[16][5];
  float rp[16][5];
  unsigned long long mbar;
  unsigned long long mbarw;
  unsigned long long mbarc;
  unsigned long long mbarh;
  uint32_t target;
  uint32_t best;
  uint32_t win;
};

__device__ uint4 g_kv[D_ * S_ / 8];
__device__ uint4 g_y2[D_ * S_ / 8];
__device__ uint32_t g_keys[NCTA][NCTA];
__device__ uint4 g_cand[NCTA][2][80];
__device__ uint4 g_act[N2][F_ / 8];
__device__ unsigned int g_ctr;
__device__ unsigned int g_ctr2;
#define STAMP(i)
#define CST(c, i)

__device__ __forceinline__ uint32_t smem_u32(const void* p) { return (uint32_t)__cvta_generic_to_shared(p); }
__device__ __forceinline__ void wg_fence() { asm volatile("wgmma.fence.sync.aligned;" ::: "memory"); }
__device__ __forceinline__ void wg_commit() { asm volatile("wgmma.commit_group.sync.aligned;" ::: "memory"); }
template <int N> __device__ __forceinline__ void wg_wait() { asm volatile("wgmma.wait_group.sync.aligned %0;" ::"n"(N) : "memory"); }
__device__ __forceinline__ void bar_sync(int id, int n) { asm volatile("bar.sync %0, %1;" ::"r"(id), "r"(n) : "memory"); }
__device__ __forceinline__ void bar_arrive(int id, int n) { asm volatile("bar.arrive %0, %1;" ::"r"(id), "r"(n) : "memory"); }
__device__ __forceinline__ bf162 u2b(uint32_t u) { return *reinterpret_cast<bf162*>(&u); }
__device__ __forceinline__ uint32_t b2u(bf162 b) { return *reinterpret_cast<uint32_t*>(&b); }
__device__ __forceinline__ float lo_f(uint32_t u) { return __uint_as_float(u << 16); }
__device__ __forceinline__ float hi_f(uint32_t u) { return __uint_as_float(u & 0xFFFF0000u); }
__device__ __forceinline__ float rbf(float x) { return __bfloat162float(__float2bfloat16_rn(x)); }
__device__ __forceinline__ uint32_t pack2(float a, float b) { return b2u(__floats2bfloat162_rn(a, b)); }
__device__ __forceinline__ uint32_t enc(uint32_t w) { return max(~w, 1u); }
__device__ __forceinline__ uint4 enc4(uint4 v) { return make_uint4(enc(v.x), enc(v.y), enc(v.z), enc(v.w)); }
__device__ __forceinline__ uint4 ld_poll4(const uint4* p) {
  uint4 v;
  asm volatile("ld.relaxed.gpu.global.v4.u32 {%0,%1,%2,%3}, [%4];" : "=r"(v.x), "=r"(v.y), "=r"(v.z), "=r"(v.w) : "l"(p) : "memory");
  return v;
}
__device__ __forceinline__ bool ready4(uint4 v) { return v.x != 0u && v.y != 0u && v.z != 0u && v.w != 0u; }
__device__ __forceinline__ uint4 poll4(const uint4* p) {
  uint4 v = ld_poll4(p);
  int it = 0;
  while (!ready4(v) && ++it < SPIN_LIMIT) v = ld_poll4(p);
  return make_uint4(~v.x, ~v.y, ~v.z, ~v.w);
}
__device__ __forceinline__ void st_pub4(uint4* p, uint4 v) {
  asm volatile("st.relaxed.gpu.global.v4.u32 [%0], {%1,%2,%3,%4};" ::"l"(p), "r"(v.x), "r"(v.y), "r"(v.z), "r"(v.w) : "memory");
}
__device__ __forceinline__ void st_pub2(uint2* p, uint32_t a, uint32_t b) {
  asm volatile("st.relaxed.gpu.global.v2.u32 [%0], {%1,%2};" ::"l"(p), "r"(a), "r"(b) : "memory");
}
__device__ __forceinline__ void mma_bf16(float (&c)[4], uint32_t a0, uint32_t a2, uint32_t b0, uint32_t b1) {
  asm volatile("mma.sync.aligned.m16n8k16.row.col.f32.bf16.bf16.f32 {%0,%1,%2,%3}, {%4,%5,%6,%5}, {%7,%8}, {%0,%1,%2,%3};"
               : "+f"(c[0]), "+f"(c[1]), "+f"(c[2]), "+f"(c[3]) : "r"(a0), "r"(0u), "r"(a2), "r"(b0), "r"(b1));
}
__device__ __forceinline__ void mbar_wait(const unsigned long long* bar) {
  const uint32_t mb = smem_u32(bar);
  uint32_t ok = 0;
  int it = 0;
  while (!ok && ++it < SPIN_LIMIT)
    asm volatile("{ .reg .pred p; mbarrier.try_wait.parity.shared.b64 p, [%1], 0; selp.u32 %0, 1, 0, p; }" : "=r"(ok) : "r"(mb) : "memory");
}
__device__ __forceinline__ void bulk_g2s(void* dst, const void* src, uint32_t bytes, const unsigned long long* bar) {
  asm volatile("cp.async.bulk.shared::cluster.global.mbarrier::complete_tx::bytes [%0], [%1], %2, [%3];" ::"r"(smem_u32(dst)),
               "l"(src), "r"(bytes), "r"(smem_u32(bar)) : "memory");
}
__device__ __forceinline__ void mbar_expect(const unsigned long long* bar, uint32_t bytes) {
  asm volatile("mbarrier.arrive.expect_tx.shared.b64 _, [%0], %1;" ::"r"(smem_u32(bar)), "r"(bytes) : "memory");
}
__device__ __forceinline__ void mma_bf16x(float (&c)[4], uint32_t a0, uint32_t a1, uint32_t a2, uint32_t a3, uint32_t b0, uint32_t b1) {
  asm volatile("mma.sync.aligned.m16n8k16.row.col.f32.bf16.bf16.f32 {%0,%1,%2,%3}, {%4,%5,%6,%7}, {%8,%9}, {%0,%1,%2,%3};"
               : "+f"(c[0]), "+f"(c[1]), "+f"(c[2]), "+f"(c[3]) : "r"(a0), "r"(a1), "r"(a2), "r"(a3), "r"(b0), "r"(b1));
}
__device__ __forceinline__ float fdivr(float a, float d, float r) {
  float q = a * r;
  float e = fmaf(-q, d, a);
  return fmaf(e, r, q);
}

template <bool FIRST> __device__ __forceinline__ void wgmma32(float (&d)[16], const uint32_t* a, uint64_t desc) {
  if (FIRST) {
    asm volatile("wgmma.mma_async.sync.aligned.m64n32k16.f32.bf16.bf16 {%0,%1,%2,%3,%4,%5,%6,%7,%8,%9,%10,%11,%12,%13,%14,%15}, {%16,%17,%18,%19}, %20, 0, 1, 1, 0;"
                 : "+f"(d[0]), "+f"(d[1]), "+f"(d[2]), "+f"(d[3]), "+f"(d[4]), "+f"(d[5]), "+f"(d[6]), "+f"(d[7]),
                   "+f"(d[8]), "+f"(d[9]), "+f"(d[10]), "+f"(d[11]), "+f"(d[12]), "+f"(d[13]), "+f"(d[14]), "+f"(d[15])
                 : "r"(a[0]), "r"(a[1]), "r"(a[2]), "r"(a[3]), "l"(desc));
  } else {
    asm volatile("wgmma.mma_async.sync.aligned.m64n32k16.f32.bf16.bf16 {%0,%1,%2,%3,%4,%5,%6,%7,%8,%9,%10,%11,%12,%13,%14,%15}, {%16,%17,%18,%19}, %20, 1, 1, 1, 0;"
                 : "+f"(d[0]), "+f"(d[1]), "+f"(d[2]), "+f"(d[3]), "+f"(d[4]), "+f"(d[5]), "+f"(d[6]), "+f"(d[7]),
                   "+f"(d[8]), "+f"(d[9]), "+f"(d[10]), "+f"(d[11]), "+f"(d[12]), "+f"(d[13]), "+f"(d[14]), "+f"(d[15])
                 : "r"(a[0]), "r"(a[1]), "r"(a[2]), "r"(a[3]), "l"(desc));
  }
}

template <int G> __device__ __forceinline__ void load_a(uint32_t (&a)[8], const uint32_t* tp) {
#pragma unroll
  for (int q = 0; q < 2; q++) {
    const int e = 2 * G + q;
    a[4 * q + 0] = tp[-64 * e];
    a[4 * q + 1] = tp[-64 * e - 32];
    a[4 * q + 2] = tp[-64 * e + 4];
    a[4 * q + 3] = tp[-64 * e - 28];
  }
}
__device__ __forceinline__ void load_a_all(uint32_t (&a)[8][8], const uint32_t* tp) {
  load_a<0>(a[0], tp); load_a<1>(a[1], tp); load_a<2>(a[2], tp); load_a<3>(a[3], tp);
  load_a<4>(a[4], tp); load_a<5>(a[5], tp); load_a<6>(a[6], tp); load_a<7>(a[7], tp);
}
template <int G> __device__ __forceinline__ void issue_g(float (&acc)[8][16], uint32_t (&a)[8], uint64_t desc0) {
  wg_fence();
#pragma unroll
  for (int q = 0; q < 2; q++) {
#pragma unroll
    for (int b = G; b < 8; b++) {
      const int delta = 2 * b - (2 * G + q);
      if (G == 0 && q == 0) wgmma32<true>(acc[b], &a[4 * q], desc0 + (uint64_t)(int64_t)(16 * delta));
      else wgmma32<false>(acc[b], &a[4 * q], desc0 + (uint64_t)(int64_t)(16 * delta));
    }
  }
  wg_commit();
}
template <int B> __device__ __forceinline__ void fence_blk(float (&acc)[8][16]) {
#pragma unroll
  for (int i = 0; i < 16; i++) asm volatile("" : "+f"(acc[B][i])::"memory");
}
__device__ __forceinline__ void fence_a(uint32_t (&a)[8]) {
#pragma unroll
  for (int i = 0; i < 8; i++) asm volatile("" : "+r"(a[i])::"memory");
}
template <int B> __device__ __forceinline__ void sts_blk(float (&acc)[8][16], float* zw, int off_even, int off_odd) {
#pragma unroll
  for (int jj = 0; jj < 4; jj++) {
    const int j = 4 * B + jj;
    float p0 = acc[B][4 * jj + 0], p1 = acc[B][4 * jj + 1];
    if (jj > 0) { p0 += acc[B][4 * (jj - 1) + 2]; p1 += acc[B][4 * (jj - 1) + 3]; }
    else if (B > 0) { p0 += acc[B > 0 ? B - 1 : 0][14]; p1 += acc[B > 0 ? B - 1 : 0][15]; }
    zw[64 * j + off_even] = p0;
    zw[64 * j + off_odd] = p1;
  }
}
__device__ __forceinline__ int tab_off(int c) { return c == 4 ? 0 : (c + 1) * 2 * TABW + (c >= 2 ? 1024 : 0); }
__device__ __forceinline__ int tile_perm(int ch) { return ch ^ (((ch >> 3) & 3) << 1); }

__device__ __forceinline__ void wait_ctr(const unsigned int* ctr, uint32_t target) {
  uint32_t v;
  int it = 0;
  do {
    asm volatile("ld.acquire.gpu.global.u32 %0, [%1];" : "=r"(v) : "l"(ctr) : "memory");
  } while ((int)(v - target) < 0 && ++it < SPIN_LIMIT);
}

__device__ __forceinline__ float2 row_part_stats(const uint32_t (&x)[16]) {
  float cs[4][4];
#pragma unroll
  for (int k = 0; k < 4; k++) {
    cs[k][0] = cs[k][1] = cs[k][2] = cs[k][3] = 0.f;
    mma_bf16x(cs[k], x[4 * k + 0], x[4 * k + 2], x[4 * k + 1], x[4 * k + 3], 0x3F803F80u, 0x3F803F80u);
  }
  const float mean = (((cs[0][0] + cs[0][2]) + (cs[1][0] + cs[1][2])) + ((cs[2][0] + cs[2][2]) + (cs[3][0] + cs[3][2]))) * (1.f / 128.f);
  float m2a = 0.f, m2b = 0.f, m2c = 0.f, m2d = 0.f;
#pragma unroll
  for (int i = 0; i < 16; i += 2) {
    const float a = lo_f(x[i]) - mean, b = hi_f(x[i]) - mean, c = lo_f(x[i + 1]) - mean, d = hi_f(x[i + 1]) - mean;
    m2a = fmaf(a, a, m2a); m2b = fmaf(b, b, m2b); m2c = fmaf(c, c, m2c); m2d = fmaf(d, d, m2d);
  }
  float m2 = (m2a + m2b) + (m2c + m2d);
  m2 += __shfl_xor_sync(0xffffffffu, m2, 1);
  m2 += __shfl_xor_sync(0xffffffffu, m2, 2);
  return make_float2(mean, m2);
}
__device__ __forceinline__ void row_normalize(const float2* st, const uint32_t (&x)[16], uint32_t (&y)[16]) {
  float mean = 0.f, m2 = 0.f;
  float2 p[5];
#pragma unroll
  for (int i = 0; i < 5; i++) { p[i] = st[i]; mean += p[i].x; }
  mean *= 0.2f;
#pragma unroll
  for (int i = 0; i < 5; i++) { const float dl = p[i].x - mean; m2 += p[i].y + 128.f * dl * dl; }
  const float hd = rbf(sqrtf(rbf(rbf(m2 * (1.f / D_)) + 1e-5f)));
  const float hr = 1.f / hd;
  const bf162 hm2 = __float2bfloat162_rn(mean);
#pragma unroll
  for (int i = 0; i < 16; i++) {
    const uint32_t d = b2u(__hsub2_rn(u2b(x[i]), hm2));
    y[i] = pack2(fdivr(lo_f(d), hd, hr), fdivr(hi_f(d), hd, hr));
  }
}

__global__ void __launch_bounds__(NTHR, 1)
fused_kernel(const __grid_constant__ CUtensorMap tmg, const __grid_constant__ CUtensorMap tmu,
             const __grid_constant__ CUtensorMap tmd, const bf16* __restrict__ gq, const bf16* __restrict__ gk, const bf16* __restrict__ gv,
             const bf16* __restrict__ gsk, const bf16* __restrict__ gh, const bf16* __restrict__ gD,
             const bf16* __restrict__ gwr, bf16* __restrict__ gout) {
  extern __shared__ __align__(128) unsigned char smraw[];
  Smem& sm = *reinterpret_cast<Smem*>(smraw);
  const int tid = threadIdx.x;
  const int cta = blockIdx.x;
  const int c0 = cta * CPC;
  const int lane = tid & 31;
  const int wid = tid >> 5;
  STAMP(0);
  const long long tstart = clock64();

  {
    uint4* hs = reinterpret_cast<uint4*>(&sm.z[0][0][0]);
    const int oc = tid >> 2;
    const int r0 = cta * 16 + (tid & 3) * 4;
    uint4 kk[7], vv[4], sk[4];
    if (tid < 320) {
      const uint4* kp = reinterpret_cast<const uint4*>(gk) + (size_t)r0 * 80 + oc;
      const uint4* vp = reinterpret_cast<const uint4*>(gv) + (size_t)r0 * 80 + oc;
#pragma unroll
      for (int i = 0; i < 7; i++) kk[i] = (i >= 3 || r0 > 0) ? __ldg(kp + (i - 3) * 80) : make_uint4(0, 0, 0, 0);
#pragma unroll
      for (int i = 0; i < 4; i++) vv[i] = __ldg(vp + i * 80);
#pragma unroll
      for (int i = 0; i < 4; i++) sk[i] = __ldg(reinterpret_cast<const uint4*>(gsk) + oc * 4 + i);
    } else if (tid == 320) {
      asm volatile("mbarrier.init.shared.b64 [%0], 1;" ::"r"(smem_u32(&sm.mbarh)) : "memory");
      asm volatile("mbarrier.init.shared.b64 [%0], 1;" ::"r"(smem_u32(&sm.mbar)) : "memory");
      asm volatile("mbarrier.init.shared.b64 [%0], 1;" ::"r"(smem_u32(&sm.mbarw)) : "memory");
      asm volatile("mbarrier.init.shared.b64 [%0], 1;" ::"r"(smem_u32(&sm.mbarc)) : "memory");
      asm volatile("fence.proxy.async.shared::cta;" ::: "memory");
    }
    if (tid < 320) bar_sync(6, 384); else { bar_arrive(6, 384); bar_sync(5, 64); }
    STAMP(9);
    if (tid < 320) {
      uint32_t o[4][4];
#pragma unroll
      for (int p = 0; p < 4; p++) {
        const bf162 w0 = u2b(__byte_perm(sk[p].x, sk[p].z, 0x5410)), w1 = u2b(__byte_perm(sk[p].x, sk[p].z, 0x7632));
        const bf162 w2 = u2b(__byte_perm(sk[p].y, sk[p].w, 0x5410)), w3 = u2b(__byte_perm(sk[p].y, sk[p].w, 0x7632));
        uint32_t kv[4];
#pragma unroll
        for (int i = 0; i < 4; i++) {
          const uint32_t k0 = p == 0 ? kk[i].x : p == 1 ? kk[i].y : p == 2 ? kk[i].z : kk[i].w;
          const uint32_t k1 = p == 0 ? kk[i + 1].x : p == 1 ? kk[i + 1].y : p == 2 ? kk[i + 1].z : kk[i + 1].w;
          const uint32_t k2 = p == 0 ? kk[i + 2].x : p == 1 ? kk[i + 2].y : p == 2 ? kk[i + 2].z : kk[i + 2].w;
          const uint32_t k3 = p == 0 ? kk[i + 3].x : p == 1 ? kk[i + 3].y : p == 2 ? kk[i + 3].z : kk[i + 3].w;
          const uint32_t vx = p == 0 ? vv[i].x : p == 1 ? vv[i].y : p == 2 ? vv[i].z : vv[i].w;
          bf162 a = __hmul2_rn(u2b(k0), w3);
          a = __hadd2_rn(a, __hmul2_rn(u2b(k1), w2));
          a = __hadd2_rn(a, __hmul2_rn(u2b(k2), w1));
          a = __hadd2_rn(a, __hmul2_rn(u2b(k3), w0));
          kv[i] = b2u(__hmul2_rn(a, u2b(vx)));
        }
        o[p][0] = enc(__byte_perm(kv[0], kv[1], 0x5410)); o[p][1] = enc(__byte_perm(kv[2], kv[3], 0x5410));
        o[p][2] = enc(__byte_perm(kv[0], kv[1], 0x7632)); o[p][3] = enc(__byte_perm(kv[2], kv[3], 0x7632));
      }
      uint2* dst = reinterpret_cast<uint2*>(g_kv) + (size_t)(oc * 8) * 512 + (r0 >> 2);
#pragma unroll
      for (int p = 0; p < 4; p++) {
        st_pub2(dst + (2 * p) * 512, o[p][0], o[p][1]);
        st_pub2(dst + (2 * p + 1) * 512, o[p][2], o[p][3]);
      }
      STAMP(10);
      if (wid == 0) bar_sync(4, 320); else bar_arrive(4, 320);
      if (tid == 0) {
        const unsigned old = atomicAdd(&g_ctr2, 1u);
        const unsigned target = (old / NCTA + 1u) * NCTA;
        uint32_t v;
        int it = 0;
        do {
          if (CTR_NS) __nanosleep(CTR_NS);
          asm volatile("ld.relaxed.gpu.global.u32 %0, [%1];" : "=r"(v) : "l"(&g_ctr2) : "memory");
        } while ((int)(v - target) < 0 && ++it < SPIN_LIMIT);
        asm volatile("mbarrier.arrive.shared.b64 _, [%0];" ::"r"(smem_u32(&sm.mbarc)) : "memory");
      }
      __syncwarp();
    } else {
      const int t0 = tid - 320;
      const uint4 zz = make_uint4(0, 0, 0, 0);
      if (tid == 320) {
        while (clock64() - tstart < H_DELAY) {}
        mbar_expect(&sm.mbarh, CPC * S_ * 2);
        bulk_g2s(hs, gh + (size_t)c0 * S_, CPC * S_ * 2, &sm.mbarh);
      }
      __syncwarp();
      for (int t = t0; t < CPC * 17; t += 64) *reinterpret_cast<uint4*>(&sm.u[t / 17][(t % 17) * 8]) = zz;
      if (t0 < 40) *reinterpret_cast<uint4*>(&sm.tabA[0][0][0] + tab_off(t0 >> 3) + ((t0 >> 2) & 1) * TABW + 1024 + 4 * (t0 & 3)) = zz;
#pragma unroll 4
      for (int i = 0; i < 20; i++) g_y2[cta * 1280 + t0 + 64 * i] = zz;
      (&g_cand[cta][0][0])[t0] = zz;
      (&g_cand[cta][0][0])[64 + t0] = zz;
      if (t0 < 32) (&g_cand[cta][0][0])[128 + t0] = zz;
      else reinterpret_cast<uint4*>(&g_keys[cta][0])[t0 - 32] = zz;
      if (cta >= N1 && cta < N1 + N2) {
#pragma unroll
        for (int i = 0; i < 3; i++) g_act[cta - N1][t0 + 64 * i] = zz;
      }
      bar_sync(5, 64);
      if (tid == 352) {
        __threadfence();
        const unsigned old = atomicAdd(&g_ctr, 1u);
        sm.target = (old / NCTA + 1u) * NCTA;
      }
      __syncwarp();
    }
    mbar_wait(&sm.mbarh);
#pragma unroll
    for (int i = 0; i < 4; i++) {
      const int t = (NTHR - 1 - tid) + NTHR * i;
      if (t < CPC * 256) {
        uint32_t* tb = &sm.tabA[0][0][0] + tab_off(t >> 8) + (255 - (t & 255)) * 4;
        const uint4 h = hs[t];
        const uint32_t hp = (t & 255) ? reinterpret_cast<const uint32_t*>(hs)[4 * t - 1] : 0u;
        uint4 r1, rr;
        r1.x = __byte_perm(h.w, 0, 0x1032); r1.y = __byte_perm(h.z, 0, 0x1032);
        r1.z = __byte_perm(h.y, 0, 0x1032); r1.w = __byte_perm(h.x, 0, 0x1032);
        rr.x = __byte_perm(h.w, h.z, 0x7610); rr.y = __byte_perm(h.z, h.y, 0x7610);
        rr.z = __byte_perm(h.y, h.x, 0x7610); rr.w = __byte_perm(h.x, hp, 0x7610);
        *reinterpret_cast<uint4*>(tb) = rr;
        *reinterpret_cast<uint4*>(tb + TABW) = r1;
      }
    }
    STAMP(12);
  }
  mbar_wait(&sm.mbarc);
  {
    uint4 v[4];
    uint4* src = g_kv + c0 * 256 + tid;
#pragma unroll
    for (int i = 0; i < 4; i++) if (i < 3 || tid < 128) v[i] = ld_poll4(src + NTHR * i);
#pragma unroll
    for (int i = 0; i < 4; i++) {
      if (i < 3 || tid < 128) {
        int it = 0;
        while (!ready4(v[i]) && ++it < SPIN_LIMIT) { __nanosleep(POLL_NS); v[i] = ld_poll4(src + NTHR * i); }
        const int t = tid + NTHR * i;
        *reinterpret_cast<uint4*>(&sm.u[t >> 8][UPAD + (t & 255) * 8]) = make_uint4(~v[i].x, ~v[i].y, ~v[i].z, ~v[i].w);
      }
    }
    STAMP(11);
    asm volatile("fence.proxy.async.shared::cta;" ::: "memory");
    __syncthreads();
#pragma unroll
    for (int i = 0; i < 4; i++) if (i < 3 || tid < 128) src[NTHR * i] = make_uint4(0, 0, 0, 0);
    if (tid >= 256) {
      const int t0 = tid - 256;
      if (((t0 & 15) >> 2) < ((t0 >> 4) & 3))
        *reinterpret_cast<uint4*>(&sm.z[t0 >> 6][(t0 >> 4) & 3][(t0 & 15) * 4]) = make_uint4(0, 0, 0, 0);
    }
  }
  STAMP(1);
  if (ABL == 5) return;

  const int wg = __shfl_sync(0xffffffffu, tid >> 7, 0);
  const int wtid = tid & 127;
  uint4* tile = reinterpret_cast<uint4*>(&sm.tabB[0][0][0]);
  if (wg < 2) {
    asm volatile("setmaxnreg.inc.sync.aligned.u32 224;");
    const int w = (tid >> 5) & 3, g = lane >> 2, tq = lane & 3;
    float* zw = sm.z[wg][w];
    const int sw = 3 * (((tq + w) >> 1) & 1);
    const int off_even = 16 * (tq + w) + 4 * ((0 + (g >> 2)) ^ sw) + (g & 3);
    const int off_odd = 16 * (tq + w) + 4 * ((2 + (g >> 2)) ^ sw) + (g & 3);
    uint32_t a[8][8];
    const uint32_t* tp0 = &sm.tabA[0][g & 1][1019 - 8 * w - (g >> 1) + tq];
    load_a_all(a, tp0 + tab_off(wg));
    float acc[8][16];
#pragma unroll
    for (int b = 0; b < 8; b++)
#pragma unroll
      for (int i = 0; i < 16; i++) acc[b][i] = 0.f;
#pragma unroll 1
    for (int c = wg; c < CPC; c += 2) {
      const uint64_t desc = (uint64_t)((smem_u32(&sm.u[c][UPAD - 8]) & 0x3FFFF) >> 4) | ((uint64_t)1 << 16) | ((uint64_t)8 << 32);
      CST(c, 0);
      if (c > 0) bar_sync(1 + wg, 256);
      issue_g<0>(acc, a[0], desc);
      CST(c, 1);
      issue_g<1>(acc, a[1], desc);
      issue_g<2>(acc, a[2], desc);
      issue_g<3>(acc, a[3], desc);
      issue_g<4>(acc, a[4], desc);
      issue_g<5>(acc, a[5], desc);
      if (c + 1 < CPC) bar_arrive(1 + (wg ^ 1), 256);
      issue_g<6>(acc, a[6], desc);
      issue_g<7>(acc, a[7], desc);
      CST(c, 2);
      if (c >= 2) bar_sync(5 + wg, 256);
      wg_wait<4>();
      fence_blk<0>(acc); fence_blk<1>(acc); fence_blk<2>(acc); fence_blk<3>(acc);
      sts_blk<0>(acc, zw, off_even, off_odd);
      sts_blk<1>(acc, zw, off_even, off_odd);
      sts_blk<2>(acc, zw, off_even, off_odd);
      sts_blk<3>(acc, zw, off_even, off_odd);
      CST(c, 3);
      wg_wait<0>();
      fence_blk<4>(acc); fence_blk<5>(acc); fence_blk<6>(acc); fence_blk<7>(acc);
#pragma unroll
      for (int i = 0; i < 8; i++) fence_a(a[i]);
      sts_blk<4>(acc, zw, off_even, off_odd);
      sts_blk<5>(acc, zw, off_even, off_odd);
      sts_blk<6>(acc, zw, off_even, off_odd);
      sts_blk<7>(acc, zw, off_even, off_odd);
      bar_arrive(3 + wg, 256);
      CST(c, 4);
      if (c + 2 < CPC) load_a_all(a, tp0 + tab_off(c + 2));
    }
    STAMP(2 + wg);
    asm volatile("setmaxnreg.dec.sync.aligned.u32 168;");
  } else {
    asm volatile("setmaxnreg.dec.sync.aligned.u32 56;");
    if (wtid == 32) {
      const uint32_t mw = smem_u32(&sm.mbarw);
      mbar_expect(&sm.mbar, 17 * D_ * 2);
#pragma unroll 1
      for (int r = 0; r < 16; r++) bulk_g2s(&sm.q[r][0], gq + (size_t)(cta * 16 + r) * D_, D_ * 2, &sm.mbar);
      bulk_g2s(&sm.wr[0], gwr, D_ * 2, &sm.mbar);
      if (cta < N1) {
        asm volatile("mbarrier.arrive.expect_tx.shared.b64 _, [%0], %1;" ::"r"(mw), "r"(3840 * 16) : "memory");
#pragma unroll 1
        for (int i = 0; i < 4; i++) {
          asm volatile("cp.async.bulk.tensor.2d.shared::cluster.global.mbarrier::complete_tx::bytes [%0], [%1, {%3, %4}], [%2];" ::"r"(smem_u32(&sm.w[i * 480])),
                       "l"(&tmg), "r"(mw), "r"(cta * 24), "r"(i * 160) : "memory");
          asm volatile("cp.async.bulk.tensor.2d.shared::cluster.global.mbarrier::complete_tx::bytes [%0], [%1, {%3, %4}], [%2];" ::"r"(smem_u32(&sm.w[1920 + i * 480])),
                       "l"(&tmu), "r"(mw), "r"(cta * 24), "r"(i * 160) : "memory");
        }
      } else if (cta < N1 + N2) {
        asm volatile("mbarrier.arrive.expect_tx.shared.b64 _, [%0], %1;" ::"r"(mw), "r"(3072 * 16) : "memory");
#pragma unroll 1
        for (int i = 0; i < 6; i++)
          asm volatile("cp.async.bulk.tensor.2d.shared::cluster.global.mbarrier::complete_tx::bytes [%0], [%1, {%3, %4}], [%2];" ::"r"(smem_u32(&sm.w[i * 512])),
                       "l"(&tmd), "r"(mw), "r"((cta - N1) * 16), "r"(i * 256) : "memory");
      }
    }
    if (wtid == 0) wait_ctr(&g_ctr, sm.target);
    const int rpb = wtid >> 1, re2 = wtid & 1;
    const int rsw = 3 * ((rpb >> 1) & 1);
    const int roff0 = 16 * rpb + 4 * ((2 * re2 + 0) ^ rsw);
    const int roff1 = 16 * rpb + 4 * ((2 * re2 + 1) ^ rsw);
    const uint32_t dvl = reinterpret_cast<const unsigned short*>(gD)[c0 + (lane < CPC ? lane : 0)];
#pragma unroll 1
    for (int c = 0; c < CPC; c++) {
      const int zg = c & 1;
      const uint32_t dvc = __shfl_sync(0xffffffffu, dvl, c);
      const bf162 d2 = u2b(dvc | (dvc << 16));
      CST(c, 5);
      bar_sync(3 + zg, 256);
#pragma unroll
      for (int half = 0; half < 2; half++) {
        const float* zb = sm.z[zg][0] + half * 1024;
        float4 x[4][2];
#pragma unroll
        for (int ww = 0; ww < 4; ww++) {
          x[ww][0] = *reinterpret_cast<const float4*>(zb + ww * ZPB * 16 + roff0);
          x[ww][1] = *reinterpret_cast<const float4*>(zb + ww * ZPB * 16 + roff1);
        }
        const int sidx = half * 1024 + wtid * 8;
        const uint4 kvv = *reinterpret_cast<const uint4*>(&sm.u[c][UPAD + sidx]);
        if (half == 1 && c + 2 < CPC) bar_arrive(5 + zg, 256);
        uint4 o;
        o.x = pack2((x[0][0].x + x[1][0].x) + (x[2][0].x + x[3][0].x), (x[0][0].y + x[1][0].y) + (x[2][0].y + x[3][0].y));
        o.y = pack2((x[0][0].z + x[1][0].z) + (x[2][0].z + x[3][0].z), (x[0][0].w + x[1][0].w) + (x[2][0].w + x[3][0].w));
        o.z = pack2((x[0][1].x + x[1][1].x) + (x[2][1].x + x[3][1].x), (x[0][1].y + x[1][1].y) + (x[2][1].y + x[3][1].y));
        o.w = pack2((x[0][1].z + x[1][1].z) + (x[2][1].z + x[3][1].z), (x[0][1].w + x[1][1].w) + (x[2][1].w + x[3][1].w));
        o.x = b2u(__hadd2_rn(u2b(o.x), __hmul2_rn(u2b(kvv.x), d2)));
        o.y = b2u(__hadd2_rn(u2b(o.y), __hmul2_rn(u2b(kvv.y), d2)));
        o.z = b2u(__hadd2_rn(u2b(o.z), __hmul2_rn(u2b(kvv.z), d2)));
        o.w = b2u(__hadd2_rn(u2b(o.w), __hmul2_rn(u2b(kvv.w), d2)));
        st_pub4(g_y2 + ((64 * half + rpb) * 640 + c0 + c) * 2 + re2, enc4(o));
        CST(c, 6 + half);
      }
    }
    STAMP(4);
    asm volatile("setmaxnreg.inc.sync.aligned.u32 168;");
  }

  if (ABL == 4) { if (cta < N1 + N2) mbar_wait(&sm.mbarw); mbar_wait(&sm.mbar); return; }
  const int g = lane >> 2, tq = lane & 3;
  const int hh = wid & 1, gqi = wid >> 1;
  const int row = hh * 8 + g;
  uint32_t hreg[16], hnreg[16];
  {
    const uint4* src = g_y2 + cta * 1280 + tid;
    uint4 v[4];
#pragma unroll
    for (int i = 0; i < 4; i++) if (i < 3 || tid < 128) v[i] = ld_poll4(src + NTHR * i);
    if (wid < 10) {
      mbar_wait(&sm.mbar);
#pragma unroll
      for (int k = 0; k < 4; k++) {
        const uint4 qv4 = *reinterpret_cast<const uint4*>(&sm.q[row][32 * (4 * gqi + k) + 8 * tq]);
        hreg[4 * k] = qv4.x; hreg[4 * k + 1] = qv4.y; hreg[4 * k + 2] = qv4.z; hreg[4 * k + 3] = qv4.w;
      }
      const float2 ps = row_part_stats(hreg);
      if (tq == 0) sm.stq[row][gqi] = ps;
      bar_sync(7, 320);
      row_normalize(sm.stq[row], hreg, hnreg);
    }
    int it = 0;
    bool all;
    do {
      all = true;
#pragma unroll
      for (int i = 0; i < 4; i++)
        if ((i < 3 || tid < 128) && !ready4(v[i])) { v[i] = ld_poll4(src + NTHR * i); all = false; }
    } while (!all && ++it < SPIN_LIMIT);
#pragma unroll
    for (int i = 0; i < 4; i++) {
      if (i < 3 || tid < 128) {
        const int t = tid + NTHR * i;
        tile[(t & 1) * 640 + tile_perm(t >> 1)] = make_uint4(~v[i].x, ~v[i].y, ~v[i].z, ~v[i].w);
      }
    }
  }
  __syncthreads();
  STAMP(5);
  if (ABL == 3) { if (cta < N1 + N2) mbar_wait(&sm.mbarw); return; }

  if (wid < 10) {
#pragma unroll
    for (int k = 0; k < 4; k++) {
      const int base = 32 * (4 * gqi + k);
      const int lch = base + 8 * ((lane & 7) >> 1) + 2 * (lane >> 3) + (lane & 1);
      uint32_t y[4];
      asm volatile("ldmatrix.sync.aligned.m8n8.x4.trans.shared.b16 {%0,%1,%2,%3}, [%4];"
                   : "=r"(y[0]), "=r"(y[1]), "=r"(y[2]), "=r"(y[3]) : "r"(smem_u32(&tile[hh * 640 + tile_perm(lch)])) : "memory");
#pragma unroll
      for (int i = 0; i < 4; i++)
        hreg[4 * k + i] = b2u(__hadd2_rn(u2b(hreg[4 * k + i]), __hmul2_rn(u2b(hnreg[4 * k + i]), u2b(y[i]))));
    }
    const float2 ps = row_part_stats(hreg);
    if (tq == 0) sm.st[row][gqi] = ps;
    STAMP(13);
    bar_sync(7, 320);
    row_normalize(sm.st[row], hreg, hnreg);
    float cr[4][4];
#pragma unroll
    for (int k = 0; k < 4; k++) {
      cr[k][0] = cr[k][1] = cr[k][2] = cr[k][3] = 0.f;
      const uint4 w4 = sm.wr[4 * (4 * gqi + k) + tq];
      mma_bf16(cr[k], hnreg[4 * k + 0], hnreg[4 * k + 1], w4.x, w4.y);
      mma_bf16(cr[k], hnreg[4 * k + 2], hnreg[4 * k + 3], w4.z, w4.w);
    }
    if (tq == 0) sm.rp[row][gqi] = (cr[0][0] + cr[1][0]) + (cr[2][0] + cr[3][0]);
  }
  STAMP(14);
  __syncthreads();
  uint32_t best;
  {
    const int rr = lane & 15;
    const float r = ((sm.rp[rr][0] + sm.rp[rr][1]) + (sm.rp[rr][2] + sm.rp[rr][3])) + sm.rp[rr][4];
    const uint32_t bits = __bfloat16_as_ushort(__float2bfloat16_rn(r));
    const uint32_t ord = (bits & 0x8000u) ? (bits ^ 0xFFFFu) : (bits ^ 0x8000u);
    const uint32_t key = (ord << 16) | 0x8000u | (uint32_t)(2047 - (cta * 16 + rr));
    best = __reduce_max_sync(0xffffffffu, key);
  }
  if (wid >= 8) asm volatile("st.relaxed.gpu.global.u32 [%0], %1;" ::"l"(&g_keys[tid - 256][cta]), "r"(best) : "memory");
  STAMP(15);
  const int brow = (2047 - (int)(best & 0x7FFu)) - cta * 16;
  if (wid < 10 && row == brow) {
#pragma unroll
    for (int k = 0; k < 4; k++)
      st_pub4(&g_cand[cta][0][4 * (4 * gqi + k) + tq], enc4(make_uint4(hnreg[4 * k], hnreg[4 * k + 1], hnreg[4 * k + 2], hnreg[4 * k + 3])));
#pragma unroll
    for (int k = 0; k < 4; k++)
      st_pub4(&g_cand[cta][1][4 * (4 * gqi + k) + tq], enc4(make_uint4(hreg[4 * k], hreg[4 * k + 1], hreg[4 * k + 2], hreg[4 * k + 3])));
  }
#pragma unroll
  for (int i = 0; i < 16; i++) hreg[i] = b2u(__hadd2_rn(u2b(hreg[i]), u2b(hnreg[i])));
  STAMP(6);
  if (ABL == 2) { if (cta < N1 + N2) mbar_wait(&sm.mbarw); return; }
  if (wid == 11) {
    const uint4* kp = reinterpret_cast<const uint4*>(&g_keys[cta][0]) + lane;
    uint4 v = ld_poll4(kp);
    int it = 0;
    while (!ready4(v) && ++it < SPIN_LIMIT) v = ld_poll4(kp);
    const uint32_t m = max(max(v.x, v.y), max(v.z, v.w));
    const uint32_t wk = __reduce_max_sync(0xffffffffu, m);
    if (lane == 0) sm.win = wk;
  }
  __syncthreads();
  const uint32_t win = sm.win;
  const int wrow = 2047 - (int)(win & 0x7FFu);
  const int wcta = wrow >> 4;
  const bool st_out = wid < 10 && (cta * 16 + row) != wrow;
  uint4* outp = reinterpret_cast<uint4*>(gout + (size_t)(cta * 16 + row) * D_) + 16 * gqi + tq;
  if (cta >= N1 && st_out) {
#pragma unroll
    for (int k = 0; k < 4; k++) outp[4 * k] = make_uint4(hreg[4 * k], hreg[4 * k + 1], hreg[4 * k + 2], hreg[4 * k + 3]);
  }
  STAMP(7);
  if (ABL == 1) { if (cta < N1 + N2) mbar_wait(&sm.mbarw); return; }
  if (cta < N1 + N2) mbar_wait(&sm.mbarw);
  float* xs = &sm.z[0][0][0];
  float* part = xs + 2048;
  if (cta < N1) {
    if (tid < 80) {
      const uint4 v = poll4(&g_cand[wcta][0][tid]);
      float4* xp = reinterpret_cast<float4*>(xs + tid * 8);
      xp[0] = make_float4(lo_f(v.x), hi_f(v.x), lo_f(v.y), hi_f(v.y));
      xp[1] = make_float4(lo_f(v.z), hi_f(v.z), lo_f(v.w), hi_f(v.w));
    }
    __syncthreads();
    const int m = wid / 6, hc = (wid % 6) >> 1, rs = (wid & 1) * 32 + lane;
    float a[8];
#pragma unroll
    for (int j = 0; j < 8; j++) a[j] = 0.f;
#pragma unroll
    for (int it = 0; it < 10; it++) {
      const int r = rs + 64 * it;
      const uint4 wv = sm.w[m * 1920 + r * 3 + hc];
      const float x = xs[r];
      a[0] = fmaf(x, lo_f(wv.x), a[0]); a[1] = fmaf(x, hi_f(wv.x), a[1]);
      a[2] = fmaf(x, lo_f(wv.y), a[2]); a[3] = fmaf(x, hi_f(wv.y), a[3]);
      a[4] = fmaf(x, lo_f(wv.z), a[4]); a[5] = fmaf(x, hi_f(wv.z), a[5]);
      a[6] = fmaf(x, lo_f(wv.w), a[6]); a[7] = fmaf(x, hi_f(wv.w), a[7]);
    }
    {
      const bool up = lane & 16;
#pragma unroll
      for (int j = 0; j < 4; j++) {
        const float send = up ? a[j] : a[j + 4], keep = up ? a[j + 4] : a[j];
        a[j] = keep + __shfl_xor_sync(0xffffffffu, send, 16);
      }
      const bool up2 = lane & 8;
#pragma unroll
      for (int j = 0; j < 2; j++) {
        const float send = up2 ? a[j] : a[j + 2], keep = up2 ? a[j + 2] : a[j];
        a[j] = keep + __shfl_xor_sync(0xffffffffu, send, 8);
      }
      const bool up3 = lane & 4;
      const float send = up3 ? a[0] : a[1], keep = up3 ? a[1] : a[0];
      a[0] = keep + __shfl_xor_sync(0xffffffffu, send, 4);
      a[0] += __shfl_xor_sync(0xffffffffu, a[0], 2);
      a[0] += __shfl_xor_sync(0xffffffffu, a[0], 1);
      if ((lane & 3) == 0) part[wid * 8 + (lane >> 2)] = a[0];
    }
    __syncthreads();
    if (wid == 0) {
      uint32_t bits = 0;
      if (lane < 24) {
        const int hc2 = lane >> 3, j = lane & 7;
        const float gt = rbf(part[(2 * hc2) * 8 + j] + part[(2 * hc2 + 1) * 8 + j]);
        const float up = rbf(part[(6 + 2 * hc2) * 8 + j] + part[(6 + 2 * hc2 + 1) * 8 + j]);
        const float sg = rbf(gt / (1.f + __expf(-gt)));
        bits = __bfloat16_as_ushort(__float2bfloat16_rn(sg * up));
      }
      const uint32_t nb = __shfl_down_sync(0xffffffffu, bits, 1);
      const uint32_t pw = bits | (nb << 16);
      const uint32_t w1 = __shfl_down_sync(0xffffffffu, pw, 2), w2 = __shfl_down_sync(0xffffffffu, pw, 4), w3 = __shfl_down_sync(0xffffffffu, pw, 6);
      const uint4 mine = enc4(make_uint4(pw, w1, w2, w3));
#pragma unroll
      for (int i = 0; i < 4; i++) {
        const int t = lane + 32 * i;
        const int cons = t / 3, ck = t - 3 * cons;
        uint4 v;
        v.x = __shfl_sync(0xffffffffu, mine.x, 8 * ck); v.y = __shfl_sync(0xffffffffu, mine.y, 8 * ck);
        v.z = __shfl_sync(0xffffffffu, mine.z, 8 * ck); v.w = __shfl_sync(0xffffffffu, mine.w, 8 * ck);
        if (t < 3 * N2) st_pub4(&g_act[cons][cta * 3 + ck], v);
      }
      __syncwarp();
      bar_arrive(7, 320);
    } else if (wid < 10) {
      bar_sync(7, 320);
    }
    if (st_out) {
#pragma unroll
      for (int k = 0; k < 4; k++) outp[4 * k] = make_uint4(hreg[4 * k], hreg[4 * k + 1], hreg[4 * k + 2], hreg[4 * k + 3]);
    }
  } else if (cta < N1 + N2 && ABL != 6) {
    const int j2 = cta - N1;
    uint4 rowv = make_uint4(0, 0, 0, 0);
    if (tid < 192) {
      const uint4 v = poll4(&g_act[j2][tid]);
      float4* xp = reinterpret_cast<float4*>(xs + tid * 8);
      xp[0] = make_float4(lo_f(v.x), hi_f(v.x), lo_f(v.y), hi_f(v.y));
      xp[1] = make_float4(lo_f(v.z), hi_f(v.z), lo_f(v.w), hi_f(v.w));
    } else if (tid < 196) {
      const int t = tid - 192;
      rowv = poll4(&g_cand[wcta][t >> 1][j2 * 2 + (t & 1)]);
      reinterpret_cast<uint4*>(part + 256)[t] = rowv;
    }
    __syncthreads();
    const int hc = lane & 1, rs = wid * 16 + (lane >> 1);
    float a[8];
#pragma unroll
    for (int j = 0; j < 8; j++) a[j] = 0.f;
#pragma unroll
    for (int it = 0; it < 8; it++) {
      const int r = rs + 192 * it;
      const uint4 wv = sm.w[r * 2 + hc];
      const float x = xs[r];
      a[0] = fmaf(x, lo_f(wv.x), a[0]); a[1] = fmaf(x, hi_f(wv.x), a[1]);
      a[2] = fmaf(x, lo_f(wv.y), a[2]); a[3] = fmaf(x, hi_f(wv.y), a[3]);
      a[4] = fmaf(x, lo_f(wv.z), a[4]); a[5] = fmaf(x, hi_f(wv.z), a[5]);
      a[6] = fmaf(x, lo_f(wv.w), a[6]); a[7] = fmaf(x, hi_f(wv.w), a[7]);
    }
    {
      const bool up = lane & 16;
#pragma unroll
      for (int j = 0; j < 4; j++) {
        const float send = up ? a[j] : a[j + 4], keep = up ? a[j + 4] : a[j];
        a[j] = keep + __shfl_xor_sync(0xffffffffu, send, 16);
      }
      const bool up2 = lane & 8;
#pragma unroll
      for (int j = 0; j < 2; j++) {
        const float send = up2 ? a[j] : a[j + 2], keep = up2 ? a[j + 2] : a[j];
        a[j] = keep + __shfl_xor_sync(0xffffffffu, send, 8);
      }
      const bool up3 = lane & 4;
      const float send = up3 ? a[0] : a[1], keep = up3 ? a[1] : a[0];
      a[0] = keep + __shfl_xor_sync(0xffffffffu, send, 4);
      a[0] += __shfl_xor_sync(0xffffffffu, a[0], 2);
      if ((lane & 2) == 0) part[wid * 16 + hc * 8 + (lane >> 2)] = a[0];
    }
    __syncthreads();
    if (tid < 16) {
      float y = 0.f;
#pragma unroll
      for (int i = 0; i < 12; i++) y += part[i * 16 + tid];
      const uint32_t ord = win >> 16;
      const uint32_t rb = (ord & 0x8000u) ? (ord ^ 0x8000u) : (ord ^ 0xFFFFu);
      const float r = __uint_as_float(rb << 16);
      const float sg = rbf(1.f / (1.f + __expf(-r)));
      const float yy = rbf(rbf(y) * sg);
      const unsigned short* rv = reinterpret_cast<const unsigned short*>(part + 256);
      const float hn = __uint_as_float((uint32_t)rv[tid] << 16), h = __uint_as_float((uint32_t)rv[16 + tid] << 16);
      gout[(size_t)wrow * D_ + j2 * 16 + tid] = __float2bfloat16_rn(h + rbf(hn + yy));
    }
  }
  STAMP(8);
}

}

typedef CUresult (*EncodeFn)(CUtensorMap*, CUtensorMapDataType, cuuint32_t, void*, const cuuint64_t*, const cuuint64_t*,
                             const cuuint32_t*, const cuuint32_t*, CUtensorMapInterleave, CUtensorMapSwizzle,
                             CUtensorMapL2promotion, CUtensorMapFloatOOBfill);

extern "C" void kernel_launch(void* const* d_in, const int* in_sizes, int n_in, void* d_out, int out_size) {
  (void)in_sizes; (void)n_in; (void)out_size;
  static EncodeFn encode = nullptr;
  static CUtensorMap tmg, tmu, tmd;
  static void* cached[3] = {nullptr, nullptr, nullptr};
  if (!encode) {
    cudaFuncSetAttribute(fused_kernel, cudaFuncAttributeMaxDynamicSharedMemorySize, (int)sizeof(Smem));
    void* fn = nullptr;
    cudaDriverEntryPointQueryResult qr;
    cudaGetDriverEntryPoint("cuTensorMapEncodeTiled", &fn, cudaEnableDefault, &qr);
    encode = (EncodeFn)fn;
  }
  if (cached[0] != d_in[8] || cached[1] != d_in[9] || cached[2] != d_in[10]) {
    const cuuint32_t es[2] = {1, 1};
    {
      const cuuint64_t dims[2] = {F_, D_}, strides[1] = {F_ * 2};
      const cuuint32_t box[2] = {24, 160};
      encode(&tmg, CU_TENSOR_MAP_DATA_TYPE_BFLOAT16, 2, d_in[8], dims, strides, box, es, CU_TENSOR_MAP_INTERLEAVE_NONE,
             CU_TENSOR_MAP_SWIZZLE_NONE, CU_TENSOR_MAP_L2_PROMOTION_NONE, CU_TENSOR_MAP_FLOAT_OOB_FILL_NONE);
      encode(&tmu, CU_TENSOR_MAP_DATA_TYPE_BFLOAT16, 2, d_in[9], dims, strides, box, es, CU_TENSOR_MAP_INTERLEAVE_NONE,
             CU_TENSOR_MAP_SWIZZLE_NONE, CU_TENSOR_MAP_L2_PROMOTION_NONE, CU_TENSOR_MAP_FLOAT_OOB_FILL_NONE);
    }
    {
      const cuuint64_t dims[2] = {D_, F_}, strides[1] = {D_ * 2};
      const cuuint32_t box[2] = {16, 256};
      encode(&tmd, CU_TENSOR_MAP_DATA_TYPE_BFLOAT16, 2, d_in[10], dims, strides, box, es, CU_TENSOR_MAP_INTERLEAVE_NONE,
             CU_TENSOR_MAP_SWIZZLE_NONE, CU_TENSOR_MAP_L2_PROMOTION_NONE, CU_TENSOR_MAP_FLOAT_OOB_FILL_NONE);
    }
    cached[0] = d_in[8]; cached[1] = d_in[9]; cached[2] = d_in[10];
  }
  fused_kernel<<<NCTA, NTHR, sizeof(Smem), cudaStreamPerThread>>>(
      tmg, tmu, tmd, (const bf16*)d_in[0], (const bf16*)d_in[1], (const bf16*)d_in[2], (const bf16*)d_in[3],
      (const bf16*)d_in[4], (const bf16*)d_in[5], (const bf16*)d_in[7], (bf16*)d_out);
}
```

```cpp
#include <cuda_runtime.h>
#include <cuda_bf16.h>
#include <cuda.h>
#include <stdint.h>

namespace {

typedef __nv_bfloat16 bf16;
typedef __nv_bfloat162 bf162;

constexpr int S_ = 2048, D_ = 640, F_ = 1536;
constexpr int NCTA = 128, CPC = 5, NTHR = 384;
constexpr int UPAD = 136, USTR = 2192;
constexpr int TABW = 1040;
constexpr int ZPB = 132;
constexpr int QSTR = 648;
constexpr int N1 = 64;
constexpr int N2 = 40;
constexpr int SPIN_LIMIT = 1 << 19;
#define LN2_EXACT 1
#define ABL 0
#define CTR_NS 0
#define C_DELAY 0
#define TESTV 0
#define TESTC 0
#define POLL_NS 100
#define H_DELAY 0
#define Q_DELAY 4500

struct __align__(128) Smem {
  uint32_t tabA[3][2][TABW];
  uint32_t extra[1024];
  uint32_t tabB[2][2][TABW];
  bf16 u[CPC][USTR];
  float z[2][4][ZPB * 16];
  bf16 q[16][QSTR];
  alignas(128) uint4 w[3840];
  uint4 wr[80];
  float2 st[16][5];
  float2 stq[16][5];
  float rp[16][5];
  unsigned long long mbar;
  unsigned long long mbarw;
  unsigned long long mbarc;
  unsigned long long mbary;
  unsigned long long mbarh;
  uint32_t target;
  uint32_t best;
  uint32_t win;
};

__device__ uint4 g_kv[D_ * S_ / 8];
__device__ uint4 g_y2[D_ * S_ / 8];
__device__ uint32_t g_keys[NCTA][NCTA];
__device__ uint4 g_cand[NCTA][2][80];
__device__ uint4 g_act[N2][F_ / 8];
__device__ unsigned int g_ctr;
__device__ unsigned int g_ctr2;
__device__ unsigned int g_ctr3;
#define STAMP(i)
#define CST(c, i)

__device__ __forceinline__ uint32_t smem_u32(const void* p) { return (uint32_t)__cvta_generic_to_shared(p); }
__device__ __forceinline__ void wg_fence() { asm volatile("wgmma.fence.sync.aligned;" ::: "memory"); }
__device__ __forceinline__ void wg_commit() { asm volatile("wgmma.commit_group.sync.aligned;" ::: "memory"); }
template <int N> __device__ __forceinline__ void wg_wait() { asm volatile("wgmma.wait_group.sync.aligned %0;" ::"n"(N) : "memory"); }
__device__ __forceinline__ void bar_sync(int id, int n) { asm volatile("bar.sync %0, %1;" ::"r"(id), "r"(n) : "memory"); }
__device__ __forceinline__ void bar_arrive(int id, int n) { asm volatile("bar.arrive %0, %1;" ::"r"(id), "r"(n) : "memory"); }
__device__ __forceinline__ bf162 u2b(uint32_t u) { return *reinterpret_cast<bf162*>(&u); }
__device__ __forceinline__ uint32_t b2u(bf162 b) { return *reinterpret_cast<uint32_t*>(&b); }
__device__ __forceinline__ float lo_f(uint32_t u) { return __uint_as_float(u << 16); }
__device__ __forceinline__ float hi_f(uint32_t u) { return __uint_as_float(u & 0xFFFF0000u); }
__device__ __forceinline__ float rbf(float x) { return __bfloat162float(__float2bfloat16_rn(x)); }
__device__ __forceinline__ uint32_t pack2(float a, float b) { return b2u(__floats2bfloat162_rn(a, b)); }
__device__ __forceinline__ uint32_t enc(uint32_t w) { return max(~w, 1u); }
__device__ __forceinline__ uint4 enc4(uint4 v) { return make_uint4(enc(v.x), enc(v.y), enc(v.z), enc(v.w)); }
__device__ __forceinline__ uint4 ld_poll4(const uint4* p) {
  uint4 v;
  asm volatile("ld.relaxed.gpu.global.v4.u32 {%0,%1,%2,%3}, [%4];" : "=r"(v.x), "=r"(v.y), "=r"(v.z), "=r"(v.w) : "l"(p) : "memory");
  return v;
}
__device__ __forceinline__ bool ready4(uint4 v) { return v.x != 0u && v.y != 0u && v.z != 0u && v.w != 0u; }
__device__ __forceinline__ uint4 poll4(const uint4* p) {
  uint4 v = ld_poll4(p);
  int it = 0;
  while (!ready4(v) && ++it < SPIN_LIMIT) v = ld_poll4(p);
  return make_uint4(~v.x, ~v.y, ~v.z, ~v.w);
}
__device__ __forceinline__ void st_pub4(uint4* p, uint4 v) {
  asm volatile("st.relaxed.gpu.global.v4.u32 [%0], {%1,%2,%3,%4};" ::"l"(p), "r"(v.x), "r"(v.y), "r"(v.z), "r"(v.w) : "memory");
}
__device__ __forceinline__ void st_pub2(uint2* p, uint32_t a, uint32_t b) {
  asm volatile("st.relaxed.gpu.global.v2.u32 [%0], {%1,%2};" ::"l"(p), "r"(a), "r"(b) : "memory");
}
__device__ __forceinline__ void mma_bf16(float (&c)[4], uint32_t a0, uint32_t a2, uint32_t b0, uint32_t b1) {
  asm volatile("mma.sync.aligned.m16n8k16.row.col.f32.bf16.bf16.f32 {%0,%1,%2,%3}, {%4,%5,%6,%5}, {%7,%8}, {%0,%1,%2,%3};"
               : "+f"(c[0]), "+f"(c[1]), "+f"(c[2]), "+f"(c[3]) : "r"(a0), "r"(0u), "r"(a2), "r"(b0), "r"(b1));
}
__device__ __forceinline__ void mbar_wait(const unsigned long long* bar) {
  const uint32_t mb = smem_u32(bar);
  uint32_t ok = 0;
  int it = 0;
  while (!ok && ++it < SPIN_LIMIT)
    asm volatile("{ .reg .pred p; mbarrier.try_wait.parity.shared.b64 p, [%1], 0; selp.u32 %0, 1, 0, p; }" : "=r"(ok) : "r"(mb) : "memory");
}
__device__ __forceinline__ void bulk_g2s(void* dst, const void* src, uint32_t bytes, const unsigned long long* bar) {
  asm volatile("cp.async.bulk.shared::cluster.global.mbarrier::complete_tx::bytes [%0], [%1], %2, [%3];" ::"r"(smem_u32(dst)),
               "l"(src), "r"(bytes), "r"(smem_u32(bar)) : "memory");
}
__device__ __forceinline__ void mbar_expect(const unsigned long long* bar, uint32_t bytes) {
  asm volatile("mbarrier.arrive.expect_tx.shared.b64 _, [%0], %1;" ::"r"(smem_u32(bar)), "r"(bytes) : "memory");
}
__device__ __forceinline__ void mma_bf16x(float (&c)[4], uint32_t a0, uint32_t a1, uint32_t a2, uint32_t a3, uint32_t b0, uint32_t b1) {
  asm volatile("mma.sync.aligned.m16n8k16.row.col.f32.bf16.bf16.f32 {%0,%1,%2,%3}, {%4,%5,%6,%7}, {%8,%9}, {%0,%1,%2,%3};"
               : "+f"(c[0]), "+f"(c[1]), "+f"(c[2]), "+f"(c[3]) : "r"(a0), "r"(a1), "r"(a2), "r"(a3), "r"(b0), "r"(b1));
}
__device__ __forceinline__ float fdivr(float a, float d, float r) {
  float q = a * r;
  float e = fmaf(-q, d, a);
  return fmaf(e, r, q);
}

template <bool FIRST> __device__ __forceinline__ void wgmma32(float (&d)[16], const uint32_t* a, uint64_t desc) {
  if (FIRST) {
    asm volatile("wgmma.mma_async.sync.aligned.m64n32k16.f32.bf16.bf16 {%0,%1,%2,%3,%4,%5,%6,%7,%8,%9,%10,%11,%12,%13,%14,%15}, {%16,%17,%18,%19}, %20, 0, 1, 1, 0;"
                 : "+f"(d[0]), "+f"(d[1]), "+f"(d[2]), "+f"(d[3]), "+f"(d[4]), "+f"(d[5]), "+f"(d[6]), "+f"(d[7]),
                   "+f"(d[8]), "+f"(d[9]), "+f"(d[10]), "+f"(d[11]), "+f"(d[12]), "+f"(d[13]), "+f"(d[14]), "+f"(d[15])
                 : "r"(a[0]), "r"(a[1]), "r"(a[2]), "r"(a[3]), "l"(desc));
  } else {
    asm volatile("wgmma.mma_async.sync.aligned.m64n32k16.f32.bf16.bf16 {%0,%1,%2,%3,%4,%5,%6,%7,%8,%9,%10,%11,%12,%13,%14,%15}, {%16,%17,%18,%19}, %20, 1, 1, 1, 0;"
                 : "+f"(d[0]), "+f"(d[1]), "+f"(d[2]), "+f"(d[3]), "+f"(d[4]), "+f"(d[5]), "+f"(d[6]), "+f"(d[7]),
                   "+f"(d[8]), "+f"(d[9]), "+f"(d[10]), "+f"(d[11]), "+f"(d[12]), "+f"(d[13]), "+f"(d[14]), "+f"(d[15])
                 : "r"(a[0]), "r"(a[1]), "r"(a[2]), "r"(a[3]), "l"(desc));
  }
}

template <int G> __device__ __forceinline__ void load_a(uint32_t (&a)[8], const uint32_t* tp) {
#pragma unroll
  for (int q = 0; q < 2; q++) {
    const int e = 2 * G + q;
    a[4 * q + 0] = tp[-64 * e];
    a[4 * q + 1] = tp[-64 * e - 32];
    a[4 * q + 2] = tp[-64 * e + 4];
    a[4 * q + 3] = tp[-64 * e - 28];
  }
}
__device__ __forceinline__ void load_a_all(uint32_t (&a)[8][8], const uint32_t* tp) {
  load_a<0>(a[0], tp); load_a<1>(a[1], tp); load_a<2>(a[2], tp); load_a<3>(a[3], tp);
  load_a<4>(a[4], tp); load_a<5>(a[5], tp); load_a<6>(a[6], tp); load_a<7>(a[7], tp);
}
template <int G> __device__ __forceinline__ void issue_g(float (&acc)[8][16], uint32_t (&a)[8], uint64_t desc0) {
  wg_fence();
#pragma unroll
  for (int q = 0; q < 2; q++) {
#pragma unroll
    for (int b = G; b < 8; b++) {
      const int delta = 2 * b - (2 * G + q);
      if (G == 0 && q == 0) wgmma32<true>(acc[b], &a[4 * q], desc0 + (uint64_t)(int64_t)(16 * delta));
      else wgmma32<false>(acc[b], &a[4 * q], desc0 + (uint64_t)(int64_t)(16 * delta));
    }
  }
  wg_commit();
}
template <int B> __device__ __forceinline__ void fence_blk(float (&acc)[8][16]) {
#pragma unroll
  for (int i = 0; i < 16; i++) asm volatile("" : "+f"(acc[B][i])::"memory");
}
__device__ __forceinline__ void fence_a(uint32_t (&a)[8]) {
#pragma unroll
  for (int i = 0; i < 8; i++) asm volatile("" : "+r"(a[i])::"memory");
}
template <int B> __device__ __forceinline__ void sts_blk(float (&acc)[8][16], float* zw, int off_even, int off_odd) {
#pragma unroll
  for (int jj = 0; jj < 4; jj++) {
    const int j = 4 * B + jj;
    float p0 = acc[B][4 * jj + 0], p1 = acc[B][4 * jj + 1];
    if (jj > 0) { p0 += acc[B][4 * (jj - 1) + 2]; p1 += acc[B][4 * (jj - 1) + 3]; }
    else if (B > 0) { p0 += acc[B > 0 ? B - 1 : 0][14]; p1 += acc[B > 0 ? B - 1 : 0][15]; }
    zw[64 * j + off_even] = p0;
    zw[64 * j + off_odd] = p1;
  }
}
__device__ __forceinline__ int tab_off(int c) { return c == 4 ? 0 : (c + 1) * 2 * TABW + (c >= 2 ? 1024 : 0); }
__device__ __forceinline__ int tile_perm(int ch) { return ch ^ (((ch >> 3) & 3) << 1); }

__device__ __forceinline__ void wait_ctr(const unsigned int* ctr, uint32_t target) {
  uint32_t v;
  int it = 0;
  do {
    asm volatile("ld.acquire.gpu.global.u32 %0, [%1];" : "=r"(v) : "l"(ctr) : "memory");
  } while ((int)(v - target) < 0 && ++it < SPIN_LIMIT);
}

__device__ __forceinline__ float2 row_part_stats(const uint32_t (&x)[16]) {
  float cs[4][4];
#pragma unroll
  for (int k = 0; k < 4; k++) {
    cs[k][0] = cs[k][1] = cs[k][2] = cs[k][3] = 0.f;
    mma_bf16x(cs[k], x[4 * k + 0], x[4 * k + 2], x[4 * k + 1], x[4 * k + 3], 0x3F803F80u, 0x3F803F80u);
  }
  const float mean = (((cs[0][0] + cs[0][2]) + (cs[1][0] + cs[1][2])) + ((cs[2][0] + cs[2][2]) + (cs[3][0] + cs[3][2]))) * (1.f / 128.f);
  float m2a = 0.f, m2b = 0.f, m2c = 0.f, m2d = 0.f;
#pragma unroll
  for (int i = 0; i < 16; i += 2) {
    const float a = lo_f(x[i]) - mean, b = hi_f(x[i]) - mean, c = lo_f(x[i + 1]) - mean, d = hi_f(x[i + 1]) - mean;
    m2a = fmaf(a, a, m2a); m2b = fmaf(b, b, m2b); m2c = fmaf(c, c, m2c); m2d = fmaf(d, d, m2d);
  }
  float m2 = (m2a + m2b) + (m2c + m2d);
  m2 += __shfl_xor_sync(0xffffffffu, m2, 1);
  m2 += __shfl_xor_sync(0xffffffffu, m2, 2);
  return make_float2(mean, m2);
}
__device__ __forceinline__ void row_normalize(const float2* st, const uint32_t (&x)[16], uint32_t (&y)[16]) {
  float mean = 0.f, m2 = 0.f;
  float2 p[5];
#pragma unroll
  for (int i = 0; i < 5; i++) { p[i] = st[i]; mean += p[i].x; }
  mean *= 0.2f;
#pragma unroll
  for (int i = 0; i < 5; i++) { const float dl = p[i].x - mean; m2 += p[i].y + 128.f * dl * dl; }
  const float hd = rbf(sqrtf(rbf(rbf(m2 * (1.f / D_)) + 1e-5f)));
  const float hr = 1.f / hd;
  const bf162 hm2 = __float2bfloat162_rn(mean);
#pragma unroll
  for (int i = 0; i < 16; i++) {
    const uint32_t d = b2u(__hsub2_rn(u2b(x[i]), hm2));
    y[i] = pack2(fdivr(lo_f(d), hd, hr), fdivr(hi_f(d), hd, hr));
  }
}

__global__ void __launch_bounds__(NTHR, 1)
fused_kernel(const __grid_constant__ CUtensorMap tmg, const __grid_constant__ CUtensorMap tmu,
             const __grid_constant__ CUtensorMap tmd, const bf16* __restrict__ gq, const bf16* __restrict__ gk, const bf16* __restrict__ gv,
             const bf16* __restrict__ gsk, const bf16* __restrict__ gh, const bf16* __restrict__ gD,
             const bf16* __restrict__ gwr, bf16* __restrict__ gout) {
  extern __shared__ __align__(128) unsigned char smraw[];
  Smem& sm = *reinterpret_cast<Smem*>(smraw);
  const int tid = threadIdx.x;
  const int cta = blockIdx.x;
  const int c0 = cta * CPC;
  const int lane = tid & 31;
  const int wid = tid >> 5;
  STAMP(0);
  const long long tstart = clock64();

  {
    uint4* hs = reinterpret_cast<uint4*>(&sm.z[0][0][0]);
    const int oc = tid >> 2;
    const int r0 = cta * 16 + (tid & 3) * 4;
    uint4 kk[7], vv[4], sk[4];
    if (tid < 320) {
      const uint4* kp = reinterpret_cast<const uint4*>(gk) + (size_t)r0 * 80 + oc;
      const uint4* vp = reinterpret_cast<const uint4*>(gv) + (size_t)r0 * 80 + oc;
#pragma unroll
      for (int i = 0; i < 7; i++) kk[i] = (i >= 3 || r0 > 0) ? __ldg(kp + (i - 3) * 80) : make_uint4(0, 0, 0, 0);
#pragma unroll
      for (int i = 0; i < 4; i++) vv[i] = __ldg(vp + i * 80);
#pragma unroll
      for (int i = 0; i < 4; i++) sk[i] = __ldg(reinterpret_cast<const uint4*>(gsk) + oc * 4 + i);
    } else if (tid == 320) {
      asm volatile("mbarrier.init.shared.b64 [%0], 1;" ::"r"(smem_u32(&sm.mbarh)) : "memory");
      asm volatile("mbarrier.init.shared.b64 [%0], 1;" ::"r"(smem_u32(&sm.mbar)) : "memory");
      asm volatile("mbarrier.init.shared.b64 [%0], 1;" ::"r"(smem_u32(&sm.mbarw)) : "memory");
      asm volatile("mbarrier.init.shared.b64 [%0], 1;" ::"r"(smem_u32(&sm.mbarc)) : "memory");
      asm volatile("mbarrier.init.shared.b64 [%0], 1;" ::"r"(smem_u32(&sm.mbary)) : "memory");
      asm volatile("fence.proxy.async.shared::cta;" ::: "memory");
    }
    if (tid < 320) bar_sync(6, 384); else { bar_arrive(6, 384); bar_sync(5, 64); }
    STAMP(9);
    if (tid < 320) {
      uint32_t o[4][4];
#pragma unroll
      for (int p = 0; p < 4; p++) {
        const bf162 w0 = u2b(__byte_perm(sk[p].x, sk[p].z, 0x5410)), w1 = u2b(__byte_perm(sk[p].x, sk[p].z, 0x7632));
        const bf162 w2 = u2b(__byte_perm(sk[p].y, sk[p].w, 0x5410)), w3 = u2b(__byte_perm(sk[p].y, sk[p].w, 0x7632));
        uint32_t kv[4];
#pragma unroll
        for (int i = 0; i < 4; i++) {
          const uint32_t k0 = p == 0 ? kk[i].x : p == 1 ? kk[i].y : p == 2 ? kk[i].z : kk[i].w;
          const uint32_t k1 = p == 0 ? kk[i + 1].x : p == 1 ? kk[i + 1].y : p == 2 ? kk[i + 1].z : kk[i + 1].w;
          const uint32_t k2 = p == 0 ? kk[i + 2].x : p == 1 ? kk[i + 2].y : p == 2 ? kk[i + 2].z : kk[i + 2].w;
          const uint32_t k3 = p == 0 ? kk[i + 3].x : p == 1 ? kk[i + 3].y : p == 2 ? kk[i + 3].z : kk[i + 3].w;
          const uint32_t vx = p == 0 ? vv[i].x : p == 1 ? vv[i].y : p == 2 ? vv[i].z : vv[i].w;
          bf162 a = __hmul2_rn(u2b(k0), w3);
          a = __hadd2_rn(a, __hmul2_rn(u2b(k1), w2));
          a = __hadd2_rn(a, __hmul2_rn(u2b(k2), w1));
          a = __hadd2_rn(a, __hmul2_rn(u2b(k3), w0));
          kv[i] = b2u(__hmul2_rn(a, u2b(vx)));
        }
        o[p][0] = enc(__byte_perm(kv[0], kv[1], 0x5410)); o[p][1] = enc(__byte_perm(kv[2], kv[3], 0x5410));
        o[p][2] = enc(__byte_perm(kv[0], kv[1], 0x7632)); o[p][3] = enc(__byte_perm(kv[2], kv[3], 0x7632));
      }
      uint2* dst = reinterpret_cast<uint2*>(g_kv) + (size_t)(oc * 8) * 512 + (r0 >> 2);
#pragma unroll
      for (int p = 0; p < 4; p++) {
        st_pub2(dst + (2 * p) * 512, o[p][0], o[p][1]);
        st_pub2(dst + (2 * p + 1) * 512, o[p][2], o[p][3]);
      }
      STAMP(10);
      if (wid == 0) bar_sync(4, 320); else bar_arrive(4, 320);
      if (tid == 0) {
        const unsigned old = atomicAdd(&g_ctr2, 1u);
        const unsigned target = (old / NCTA + 1u) * NCTA;
        uint32_t v;
        int it = 0;
        do {
          if (CTR_NS) __nanosleep(CTR_NS);
          asm volatile("ld.relaxed.gpu.global.u32 %0, [%1];" : "=r"(v) : "l"(&g_ctr2) : "memory");
        } while (ABL != 7 && ABL != 9 && (int)(v - target) < 0 && ++it < SPIN_LIMIT);
        asm volatile("mbarrier.arrive.shared.b64 _, [%0];" ::"r"(smem_u32(&sm.mbarc)) : "memory");
      }
      __syncwarp();
    } else {
      const int t0 = tid - 320;
      const uint4 zz = make_uint4(0, 0, 0, 0);
      if (tid == 320) {
        while (clock64() - tstart < H_DELAY) {}
        mbar_expect(&sm.mbarh, CPC * S_ * 2);
        bulk_g2s(hs, gh + (size_t)c0 * S_, CPC * S_ * 2, &sm.mbarh);
      }
      __syncwarp();
      for (int t = t0; t < CPC * 17; t += 64) *reinterpret_cast<uint4*>(&sm.u[t / 17][(t % 17) * 8]) = zz;
      if (t0 < 40) *reinterpret_cast<uint4*>(&sm.tabA[0][0][0] + tab_off(t0 >> 3) + ((t0 >> 2) & 1) * TABW + 1024 + 4 * (t0 & 3)) = zz;
      while (clock64() - tstart < C_DELAY) {}
      (&g_cand[cta][0][0])[t0] = zz;
      (&g_cand[cta][0][0])[64 + t0] = zz;
      if (t0 < 32) (&g_cand[cta][0][0])[128 + t0] = zz;
      else reinterpret_cast<uint4*>(&g_keys[cta][0])[t0 - 32] = zz;
      if (cta >= N1 && cta < N1 + N2) {
#pragma unroll
        for (int i = 0; i < 3; i++) g_act[cta - N1][t0 + 64 * i] = zz;
      }
      bar_sync(5, 64);
      if (tid == 352) {
        __threadfence();
        const unsigned old = atomicAdd(&g_ctr, 1u);
        sm.target = (old / NCTA + 1u) * NCTA;
      }
      __syncwarp();
    }
    mbar_wait(&sm.mbarh);
    if (ABL == 9) return;
#pragma unroll
    for (int i = 0; i < 4; i++) {
      const int t = (NTHR - 1 - tid) + NTHR * i;
      if (t < CPC * 256) {
        uint32_t* tb = &sm.tabA[0][0][0] + tab_off(t >> 8) + (255 - (t & 255)) * 4;
        const uint4 h = hs[t];
        const uint32_t hp = (t & 255) ? reinterpret_cast<const uint32_t*>(hs)[4 * t - 1] : 0u;
        uint4 r1, rr;
        r1.x = __byte_perm(h.w, 0, 0x1032); r1.y = __byte_perm(h.z, 0, 0x1032);
        r1.z = __byte_perm(h.y, 0, 0x1032); r1.w = __byte_perm(h.x, 0, 0x1032);
        rr.x = __byte_perm(h.w, h.z, 0x7610); rr.y = __byte_perm(h.z, h.y, 0x7610);
        rr.z = __byte_perm(h.y, h.x, 0x7610); rr.w = __byte_perm(h.x, hp, 0x7610);
        *reinterpret_cast<uint4*>(tb) = rr;
        *reinterpret_cast<uint4*>(tb + TABW) = r1;
      }
    }
    STAMP(12);
  }
  mbar_wait(&sm.mbarc);
  if (ABL == 7 || ABL == 8) return;
  {
    uint4 v[4];
    uint4* src = g_kv + c0 * 256 + tid;
#pragma unroll
    for (int i = 0; i < 4; i++) if (i < 3 || tid < 128) v[i] = ld_poll4(src + NTHR * i);
#pragma unroll
    for (int i = 0; i < 4; i++) {
      if (i < 3 || tid < 128) {
        int it = 0;
        while (!ready4(v[i]) && ++it < SPIN_LIMIT) { __nanosleep(POLL_NS); v[i] = ld_poll4(src + NTHR * i); }
        const int t = tid + NTHR * i;
        *reinterpret_cast<uint4*>(&sm.u[t >> 8][UPAD + (t & 255) * 8]) = make_uint4(~v[i].x, ~v[i].y, ~v[i].z, ~v[i].w);
      }
    }
    STAMP(11);
    asm volatile("fence.proxy.async.shared::cta;" ::: "memory");
    __syncthreads();
#pragma unroll
    for (int i = 0; i < 4; i++) if (i < 3 || tid < 128) src[NTHR * i] = make_uint4(0, 0, 0, 0);
    if (tid >= 256) {
      const int t0 = tid - 256;
      if (((t0 & 15) >> 2) < ((t0 >> 4) & 3))
        *reinterpret_cast<uint4*>(&sm.z[t0 >> 6][(t0 >> 4) & 3][(t0 & 15) * 4]) = make_uint4(0, 0, 0, 0);
    }
  }
  STAMP(1);
  if (ABL == 5) return;

  const int wg = __shfl_sync(0xffffffffu, tid >> 7, 0);
  const int wtid = tid & 127;
  uint4* tile = reinterpret_cast<uint4*>(&sm.tabB[0][0][0]);
  if (wg < 2) {
    asm volatile("setmaxnreg.inc.sync.aligned.u32 224;");
    const int w = (tid >> 5) & 3, g = lane >> 2, tq = lane & 3;
    float* zw = sm.z[wg][w];
    const int sw = 3 * (((tq + w) >> 1) & 1);
    const int off_even = 16 * (tq + w) + 4 * ((0 + (g >> 2)) ^ sw) + (g & 3);
    const int off_odd = 16 * (tq + w) + 4 * ((2 + (g >> 2)) ^ sw) + (g & 3);
    uint32_t a[8][8];
    const uint32_t* tp0 = &sm.tabA[0][g & 1][1019 - 8 * w - (g >> 1) + tq];
    load_a_all(a, tp0 + tab_off(wg));
    float acc[8][16];
#pragma unroll
    for (int b = 0; b < 8; b++)
#pragma unroll
      for (int i = 0; i < 16; i++) acc[b][i] = 0.f;
#pragma unroll 1
    for (int c = wg; c < CPC; c += 2) {
      const uint64_t desc = (uint64_t)((smem_u32(&sm.u[c][UPAD - 8]) & 0x3FFFF) >> 4) | ((uint64_t)1 << 16) | ((uint64_t)8 << 32);
      CST(c, 0);
      if (c > 0) bar_sync(1 + wg, 256);
      issue_g<0>(acc, a[0], desc);
      CST(c, 1);
      issue_g<1>(acc, a[1], desc);
      issue_g<2>(acc, a[2], desc);
      issue_g<3>(acc, a[3], desc);
      issue_g<4>(acc, a[4], desc);
      issue_g<5>(acc, a[5], desc);
      if (c + 1 < CPC) bar_arrive(1 + (wg ^ 1), 256);
      issue_g<6>(acc, a[6], desc);
      issue_g<7>(acc, a[7], desc);
      CST(c, 2);
      if (c >= 2) bar_sync(5 + wg, 256);
      wg_wait<4>();
      fence_blk<0>(acc); fence_blk<1>(acc); fence_blk<2>(acc); fence_blk<3>(acc);
      sts_blk<0>(acc, zw, off_even, off_odd);
      sts_blk<1>(acc, zw, off_even, off_odd);
      sts_blk<2>(acc, zw, off_even, off_odd);
      sts_blk<3>(acc, zw, off_even, off_odd);
      CST(c, 3);
      wg_wait<0>();
      fence_blk<4>(acc); fence_blk<5>(acc); fence_blk<6>(acc); fence_blk<7>(acc);
#pragma unroll
      for (int i = 0; i < 8; i++) fence_a(a[i]);
      sts_blk<4>(acc, zw, off_even, off_odd);
      sts_blk<5>(acc, zw, off_even, off_odd);
      sts_blk<6>(acc, zw, off_even, off_odd);
      sts_blk<7>(acc, zw, off_even, off_odd);
      bar_arrive(3 + wg, 256);
      CST(c, 4);
      if (c + 2 < CPC) load_a_all(a, tp0 + tab_off(c + 2));
    }
    STAMP(2 + wg);
    asm volatile("setmaxnreg.dec.sync.aligned.u32 168;");
  } else {
    asm volatile("setmaxnreg.dec.sync.aligned.u32 56;");
    if (wtid == 32) {
      const uint32_t mw = smem_u32(&sm.mbarw);
      mbar_expect(&sm.mbar, 17 * D_ * 2);
#pragma unroll 1
      for (int r = 0; r < 16; r++) bulk_g2s(&sm.q[r][0], gq + (size_t)(cta * 16 + r) * D_, D_ * 2, &sm.mbar);
      bulk_g2s(&sm.wr[0], gwr, D_ * 2, &sm.mbar);
      if (cta < N1) {
        asm volatile("mbarrier.arrive.expect_tx.shared.b64 _, [%0], %1;" ::"r"(mw), "r"(3840 * 16) : "memory");
#pragma unroll 1
        for (int i = 0; i < 4; i++) {
          asm volatile("cp.async.bulk.tensor.2d.shared::cluster.global.mbarrier::complete_tx::bytes [%0], [%1, {%3, %4}], [%2];" ::"r"(smem_u32(&sm.w[i * 480])),
                       "l"(&tmg), "r"(mw), "r"(cta * 24), "r"(i * 160) : "memory");
          asm volatile("cp.async.bulk.tensor.2d.shared::cluster.global.mbarrier::complete_tx::bytes [%0], [%1, {%3, %4}], [%2];" ::"r"(smem_u32(&sm.w[1920 + i * 480])),
                       "l"(&tmu), "r"(mw), "r"(cta * 24), "r"(i * 160) : "memory");
        }
      } else if (cta < N1 + N2) {
        asm volatile("mbarrier.arrive.expect_tx.shared.b64 _, [%0], %1;" ::"r"(mw), "r"(3072 * 16) : "memory");
#pragma unroll 1
        for (int i = 0; i < 6; i++)
          asm volatile("cp.async.bulk.tensor.2d.shared::cluster.global.mbarrier::complete_tx::bytes [%0], [%1, {%3, %4}], [%2];" ::"r"(smem_u32(&sm.w[i * 512])),
                       "l"(&tmd), "r"(mw), "r"((cta - N1) * 16), "r"(i * 256) : "memory");
      }
    }
    const int rpb = wtid >> 1, re2 = wtid & 1;
    const int rsw = 3 * ((rpb >> 1) & 1);
    const int roff0 = 16 * rpb + 4 * ((2 * re2 + 0) ^ rsw);
    const int roff1 = 16 * rpb + 4 * ((2 * re2 + 1) ^ rsw);
    const uint32_t dvl = reinterpret_cast<const unsigned short*>(gD)[c0 + (lane < CPC ? lane : 0)];
#pragma unroll 1
    for (int c = 0; c < CPC; c++) {
      const int zg = c & 1;
      const uint32_t dvc = __shfl_sync(0xffffffffu, dvl, c);
      const bf162 d2 = u2b(dvc | (dvc << 16));
      CST(c, 5);
      bar_sync(3 + zg, 256);
#pragma unroll
      for (int half = 0; half < 2; half++) {
        const float* zb = sm.z[zg][0] + half * 1024;
        float4 x[4][2];
#pragma unroll
        for (int ww = 0; ww < 4; ww++) {
          x[ww][0] = *reinterpret_cast<const float4*>(zb + ww * ZPB * 16 + roff0);
          x[ww][1] = *reinterpret_cast<const float4*>(zb + ww * ZPB * 16 + roff1);
        }
        const int sidx = half * 1024 + wtid * 8;
        const uint4 kvv = *reinterpret_cast<const uint4*>(&sm.u[c][UPAD + sidx]);
        if (half == 1 && c + 2 < CPC) bar_arrive(5 + zg, 256);
        uint4 o;
        o.x = pack2((x[0][0].x + x[1][0].x) + (x[2][0].x + x[3][0].x), (x[0][0].y + x[1][0].y) + (x[2][0].y + x[3][0].y));
        o.y = pack2((x[0][0].z + x[1][0].z) + (x[2][0].z + x[3][0].z), (x[0][0].w + x[1][0].w) + (x[2][0].w + x[3][0].w));
        o.z = pack2((x[0][1].x + x[1][1].x) + (x[2][1].x + x[3][1].x), (x[0][1].y + x[1][1].y) + (x[2][1].y + x[3][1].y));
        o.w = pack2((x[0][1].z + x[1][1].z) + (x[2][1].z + x[3][1].z), (x[0][1].w + x[1][1].w) + (x[2][1].w + x[3][1].w));
        o.x = b2u(__hadd2_rn(u2b(o.x), __hmul2_rn(u2b(kvv.x), d2)));
        o.y = b2u(__hadd2_rn(u2b(o.y), __hmul2_rn(u2b(kvv.y), d2)));
        o.z = b2u(__hadd2_rn(u2b(o.z), __hmul2_rn(u2b(kvv.z), d2)));
        o.w = b2u(__hadd2_rn(u2b(o.w), __hmul2_rn(u2b(kvv.w), d2)));
        st_pub4(g_y2 + ((64 * half + rpb) * 640 + c0 + c) * 2 + re2, enc4(o));
        CST(c, 6 + half);
      }
    }
    if (wid == 11) bar_sync(8, 128); else bar_arrive(8, 128);
    STAMP(4);
    asm volatile("setmaxnreg.inc.sync.aligned.u32 168;");
  }

  if (tid == 352) {
    const unsigned old = atomicAdd(&g_ctr3, 1u);
    wait_ctr(&g_ctr, sm.target);
    wait_ctr(&g_ctr3, (old / NCTA + 1u) * NCTA);
    asm volatile("mbarrier.arrive.shared.b64 _, [%0];" ::"r"(smem_u32(&sm.mbary)) : "memory");
  }
  __syncwarp();
  if (ABL == 4) { if (cta < N1 + N2) mbar_wait(&sm.mbarw); mbar_wait(&sm.mbar); return; }
  const int g = lane >> 2, tq = lane & 3;
  const int hh = wid & 1, gqi = wid >> 1;
  const int row = hh * 8 + g;
  uint32_t hreg[16], hnreg[16];
  {
    const uint4* src = g_y2 + cta * 1280 + tid;
    uint4 v[4];
    if (wid < 10) {
      mbar_wait(&sm.mbar);
#pragma unroll
      for (int k = 0; k < 4; k++) {
        const uint4 qv4 = *reinterpret_cast<const uint4*>(&sm.q[row][32 * (4 * gqi + k) + 8 * tq]);
        hreg[4 * k] = qv4.x; hreg[4 * k + 1] = qv4.y; hreg[4 * k + 2] = qv4.z; hreg[4 * k + 3] = qv4.w;
      }
      const float2 ps = row_part_stats(hreg);
      if (tq == 0) sm.stq[row][gqi] = ps;
      bar_sync(7, 320);
      row_normalize(sm.stq[row], hreg, hnreg);
    }
    mbar_wait(&sm.mbary);
#pragma unroll
    for (int i = 0; i < 4; i++) if (i < 3 || tid < 128) v[i] = ld_poll4(src + NTHR * i);
    int it = 0;
    bool all;
    do {
      all = true;
#pragma unroll
      for (int i = 0; i < 4; i++)
        if ((i < 3 || tid < 128) && !ready4(v[i])) { v[i] = ld_poll4(src + NTHR * i); all = false; }
    } while (!all && ++it < SPIN_LIMIT);
#pragma unroll
    for (int i = 0; i < 4; i++) {
      if (i < 3 || tid < 128) {
        const int t = tid + NTHR * i;
        tile[(t & 1) * 640 + tile_perm(t >> 1)] = make_uint4(~v[i].x, ~v[i].y, ~v[i].z, ~v[i].w);
      }
    }
  }
  __syncthreads();
  STAMP(5);
  if (ABL == 3) { if (cta < N1 + N2) mbar_wait(&sm.mbarw); return; }

  if (wid < 10) {
#pragma unroll
    for (int k = 0; k < 4; k++) {
      const int base = 32 * (4 * gqi + k);
      const int lch = base + 8 * ((lane & 7) >> 1) + 2 * (lane >> 3) + (lane & 1);
      uint32_t y[4];
      asm volatile("ldmatrix.sync.aligned.m8n8.x4.trans.shared.b16 {%0,%1,%2,%3}, [%4];"
                   : "=r"(y[0]), "=r"(y[1]), "=r"(y[2]), "=r"(y[3]) : "r"(smem_u32(&tile[hh * 640 + tile_perm(lch)])) : "memory");
#pragma unroll
      for (int i = 0; i < 4; i++)
        hreg[4 * k + i] = b2u(__hadd2_rn(u2b(hreg[4 * k + i]), __hmul2_rn(u2b(hnreg[4 * k + i]), u2b(y[i]))));
    }
    const float2 ps = row_part_stats(hreg);
    if (tq == 0) sm.st[row][gqi] = ps;
    STAMP(13);
    bar_sync(7, 320);
    row_normalize(sm.st[row], hreg, hnreg);
    float cr[4][4];
#pragma unroll
    for (int k = 0; k < 4; k++) {
      cr[k][0] = cr[k][1] = cr[k][2] = cr[k][3] = 0.f;
      const uint4 w4 = sm.wr[4 * (4 * gqi + k) + tq];
      mma_bf16(cr[k], hnreg[4 * k + 0], hnreg[4 * k + 1], w4.x, w4.y);
      mma_bf16(cr[k], hnreg[4 * k + 2], hnreg[4 * k + 3], w4.z, w4.w);
    }
    if (tq == 0) sm.rp[row][gqi] = (cr[0][0] + cr[1][0]) + (cr[2][0] + cr[3][0]);
  }
  STAMP(14);
  __syncthreads();
  uint32_t best;
  {
    const int rr = lane & 15;
    const float r = ((sm.rp[rr][0] + sm.rp[rr][1]) + (sm.rp[rr][2] + sm.rp[rr][3])) + sm.rp[rr][4];
    const uint32_t bits = __bfloat16_as_ushort(__float2bfloat16_rn(r));
    const uint32_t ord = (bits & 0x8000u) ? (bits ^ 0xFFFFu) : (bits ^ 0x8000u);
    const uint32_t key = (ord << 16) | 0x8000u | (uint32_t)(2047 - (cta * 16 + rr));
    best = __reduce_max_sync(0xffffffffu, key);
  }
  if (wid >= 8) asm volatile("st.relaxed.gpu.global.u32 [%0], %1;" ::"l"(&g_keys[tid - 256][cta]), "r"(best) : "memory");
  STAMP(15);
  const int brow = (2047 - (int)(best & 0x7FFu)) - cta * 16;
  if (wid < 10 && row == brow) {
#pragma unroll
    for (int k = 0; k < 4; k++)
      st_pub4(&g_cand[cta][0][4 * (4 * gqi + k) + tq], enc4(make_uint4(hnreg[4 * k], hnreg[4 * k + 1], hnreg[4 * k + 2], hnreg[4 * k + 3])));
#pragma unroll
    for (int k = 0; k < 4; k++)
      st_pub4(&g_cand[cta][1][4 * (4 * gqi + k) + tq], enc4(make_uint4(hreg[4 * k], hreg[4 * k + 1], hreg[4 * k + 2], hreg[4 * k + 3])));
  }
#pragma unroll
  for (int i = 0; i < 16; i++) hreg[i] = b2u(__hadd2_rn(u2b(hreg[i]), u2b(hnreg[i])));
  STAMP(6);
  if (ABL == 2) { if (cta < N1 + N2) mbar_wait(&sm.mbarw); return; }
  if (wid == 11) {
    const uint4* kp = reinterpret_cast<const uint4*>(&g_keys[cta][0]) + lane;
    uint4 v = ld_poll4(kp);
    int it = 0;
    while (!ready4(v) && ++it < SPIN_LIMIT) v = ld_poll4(kp);
    const uint32_t m = max(max(v.x, v.y), max(v.z, v.w));
    const uint32_t wk = __reduce_max_sync(0xffffffffu, m);
    if (lane == 0) sm.win = wk;
  }
  __syncthreads();
  const uint32_t win = sm.win;
  const int wrow = 2047 - (int)(win & 0x7FFu);
  const int wcta = wrow >> 4;
  const bool st_out = wid < 10 && (cta * 16 + row) != wrow;
  uint4* outp = reinterpret_cast<uint4*>(gout + (size_t)(cta * 16 + row) * D_) + 16 * gqi + tq;
  if (cta >= N1 && st_out) {
#pragma unroll
    for (int k = 0; k < 4; k++) outp[4 * k] = make_uint4(hreg[4 * k], hreg[4 * k + 1], hreg[4 * k + 2], hreg[4 * k + 3]);
  }
  if (cta >= N1 || ABL == 1) {
#pragma unroll
    for (int i = 0; i < 4; i++) if (i < 3 || tid < 128) g_y2[cta * 1280 + tid + NTHR * i] = make_uint4(0, 0, 0, 0);
  }
  STAMP(7);
  if (ABL == 1) { if (cta < N1 + N2) mbar_wait(&sm.mbarw); return; }
  if (cta < N1 + N2) mbar_wait(&sm.mbarw);
  float* xs = &sm.z[0][0][0];
  float* part = xs + 2048;
  if (cta < N1) {
    if (tid < 80) {
      const uint4 v = poll4(&g_cand[wcta][0][tid]);
      float4* xp = reinterpret_cast<float4*>(xs + tid * 8);
      xp[0] = make_float4(lo_f(v.x), hi_f(v.x), lo_f(v.y), hi_f(v.y));
      xp[1] = make_float4(lo_f(v.z), hi_f(v.z), lo_f(v.w), hi_f(v.w));
    }
    __syncthreads();
    const int m = wid / 6, hc = (wid % 6) >> 1, rs = (wid & 1) * 32 + lane;
    float a[8];
#pragma unroll
    for (int j = 0; j < 8; j++) a[j] = 0.f;
#pragma unroll
    for (int it = 0; it < 10; it++) {
      const int r = rs + 64 * it;
      const uint4 wv = sm.w[m * 1920 + r * 3 + hc];
      const float x = xs[r];
      a[0] = fmaf(x, lo_f(wv.x), a[0]); a[1] = fmaf(x, hi_f(wv.x), a[1]);
      a[2] = fmaf(x, lo_f(wv.y), a[2]); a[3] = fmaf(x, hi_f(wv.y), a[3]);
      a[4] = fmaf(x, lo_f(wv.z), a[4]); a[5] = fmaf(x, hi_f(wv.z), a[5]);
      a[6] = fmaf(x, lo_f(wv.w), a[6]); a[7] = fmaf(x, hi_f(wv.w), a[7]);
    }
    {
      const bool up = lane & 16;
#pragma unroll
      for (int j = 0; j < 4; j++) {
        const float send = up ? a[j] : a[j + 4], keep = up ? a[j + 4] : a[j];
        a[j] = keep + __shfl_xor_sync(0xffffffffu, send, 16);
      }
      const bool up2 = lane & 8;
#pragma unroll
      for (int j = 0; j < 2; j++) {
        const float send = up2 ? a[j] : a[j + 2], keep = up2 ? a[j + 2] : a[j];
        a[j] = keep + __shfl_xor_sync(0xffffffffu, send, 8);
      }
      const bool up3 = lane & 4;
      const float send = up3 ? a[0] : a[1], keep = up3 ? a[1] : a[0];
      a[0] = keep + __shfl_xor_sync(0xffffffffu, send, 4);
      a[0] += __shfl_xor_sync(0xffffffffu, a[0], 2);
      a[0] += __shfl_xor_sync(0xffffffffu, a[0], 1);
      if ((lane & 3) == 0) part[wid * 8 + (lane >> 2)] = a[0];
    }
    __syncthreads();
    if (wid == 0) {
      uint32_t bits = 0;
      if (lane < 24) {
        const int hc2 = lane >> 3, j = lane & 7;
        const float gt = rbf(part[(2 * hc2) * 8 + j] + part[(2 * hc2 + 1) * 8 + j]);
        const float up = rbf(part[(6 + 2 * hc2) * 8 + j] + part[(6 + 2 * hc2 + 1) * 8 + j]);
        const float sg = rbf(gt / (1.f + __expf(-gt)));
        bits = __bfloat16_as_ushort(__float2bfloat16_rn(sg * up));
      }
      const uint32_t nb = __shfl_down_sync(0xffffffffu, bits, 1);
      const uint32_t pw = bits | (nb << 16);
      const uint32_t w1 = __shfl_down_sync(0xffffffffu, pw, 2), w2 = __shfl_down_sync(0xffffffffu, pw, 4), w3 = __shfl_down_sync(0xffffffffu, pw, 6);
      const uint4 mine = enc4(make_uint4(pw, w1, w2, w3));
#pragma unroll
      for (int i = 0; i < 4; i++) {
        const int t = lane + 32 * i;
        const int cons = t / 3, ck = t - 3 * cons;
        uint4 v;
        v.x = __shfl_sync(0xffffffffu, mine.x, 8 * ck); v.y = __shfl_sync(0xffffffffu, mine.y, 8 * ck);
        v.z = __shfl_sync(0xffffffffu, mine.z, 8 * ck); v.w = __shfl_sync(0xffffffffu, mine.w, 8 * ck);
        if (t < 3 * N2) st_pub4(&g_act[cons][cta * 3 + ck], v);
      }
      __syncwarp();
      bar_arrive(7, 384);
    } else {
      bar_sync(7, 384);
    }
#pragma unroll
    for (int i = 0; i < 4; i++) if (i < 3 || tid < 128) g_y2[cta * 1280 + tid + NTHR * i] = make_uint4(0, 0, 0, 0);
    if (st_out) {
#pragma unroll
      for (int k = 0; k < 4; k++) outp[4 * k] = make_uint4(hreg[4 * k], hreg[4 * k + 1], hreg[4 * k + 2], hreg[4 * k + 3]);
    }
  } else if (cta < N1 + N2 && ABL != 6) {
    const int j2 = cta - N1;
    uint4 rowv = make_uint4(0, 0, 0, 0);
    if (tid < 192) {
      const uint4 v = poll4(&g_act[j2][tid]);
      float4* xp = reinterpret_cast<float4*>(xs + tid * 8);
      xp[0] = make_float4(lo_f(v.x), hi_f(v.x), lo_f(v.y), hi_f(v.y));
      xp[1] = make_float4(lo_f(v.z), hi_f(v.z), lo_f(v.w), hi_f(v.w));
    } else if (tid < 196) {
      const int t = tid - 192;
      rowv = poll4(&g_cand[wcta][t >> 1][j2 * 2 + (t & 1)]);
      reinterpret_cast<uint4*>(part + 256)[t] = rowv;
    }
    __syncthreads();
    const int hc = lane & 1, rs = wid * 16 + (lane >> 1);
    float a[8];
#pragma unroll
    for (int j = 0; j < 8; j++) a[j] = 0.f;
#pragma unroll
    for (int it = 0; it < 8; it++) {
      const int r = rs + 192 * it;
      const uint4 wv = sm.w[r * 2 + hc];
      const float x = xs[r];
      a[0] = fmaf(x, lo_f(wv.x), a[0]); a[1] = fmaf(x, hi_f(wv.x), a[1]);
      a[2] = fmaf(x, lo_f(wv.y), a[2]); a[3] = fmaf(x, hi_f(wv.y), a[3]);
      a[4] = fmaf(x, lo_f(wv.z), a[4]); a[5] = fmaf(x, hi_f(wv.z), a[5]);
      a[6] = fmaf(x, lo_f(wv.w), a[6]); a[7] = fmaf(x, hi_f(wv.w), a[7]);
    }
    {
      const bool up = lane & 16;
#pragma unroll
      for (int j = 0; j < 4; j++) {
        const float send = up ? a[j] : a[j + 4], keep = up ? a[j + 4] : a[j];
        a[j] = keep + __shfl_xor_sync(0xffffffffu, send, 16);
      }
      const bool up2 = lane & 8;
#pragma unroll
      for (int j = 0; j < 2; j++) {
        const float send = up2 ? a[j] : a[j + 2], keep = up2 ? a[j + 2] : a[j];
        a[j] = keep + __shfl_xor_sync(0xffffffffu, send, 8);
      }
      const bool up3 = lane & 4;
      const float send = up3 ? a[0] : a[1], keep = up3 ? a[1] : a[0];
      a[0] = keep + __shfl_xor_sync(0xffffffffu, send, 4);
      a[0] += __shfl_xor_sync(0xffffffffu, a[0], 2);
      if ((lane & 2) == 0) part[wid * 16 + hc * 8 + (lane >> 2)] = a[0];
    }
    __syncthreads();
    if (tid < 16) {
      float y = 0.f;
#pragma unroll
      for (int i = 0; i < 12; i++) y += part[i * 16 + tid];
      const uint32_t ord = win >> 16;
      const uint32_t rb = (ord & 0x8000u) ? (ord ^ 0x8000u) : (ord ^ 0xFFFFu);
      const float r = __uint_as_float(rb << 16);
      const float sg = rbf(1.f / (1.f + __expf(-r)));
      const float yy = rbf(rbf(y) * sg);
      const unsigned short* rv = reinterpret_cast<const unsigned short*>(part + 256);
      const float hn = __uint_as_float((uint32_t)rv[tid] << 16), h = __uint_as_float((uint32_t)rv[16 + tid] << 16);
      gout[(size_t)wrow * D_ + j2 * 16 + tid] = __float2bfloat16_rn(h + rbf(hn + yy));
    }
  }
  STAMP(8);
}

}

typedef CUresult (*EncodeFn)(CUtensorMap*, CUtensorMapDataType, cuuint32_t, void*, const cuuint64_t*, const cuuint64_t*,
                             const cuuint32_t*, const cuuint32_t*, CUtensorMapInterleave, CUtensorMapSwizzle,
                             CUtensorMapL2promotion, CUtensorMapFloatOOBfill);

extern "C" void kernel_launch(void* const* d_in, const int* in_sizes, int n_in, void* d_out, int out_size) {
  (void)in_sizes; (void)n_in; (void)out_size;
  static EncodeFn encode = nullptr;
  static CUtensorMap tmg, tmu, tmd;
  static void* cached[3] = {nullptr, nullptr, nullptr};
  if (!encode) {
    cudaFuncSetAttribute(fused_kernel, cudaFuncAttributeMaxDynamicSharedMemorySize, (int)sizeof(Smem));
    void* fn = nullptr;
    cudaDriverEntryPointQueryResult qr;
    cudaGetDriverEntryPoint("cuTensorMapEncodeTiled", &fn, cudaEnableDefault, &qr);
    encode = (EncodeFn)fn;
  }
  if (cached[0] != d_in[8] || cached[1] != d_in[9] || cached[2] != d_in[10]) {
    const cuuint32_t es[2] = {1, 1};
    {
      const cuuint64_t dims[2] = {F_, D_}, strides[1] = {F_ * 2};
      const cuuint32_t box[2] = {24, 160};
      encode(&tmg, CU_TENSOR_MAP_DATA_TYPE_BFLOAT16, 2, d_in[8], dims, strides, box, es, CU_TENSOR_MAP_INTERLEAVE_NONE,
             CU_TENSOR_MAP_SWIZZLE_NONE, CU_TENSOR_MAP_L2_PROMOTION_NONE, CU_TENSOR_MAP_FLOAT_OOB_FILL_NONE);
      encode(&tmu, CU_TENSOR_MAP_DATA_TYPE_BFLOAT16, 2, d_in[9], dims, strides, box, es, CU_TENSOR_MAP_INTERLEAVE_NONE,
             CU_TENSOR_MAP_SWIZZLE_NONE, CU_TENSOR_MAP_L2_PROMOTION_NONE, CU_TENSOR_MAP_FLOAT_OOB_FILL_NONE);
    }
    {
      const cuuint64_t dims[2] = {D_, F_}, strides[1] = {D_ * 2};
      const cuuint32_t box[2] = {16, 256};
      encode(&tmd, CU_TENSOR_MAP_DATA_TYPE_BFLOAT16, 2, d_in[10], dims, strides, box, es, CU_TENSOR_MAP_INTERLEAVE_NONE,
             CU_TENSOR_MAP_SWIZZLE_NONE, CU_TENSOR_MAP_L2_PROMOTION_NONE, CU_TENSOR_MAP_FLOAT_OOB_FILL_NONE);
    }
    cached[0] = d_in[8]; cached[1] = d_in[9]; cached[2] = d_in[10];
  }
  fused_kernel<<<NCTA, NTHR, sizeof(Smem), cudaStreamPerThread>>>(
      tmg, tmu, tmd, (const bf16*)d_in[0], (const bf16*)d_in[1], (const bf16*)d_in[2], (const bf16*)d_in[3],
      (const bf16*)d_in[4], (const bf16*)d_in[5], (const bf16*)d_in[7], (bf16*)d_out);
}
```

```cpp
#include <cuda_runtime.h>
#include <cuda_bf16.h>
#include <cuda.h>
#include <stdint.h>

namespace {

typedef __nv_bfloat16 bf16;
typedef __nv_bfloat162 bf162;

constexpr int S_ = 2048, D_ = 640, F_ = 1536;
constexpr int NCTA = 128, CPC = 5, NTHR = 384;
constexpr int UPAD = 136, USTR = 2192;
constexpr int TABW = 1040;
constexpr int ZPB = 132;
constexpr int QSTR = 648;
constexpr int N1 = 64;
constexpr int N2 = 40;
constexpr int SPIN_LIMIT = 1 << 19;
#define LN2_EXACT 1
#define ABL 0
#define CTR_NS 0
#define C_DELAY 0
#define TESTV 0
#define TESTC 0
#define POLL_NS 100
#define H_DELAY 0
#define Q_DELAY 4500

struct __align__(128) Smem {
  uint32_t tabA[3][2][TABW];
  uint32_t extra[1024];
  uint32_t tabB[2][2][TABW];
  bf16 u[CPC][USTR];
  float z[2][4][ZPB * 16];
  bf16 q[16][QSTR];
  alignas(128) uint4 w[3840];
  uint4 wr[80];
  float2 st[16][5];
  float2 stq[16][5];
  float rp[16][5];
  unsigned long long mbar;
  unsigned long long mbarw;
  unsigned long long mbarc;
  unsigned long long mbary;
  unsigned long long mbarh;
  uint32_t target;
  uint32_t target2;
  uint32_t best;
  uint32_t win;
};

__device__ uint4 g_kv[D_ * S_ / 8];
__device__ uint4 g_y2[D_ * S_ / 8];
__device__ uint32_t g_keys[NCTA][NCTA];
__device__ uint4 g_cand[NCTA][2][80];
__device__ uint4 g_act[N2][F_ / 8];
__device__ unsigned int g_ctr;
__device__ unsigned int g_ctr2;
__device__ unsigned int g_ctr3;
#define STAMP(i)
#define CST(c, i)

__device__ __forceinline__ uint32_t smem_u32(const void* p) { return (uint32_t)__cvta_generic_to_shared(p); }
__device__ __forceinline__ void wg_fence() { asm volatile("wgmma.fence.sync.aligned;" ::: "memory"); }
__device__ __forceinline__ void wg_commit() { asm volatile("wgmma.commit_group.sync.aligned;" ::: "memory"); }
template <int N> __device__ __forceinline__ void wg_wait() { asm volatile("wgmma.wait_group.sync.aligned %0;" ::"n"(N) : "memory"); }
__device__ __forceinline__ void bar_sync(int id, int n) { asm volatile("bar.sync %0, %1;" ::"r"(id), "r"(n) : "memory"); }
__device__ __forceinline__ void bar_arrive(int id, int n) { asm volatile("bar.arrive %0, %1;" ::"r"(id), "r"(n) : "memory"); }
__device__ __forceinline__ bf162 u2b(uint32_t u) { return *reinterpret_cast<bf162*>(&u); }
__device__ __forceinline__ uint32_t b2u(bf162 b) { return *reinterpret_cast<uint32_t*>(&b); }
__device__ __forceinline__ float lo_f(uint32_t u) { return __uint_as_float(u << 16); }
__device__ __forceinline__ float hi_f(uint32_t u) { return __uint_as_float(u & 0xFFFF0000u); }
__device__ __forceinline__ float rbf(float x) { return __bfloat162float(__float2bfloat16_rn(x)); }
__device__ __forceinline__ uint32_t pack2(float a, float b) { return b2u(__floats2bfloat162_rn(a, b)); }
__device__ __forceinline__ uint32_t enc(uint32_t w) { return max(~w, 1u); }
__device__ __forceinline__ uint4 enc4(uint4 v) { return make_uint4(enc(v.x), enc(v.y), enc(v.z), enc(v.w)); }
__device__ __forceinline__ uint4 ld_poll4(const uint4* p) {
  uint4 v;
  asm volatile("ld.relaxed.gpu.global.v4.u32 {%0,%1,%2,%3}, [%4];" : "=r"(v.x), "=r"(v.y), "=r"(v.z), "=r"(v.w) : "l"(p) : "memory");
  return v;
}
__device__ __forceinline__ bool ready4(uint4 v) { return v.x != 0u && v.y != 0u && v.z != 0u && v.w != 0u; }
__device__ __forceinline__ uint4 poll4(const uint4* p) {
  uint4 v = ld_poll4(p);
  int it = 0;
  while (!ready4(v) && ++it < SPIN_LIMIT) v = ld_poll4(p);
  return make_uint4(~v.x, ~v.y, ~v.z, ~v.w);
}
__device__ __forceinline__ void st_pub4(uint4* p, uint4 v) {
  asm volatile("st.relaxed.gpu.global.v4.u32 [%0], {%1,%2,%3,%4};" ::"l"(p), "r"(v.x), "r"(v.y), "r"(v.z), "r"(v.w) : "memory");
}
__device__ __forceinline__ void st_pub2(uint2* p, uint32_t a, uint32_t b) {
  asm volatile("st.relaxed.gpu.global.v2.u32 [%0], {%1,%2};" ::"l"(p), "r"(a), "r"(b) : "memory");
}
__device__ __forceinline__ void mma_bf16(float (&c)[4], uint32_t a0, uint32_t a2, uint32_t b0, uint32_t b1) {
  asm volatile("mma.sync.aligned.m16n8k16.row.col.f32.bf16.bf16.f32 {%0,%1,%2,%3}, {%4,%5,%6,%5}, {%7,%8}, {%0,%1,%2,%3};"
               : "+f"(c[0]), "+f"(c[1]), "+f"(c[2]), "+f"(c[3]) : "r"(a0), "r"(0u), "r"(a2), "r"(b0), "r"(b1));
}
__device__ __forceinline__ void mbar_wait(const unsigned long long* bar) {
  const uint32_t mb = smem_u32(bar);
  uint32_t ok = 0;
  int it = 0;
  while (!ok && ++it < SPIN_LIMIT)
    asm volatile("{ .reg .pred p; mbarrier.try_wait.parity.shared.b64 p, [%1], 0; selp.u32 %0, 1, 0, p; }" : "=r"(ok) : "r"(mb) : "memory");
}
__device__ __forceinline__ void bulk_g2s(void* dst, const void* src, uint32_t bytes, const unsigned long long* bar) {
  asm volatile("cp.async.bulk.shared::cluster.global.mbarrier::complete_tx::bytes [%0], [%1], %2, [%3];" ::"r"(smem_u32(dst)),
               "l"(src), "r"(bytes), "r"(smem_u32(bar)) : "memory");
}
__device__ __forceinline__ void mbar_expect(const unsigned long long* bar, uint32_t bytes) {
  asm volatile("mbarrier.arrive.expect_tx.shared.b64 _, [%0], %1;" ::"r"(smem_u32(bar)), "r"(bytes) : "memory");
}
__device__ __forceinline__ void mma_bf16x(float (&c)[4], uint32_t a0, uint32_t a1, uint32_t a2, uint32_t a3, uint32_t b0, uint32_t b1) {
  asm volatile("mma.sync.aligned.m16n8k16.row.col.f32.bf16.bf16.f32 {%0,%1,%2,%3}, {%4,%5,%6,%7}, {%8,%9}, {%0,%1,%2,%3};"
               : "+f"(c[0]), "+f"(c[1]), "+f"(c[2]), "+f"(c[3]) : "r"(a0), "r"(a1), "r"(a2), "r"(a3), "r"(b0), "r"(b1));
}
__device__ __forceinline__ float fdivr(float a, float d, float r) {
  float q = a * r;
  float e = fmaf(-q, d, a);
  return fmaf(e, r, q);
}

template <bool FIRST> __device__ __forceinline__ void wgmma32(float (&d)[16], const uint32_t* a, uint64_t desc) {
  if (FIRST) {
    asm volatile("wgmma.mma_async.sync.aligned.m64n32k16.f32.bf16.bf16 {%0,%1,%2,%3,%4,%5,%6,%7,%8,%9,%10,%11,%12,%13,%14,%15}, {%16,%17,%18,%19}, %20, 0, 1, 1, 0;"
                 : "+f"(d[0]), "+f"(d[1]), "+f"(d[2]), "+f"(d[3]), "+f"(d[4]), "+f"(d[5]), "+f"(d[6]), "+f"(d[7]),
                   "+f"(d[8]), "+f"(d[9]), "+f"(d[10]), "+f"(d[11]), "+f"(d[12]), "+f"(d[13]), "+f"(d[14]), "+f"(d[15])
                 : "r"(a[0]), "r"(a[1]), "r"(a[2]), "r"(a[3]), "l"(desc));
  } else {
    asm volatile("wgmma.mma_async.sync.aligned.m64n32k16.f32.bf16.bf16 {%0,%1,%2,%3,%4,%5,%6,%7,%8,%9,%10,%11,%12,%13,%14,%15}, {%16,%17,%18,%19}, %20, 1, 1, 1, 0;"
                 : "+f"(d[0]), "+f"(d[1]), "+f"(d[2]), "+f"(d[3]), "+f"(d[4]), "+f"(d[5]), "+f"(d[6]), "+f"(d[7]),
                   "+f"(d[8]), "+f"(d[9]), "+f"(d[10]), "+f"(d[11]), "+f"(d[12]), "+f"(d[13]), "+f"(d[14]), "+f"(d[15])
                 : "r"(a[0]), "r"(a[1]), "r"(a[2]), "r"(a[3]), "l"(desc));
  }
}

template <int G> __device__ __forceinline__ void load_a(uint32_t (&a)[8], const uint32_t* tp) {
#pragma unroll
  for (int q = 0; q < 2; q++) {
    const int e = 2 * G + q;
    a[4 * q + 0] = tp[-64 * e];
    a[4 * q + 1] = tp[-64 * e - 32];
    a[4 * q + 2] = tp[-64 * e + 4];
    a[4 * q + 3] = tp[-64 * e - 28];
  }
}
__device__ __forceinline__ void load_a_all(uint32_t (&a)[8][8], const uint32_t* tp) {
  load_a<0>(a[0], tp); load_a<1>(a[1], tp); load_a<2>(a[2], tp); load_a<3>(a[3], tp);
  load_a<4>(a[4], tp); load_a<5>(a[5], tp); load_a<6>(a[6], tp); load_a<7>(a[7], tp);
}
template <int G> __device__ __forceinline__ void issue_g(float (&acc)[8][16], uint32_t (&a)[8], uint64_t desc0) {
  wg_fence();
#pragma unroll
  for (int q = 0; q < 2; q++) {
#pragma unroll
    for (int b = G; b < 8; b++) {
      const int delta = 2 * b - (2 * G + q);
      if (G == 0 && q == 0) wgmma32<true>(acc[b], &a[4 * q], desc0 + (uint64_t)(int64_t)(16 * delta));
      else wgmma32<false>(acc[b], &a[4 * q], desc0 + (uint64_t)(int64_t)(16 * delta));
    }
  }
  wg_commit();
}
template <int B> __device__ __forceinline__ void fence_blk(float (&acc)[8][16]) {
#pragma unroll
  for (int i = 0; i < 16; i++) asm volatile("" : "+f"(acc[B][i])::"memory");
}
__device__ __forceinline__ void fence_a(uint32_t (&a)[8]) {
#pragma unroll
  for (int i = 0; i < 8; i++) asm volatile("" : "+r"(a[i])::"memory");
}
template <int B> __device__ __forceinline__ void sts_blk(float (&acc)[8][16], float* zw, int off_even, int off_odd) {
#pragma unroll
  for (int jj = 0; jj < 4; jj++) {
    const int j = 4 * B + jj;
    float p0 = acc[B][4 * jj + 0], p1 = acc[B][4 * jj + 1];
    if (jj > 0) { p0 += acc[B][4 * (jj - 1) + 2]; p1 += acc[B][4 * (jj - 1) + 3]; }
    else if (B > 0) { p0 += acc[B > 0 ? B - 1 : 0][14]; p1 += acc[B > 0 ? B - 1 : 0][15]; }
    zw[64 * j + off_even] = p0;
    zw[64 * j + off_odd] = p1;
  }
}
__device__ __forceinline__ int tab_off(int c) { return c == 4 ? 0 : (c + 1) * 2 * TABW + (c >= 2 ? 1024 : 0); }
__device__ __forceinline__ int tile_perm(int ch) { return ch ^ (((ch >> 3) & 3) << 1); }

__device__ __forceinline__ void wait_ctr(const unsigned int* ctr, uint32_t target) {
  uint32_t v;
  int it = 0;
  do {
    asm volatile("ld.acquire.gpu.global.u32 %0, [%1];" : "=r"(v) : "l"(ctr) : "memory");
  } while ((int)(v - target) < 0 && ++it < SPIN_LIMIT);
}

__device__ __forceinline__ float2 row_part_stats(const uint32_t (&x)[16]) {
  float cs[4][4];
#pragma unroll
  for (int k = 0; k < 4; k++) {
    cs[k][0] = cs[k][1] = cs[k][2] = cs[k][3] = 0.f;
    mma_bf16x(cs[k], x[4 * k + 0], x[4 * k + 2], x[4 * k + 1], x[4 * k + 3], 0x3F803F80u, 0x3F803F80u);
  }
  const float mean = (((cs[0][0] + cs[0][2]) + (cs[1][0] + cs[1][2])) + ((cs[2][0] + cs[2][2]) + (cs[3][0] + cs[3][2]))) * (1.f / 128.f);
  float m2a = 0.f, m2b = 0.f, m2c = 0.f, m2d = 0.f;
#pragma unroll
  for (int i = 0; i < 16; i += 2) {
    const float a = lo_f(x[i]) - mean, b = hi_f(x[i]) - mean, c = lo_f(x[i + 1]) - mean, d = hi_f(x[i + 1]) - mean;
    m2a = fmaf(a, a, m2a); m2b = fmaf(b, b, m2b); m2c = fmaf(c, c, m2c); m2d = fmaf(d, d, m2d);
  }
  float m2 = (m2a + m2b) + (m2c + m2d);
  m2 += __shfl_xor_sync(0xffffffffu, m2, 1);
  m2 += __shfl_xor_sync(0xffffffffu, m2, 2);
  return make_float2(mean, m2);
}
__device__ __forceinline__ void row_normalize(const float2* st, const uint32_t (&x)[16], uint32_t (&y)[16]) {
  float mean = 0.f, m2 = 0.f;
  float2 p[5];
#pragma unroll
  for (int i = 0; i < 5; i++) { p[i] = st[i]; mean += p[i].x; }
  mean *= 0.2f;
#pragma unroll
  for (int i = 0; i < 5; i++) { const float dl = p[i].x - mean; m2 += p[i].y + 128.f * dl * dl; }
  const float hd = rbf(sqrtf(rbf(rbf(m2 * (1.f / D_)) + 1e-5f)));
  const float hr = 1.f / hd;
  const bf162 hm2 = __float2bfloat162_rn(mean);
#pragma unroll
  for (int i = 0; i < 16; i++) {
    const uint32_t d = b2u(__hsub2_rn(u2b(x[i]), hm2));
    y[i] = pack2(fdivr(lo_f(d), hd, hr), fdivr(hi_f(d), hd, hr));
  }
}

__device__ __forceinline__ void gather_kv(Smem& sm, int c0, int tid) {
  mbar_wait(&sm.mbarc);
  uint4 v[4];
  uint4* src = g_kv + c0 * 256 + tid;
#pragma unroll
  for (int i = 0; i < 4; i++) if (i < 3 || tid >= 256) v[i] = ld_poll4(src + NTHR * i - (i == 3 ? 256 : 0));
#pragma unroll
  for (int i = 0; i < 4; i++) {
    if (i < 3 || tid >= 256) {
      const int t = tid + NTHR * i - (i == 3 ? 256 : 0);
      int it = 0;
      while (!ready4(v[i]) && ++it < SPIN_LIMIT) { __nanosleep(POLL_NS); v[i] = ld_poll4(g_kv + c0 * 256 + t); }
      *reinterpret_cast<uint4*>(&sm.u[t >> 8][UPAD + (t & 255) * 8]) = make_uint4(~v[i].x, ~v[i].y, ~v[i].z, ~v[i].w);
    }
  }
  asm volatile("fence.proxy.async.shared::cta;" ::: "memory");
  __syncthreads();
}

__global__ void __launch_bounds__(NTHR, 1)
fused_kernel(const __grid_constant__ CUtensorMap tmg, const __grid_constant__ CUtensorMap tmu,
             const __grid_constant__ CUtensorMap tmd, const bf16* __restrict__ gq, const bf16* __restrict__ gk, const bf16* __restrict__ gv,
             const bf16* __restrict__ gsk, const bf16* __restrict__ gh, const bf16* __restrict__ gD,
             const bf16* __restrict__ gwr, bf16* __restrict__ gout) {
  extern __shared__ __align__(128) unsigned char smraw[];
  Smem& sm = *reinterpret_cast<Smem*>(smraw);
  const int tid = threadIdx.x;
  const int cta = blockIdx.x;
  const int c0 = cta * CPC;
  const int lane = tid & 31;
  const int wid = tid >> 5;
  STAMP(0);
  const long long tstart = clock64();

  {
    uint4* hs = reinterpret_cast<uint4*>(&sm.z[0][0][0]);
    const int oc = tid >> 2;
    const int r0 = cta * 16 + (tid & 3) * 4;
    uint4 kk[7], vv[4], sk[4];
    if (tid < 320) {
      const uint4* kp = reinterpret_cast<const uint4*>(gk) + (size_t)r0 * 80 + oc;
      const uint4* vp = reinterpret_cast<const uint4*>(gv) + (size_t)r0 * 80 + oc;
#pragma unroll
      for (int i = 0; i < 7; i++) kk[i] = (i >= 3 || r0 > 0) ? __ldg(kp + (i - 3) * 80) : make_uint4(0, 0, 0, 0);
#pragma unroll
      for (int i = 0; i < 4; i++) vv[i] = __ldg(vp + i * 80);
#pragma unroll
      for (int i = 0; i < 4; i++) sk[i] = __ldg(reinterpret_cast<const uint4*>(gsk) + oc * 4 + i);
    } else if (tid == 320) {
      asm volatile("mbarrier.init.shared.b64 [%0], 1;" ::"r"(smem_u32(&sm.mbarh)) : "memory");
      asm volatile("mbarrier.init.shared.b64 [%0], 1;" ::"r"(smem_u32(&sm.mbar)) : "memory");
      asm volatile("mbarrier.init.shared.b64 [%0], 1;" ::"r"(smem_u32(&sm.mbarw)) : "memory");
      asm volatile("mbarrier.init.shared.b64 [%0], 1;" ::"r"(smem_u32(&sm.mbarc)) : "memory");
      asm volatile("mbarrier.init.shared.b64 [%0], 1;" ::"r"(smem_u32(&sm.mbary)) : "memory");
      asm volatile("fence.proxy.async.shared::cta;" ::: "memory");
    }
    if (tid < 320) bar_sync(6, 384); else { bar_arrive(6, 384); bar_sync(5, 64); }
    STAMP(9);
    if (tid < 320) {
      uint32_t o[4][4];
#pragma unroll
      for (int p = 0; p < 4; p++) {
        const bf162 w0 = u2b(__byte_perm(sk[p].x, sk[p].z, 0x5410)), w1 = u2b(__byte_perm(sk[p].x, sk[p].z, 0x7632));
        const bf162 w2 = u2b(__byte_perm(sk[p].y, sk[p].w, 0x5410)), w3 = u2b(__byte_perm(sk[p].y, sk[p].w, 0x7632));
        uint32_t kv[4];
#pragma unroll
        for (int i = 0; i < 4; i++) {
          const uint32_t k0 = p == 0 ? kk[i].x : p == 1 ? kk[i].y : p == 2 ? kk[i].z : kk[i].w;
          const uint32_t k1 = p == 0 ? kk[i + 1].x : p == 1 ? kk[i + 1].y : p == 2 ? kk[i + 1].z : kk[i + 1].w;
          const uint32_t k2 = p == 0 ? kk[i + 2].x : p == 1 ? kk[i + 2].y : p == 2 ? kk[i + 2].z : kk[i + 2].w;
          const uint32_t k3 = p == 0 ? kk[i + 3].x : p == 1 ? kk[i + 3].y : p == 2 ? kk[i + 3].z : kk[i + 3].w;
          const uint32_t vx = p == 0 ? vv[i].x : p == 1 ? vv[i].y : p == 2 ? vv[i].z : vv[i].w;
          bf162 a = __hmul2_rn(u2b(k0), w3);
          a = __hadd2_rn(a, __hmul2_rn(u2b(k1), w2));
          a = __hadd2_rn(a, __hmul2_rn(u2b(k2), w1));
          a = __hadd2_rn(a, __hmul2_rn(u2b(k3), w0));
          kv[i] = b2u(__hmul2_rn(a, u2b(vx)));
        }
        o[p][0] = enc(__byte_perm(kv[0], kv[1], 0x5410)); o[p][1] = enc(__byte_perm(kv[2], kv[3], 0x5410));
        o[p][2] = enc(__byte_perm(kv[0], kv[1], 0x7632)); o[p][3] = enc(__byte_perm(kv[2], kv[3], 0x7632));
      }
      uint2* dst = reinterpret_cast<uint2*>(g_kv) + (size_t)(oc * 8) * 512 + (r0 >> 2);
#pragma unroll
      for (int p = 0; p < 4; p++) {
        st_pub2(dst + (2 * p) * 512, o[p][0], o[p][1]);
        st_pub2(dst + (2 * p + 1) * 512, o[p][2], o[p][3]);
      }
      STAMP(10);
      if (wid == 0) bar_sync(4, 320); else bar_arrive(4, 320);
      if (tid == 0) {
        const unsigned old = atomicAdd(&g_ctr2, 1u);
        sm.target2 = (old / NCTA + 1u) * NCTA;
      }
      __syncwarp();
    } else {
      const int t0 = tid - 320;
      const uint4 zz = make_uint4(0, 0, 0, 0);
      if (tid == 320) {
        while (clock64() - tstart < H_DELAY) {}
        mbar_expect(&sm.mbarh, CPC * S_ * 2);
        bulk_g2s(hs, gh + (size_t)c0 * S_, CPC * S_ * 2, &sm.mbarh);
      }
      __syncwarp();
      for (int t = t0; t < CPC * 17; t += 64) *reinterpret_cast<uint4*>(&sm.u[t / 17][(t % 17) * 8]) = zz;
      if (t0 < 40) *reinterpret_cast<uint4*>(&sm.tabA[0][0][0] + tab_off(t0 >> 3) + ((t0 >> 2) & 1) * TABW + 1024 + 4 * (t0 & 3)) = zz;
      while (clock64() - tstart < C_DELAY) {}
      (&g_cand[cta][0][0])[t0] = zz;
      (&g_cand[cta][0][0])[64 + t0] = zz;
      if (t0 < 32) (&g_cand[cta][0][0])[128 + t0] = zz;
      else reinterpret_cast<uint4*>(&g_keys[cta][0])[t0 - 32] = zz;
      if (cta >= N1 && cta < N1 + N2) {
#pragma unroll
        for (int i = 0; i < 3; i++) g_act[cta - N1][t0 + 64 * i] = zz;
      }
      bar_sync(5, 64);
      if (tid == 352) {
        __threadfence();
        const unsigned old = atomicAdd(&g_ctr, 1u);
        sm.target = (old / NCTA + 1u) * NCTA;
      }
      __syncwarp();
    }
    mbar_wait(&sm.mbarh);
#pragma unroll
    for (int i = 0; i < 4; i++) {
      const int t = (NTHR - 1 - tid) + NTHR * i;
      if (t < CPC * 256) {
        uint32_t* tb = &sm.tabA[0][0][0] + tab_off(t >> 8) + (255 - (t & 255)) * 4;
        const uint4 h = hs[t];
        const uint32_t hp = (t & 255) ? reinterpret_cast<const uint32_t*>(hs)[4 * t - 1] : 0u;
        uint4 r1, rr;
        r1.x = __byte_perm(h.w, 0, 0x1032); r1.y = __byte_perm(h.z, 0, 0x1032);
        r1.z = __byte_perm(h.y, 0, 0x1032); r1.w = __byte_perm(h.x, 0, 0x1032);
        rr.x = __byte_perm(h.w, h.z, 0x7610); rr.y = __byte_perm(h.z, h.y, 0x7610);
        rr.z = __byte_perm(h.y, h.x, 0x7610); rr.w = __byte_perm(h.x, hp, 0x7610);
        *reinterpret_cast<uint4*>(tb) = rr;
        *reinterpret_cast<uint4*>(tb + TABW) = r1;
      }
    }
    STAMP(12);
  }
  __syncthreads();

  const int wg = __shfl_sync(0xffffffffu, tid >> 7, 0);
  const int wtid = tid & 127;
  uint4* tile = reinterpret_cast<uint4*>(&sm.tabB[0][0][0]);
  if (wg < 2) {
    asm volatile("setmaxnreg.inc.sync.aligned.u32 224;");
    const int w = (tid >> 5) & 3, g = lane >> 2, tq = lane & 3;
    float* zw = sm.z[wg][w];
    const int sw = 3 * (((tq + w) >> 1) & 1);
    const int off_even = 16 * (tq + w) + 4 * ((0 + (g >> 2)) ^ sw) + (g & 3);
    const int off_odd = 16 * (tq + w) + 4 * ((2 + (g >> 2)) ^ sw) + (g & 3);
    uint32_t a[8][8];
    const uint32_t* tp0 = &sm.tabA[0][g & 1][1019 - 8 * w - (g >> 1) + tq];
    load_a_all(a, tp0 + tab_off(wg));
    float acc[8][16];
#pragma unroll
    for (int b = 0; b < 8; b++)
#pragma unroll
      for (int i = 0; i < 16; i++) acc[b][i] = 0.f;
    gather_kv(sm, c0, tid);
    STAMP(1);
#pragma unroll 1
    for (int c = wg; c < CPC; c += 2) {
      const uint64_t desc = (uint64_t)((smem_u32(&sm.u[c][UPAD - 8]) & 0x3FFFF) >> 4) | ((uint64_t)1 << 16) | ((uint64_t)8 << 32);
      CST(c, 0);
      if (c > 0) bar_sync(1 + wg, 256);
      issue_g<0>(acc, a[0], desc);
      CST(c, 1);
      issue_g<1>(acc, a[1], desc);
      issue_g<2>(acc, a[2], desc);
      issue_g<3>(acc, a[3], desc);
      issue_g<4>(acc, a[4], desc);
      issue_g<5>(acc, a[5], desc);
      if (c + 1 < CPC) bar_arrive(1 + (wg ^ 1), 256);
      issue_g<6>(acc, a[6], desc);
      issue_g<7>(acc, a[7], desc);
      CST(c, 2);
      if (c >= 2) bar_sync(5 + wg, 256);
      wg_wait<4>();
      fence_blk<0>(acc); fence_blk<1>(acc); fence_blk<2>(acc); fence_blk<3>(acc);
      sts_blk<0>(acc, zw, off_even, off_odd);
      sts_blk<1>(acc, zw, off_even, off_odd);
      sts_blk<2>(acc, zw, off_even, off_odd);
      sts_blk<3>(acc, zw, off_even, off_odd);
      bar_arrive(9 + wg, 256);
      CST(c, 3);
      wg_wait<0>();
      fence_blk<4>(acc); fence_blk<5>(acc); fence_blk<6>(acc); fence_blk<7>(acc);
#pragma unroll
      for (int i = 0; i < 8; i++) fence_a(a[i]);
      sts_blk<4>(acc, zw, off_even, off_odd);
      sts_blk<5>(acc, zw, off_even, off_odd);
      sts_blk<6>(acc, zw, off_even, off_odd);
      sts_blk<7>(acc, zw, off_even, off_odd);
      bar_arrive(3 + wg, 256);
      CST(c, 4);
      if (c + 2 < CPC) load_a_all(a, tp0 + tab_off(c + 2));
    }
    STAMP(2 + wg);
    asm volatile("setmaxnreg.dec.sync.aligned.u32 168;");
  } else {
    asm volatile("setmaxnreg.dec.sync.aligned.u32 56;");
    if (((wtid & 15) >> 2) < ((wtid >> 4) & 3))
      *reinterpret_cast<uint4*>(&sm.z[wtid >> 6][(wtid >> 4) & 3][(wtid & 15) * 4]) = make_uint4(0, 0, 0, 0);
    if (wtid == 64) {
      const unsigned target = sm.target2;
      uint32_t v;
      int it = 0;
      do {
        asm volatile("ld.relaxed.gpu.global.u32 %0, [%1];" : "=r"(v) : "l"(&g_ctr2) : "memory");
      } while ((int)(v - target) < 0 && ++it < SPIN_LIMIT);
      asm volatile("mbarrier.arrive.shared.b64 _, [%0];" ::"r"(smem_u32(&sm.mbarc)) : "memory");
    }
    __syncwarp();
    gather_kv(sm, c0, tid);
#pragma unroll
    for (int i = 0; i < 10; i++) g_kv[c0 * 256 + wtid + 128 * i] = make_uint4(0, 0, 0, 0);
    if (wtid == 32) {
      const uint32_t mw = smem_u32(&sm.mbarw);
      mbar_expect(&sm.mbar, 17 * D_ * 2);
#pragma unroll 1
      for (int r = 0; r < 16; r++) bulk_g2s(&sm.q[r][0], gq + (size_t)(cta * 16 + r) * D_, D_ * 2, &sm.mbar);
      bulk_g2s(&sm.wr[0], gwr, D_ * 2, &sm.mbar);
      if (cta < N1) {
        asm volatile("mbarrier.arrive.expect_tx.shared.b64 _, [%0], %1;" ::"r"(mw), "r"(3840 * 16) : "memory");
#pragma unroll 1
        for (int i = 0; i < 4; i++) {
          asm volatile("cp.async.bulk.tensor.2d.shared::cluster.global.mbarrier::complete_tx::bytes [%0], [%1, {%3, %4}], [%2];" ::"r"(smem_u32(&sm.w[i * 480])),
                       "l"(&tmg), "r"(mw), "r"(cta * 24), "r"(i * 160) : "memory");
          asm volatile("cp.async.bulk.tensor.2d.shared::cluster.global.mbarrier::complete_tx::bytes [%0], [%1, {%3, %4}], [%2];" ::"r"(smem_u32(&sm.w[1920 + i * 480])),
                       "l"(&tmu), "r"(mw), "r"(cta * 24), "r"(i * 160) : "memory");
        }
      } else if (cta < N1 + N2) {
        asm volatile("mbarrier.arrive.expect_tx.shared.b64 _, [%0], %1;" ::"r"(mw), "r"(3072 * 16) : "memory");
#pragma unroll 1
        for (int i = 0; i < 6; i++)
          asm volatile("cp.async.bulk.tensor.2d.shared::cluster.global.mbarrier::complete_tx::bytes [%0], [%1, {%3, %4}], [%2];" ::"r"(smem_u32(&sm.w[i * 512])),
                       "l"(&tmd), "r"(mw), "r"((cta - N1) * 16), "r"(i * 256) : "memory");
      }
    }
    const int rpb = wtid >> 1, re2 = wtid & 1;
    const int rsw = 3 * ((rpb >> 1) & 1);
    const int roff0 = 16 * rpb + 4 * ((2 * re2 + 0) ^ rsw);
    const int roff1 = 16 * rpb + 4 * ((2 * re2 + 1) ^ rsw);
    const uint32_t dvl = reinterpret_cast<const unsigned short*>(gD)[c0 + (lane < CPC ? lane : 0)];
#pragma unroll 1
    for (int c = 0; c < CPC; c++) {
      const int zg = c & 1;
      const uint32_t dvc = __shfl_sync(0xffffffffu, dvl, c);
      const bf162 d2 = u2b(dvc | (dvc << 16));
      CST(c, 5);
#pragma unroll
      for (int half = 0; half < 2; half++) {
        bar_sync((half ? 3 : 9) + zg, 256);
        const float* zb = sm.z[zg][0] + half * 1024;
        float4 x[4][2];
#pragma unroll
        for (int ww = 0; ww < 4; ww++) {
          x[ww][0] = *reinterpret_cast<const float4*>(zb + ww * ZPB * 16 + roff0);
          x[ww][1] = *reinterpret_cast<const float4*>(zb + ww * ZPB * 16 + roff1);
        }
        const int sidx = half * 1024 + wtid * 8;
        const uint4 kvv = *reinterpret_cast<const uint4*>(&sm.u[c][UPAD + sidx]);
        if (half == 1 && c + 2 < CPC) bar_arrive(5 + zg, 256);
        uint4 o;
        o.x = pack2((x[0][0].x + x[1][0].x) + (x[2][0].x + x[3][0].x), (x[0][0].y + x[1][0].y) + (x[2][0].y + x[3][0].y));
        o.y = pack2((x[0][0].z + x[1][0].z) + (x[2][0].z + x[3][0].z), (x[0][0].w + x[1][0].w) + (x[2][0].w + x[3][0].w));
        o.z = pack2((x[0][1].x + x[1][1].x) + (x[2][1].x + x[3][1].x), (x[0][1].y + x[1][1].y) + (x[2][1].y + x[3][1].y));
        o.w = pack2((x[0][1].z + x[1][1].z) + (x[2][1].z + x[3][1].z), (x[0][1].w + x[1][1].w) + (x[2][1].w + x[3][1].w));
        o.x = b2u(__hadd2_rn(u2b(o.x), __hmul2_rn(u2b(kvv.x), d2)));
        o.y = b2u(__hadd2_rn(u2b(o.y), __hmul2_rn(u2b(kvv.y), d2)));
        o.z = b2u(__hadd2_rn(u2b(o.z), __hmul2_rn(u2b(kvv.z), d2)));
        o.w = b2u(__hadd2_rn(u2b(o.w), __hmul2_rn(u2b(kvv.w), d2)));
        st_pub4(g_y2 + ((64 * half + rpb) * 640 + c0 + c) * 2 + re2, enc4(o));
        CST(c, 6 + half);
      }
    }
    if (wid == 11) bar_sync(8, 128); else bar_arrive(8, 128);
    STAMP(4);
    asm volatile("setmaxnreg.inc.sync.aligned.u32 168;");
  }

  if (tid == 352) {
    const unsigned old = atomicAdd(&g_ctr3, 1u);
    wait_ctr(&g_ctr, sm.target);
    wait_ctr(&g_ctr3, (old / NCTA + 1u) * NCTA);
    asm volatile("mbarrier.arrive.shared.b64 _, [%0];" ::"r"(smem_u32(&sm.mbary)) : "memory");
  }
  __syncwarp();
  if (ABL == 4) { if (cta < N1 + N2) mbar_wait(&sm.mbarw); mbar_wait(&sm.mbar); return; }
  const int g = lane >> 2, tq = lane & 3;
  const int hh = wid & 1, gqi = wid >> 1;
  const int row = hh * 8 + g;
  uint32_t hreg[16], hnreg[16];
  {
    const uint4* src = g_y2 + cta * 1280 + tid;
    uint4 v[4];
    if (wid < 10) {
      mbar_wait(&sm.mbar);
#pragma unroll
      for (int k = 0; k < 4; k++) {
        const uint4 qv4 = *reinterpret_cast<const uint4*>(&sm.q[row][32 * (4 * gqi + k) + 8 * tq]);
        hreg[4 * k] = qv4.x; hreg[4 * k + 1] = qv4.y; hreg[4 * k + 2] = qv4.z; hreg[4 * k + 3] = qv4.w;
      }
      const float2 ps = row_part_stats(hreg);
      if (tq == 0) sm.stq[row][gqi] = ps;
      bar_sync(7, 320);
      row_normalize(sm.stq[row], hreg, hnreg);
    }
    mbar_wait(&sm.mbary);
#pragma unroll
    for (int i = 0; i < 4; i++) if (i < 3 || tid < 128) v[i] = ld_poll4(src + NTHR * i);
    int it = 0;
    bool all;
    do {
      all = true;
#pragma unroll
      for (int i = 0; i < 4; i++)
        if ((i < 3 || tid < 128) && !ready4(v[i])) { v[i] = ld_poll4(src + NTHR * i); all = false; }
    } while (!all && ++it < SPIN_LIMIT);
#pragma unroll
    for (int i = 0; i < 4; i++) {
      if (i < 3 || tid < 128) {
        const int t = tid + NTHR * i;
        tile[(t & 1) * 640 + tile_perm(t >> 1)] = make_uint4(~v[i].x, ~v[i].y, ~v[i].z, ~v[i].w);
      }
    }
  }
  __syncthreads();
  STAMP(5);
  if (ABL == 3) { if (cta < N1 + N2) mbar_wait(&sm.mbarw); return; }

  if (wid < 10) {
#pragma unroll
    for (int k = 0; k < 4; k++) {
      const int base = 32 * (4 * gqi + k);
      const int lch = base + 8 * ((lane & 7) >> 1) + 2 * (lane >> 3) + (lane & 1);
      uint32_t y[4];
      asm volatile("ldmatrix.sync.aligned.m8n8.x4.trans.shared.b16 {%0,%1,%2,%3}, [%4];"
                   : "=r"(y[0]), "=r"(y[1]), "=r"(y[2]), "=r"(y[3]) : "r"(smem_u32(&tile[hh * 640 + tile_perm(lch)])) : "memory");
#pragma unroll
      for (int i = 0; i < 4; i++)
        hreg[4 * k + i] = b2u(__hadd2_rn(u2b(hreg[4 * k + i]), __hmul2_rn(u2b(hnreg[4 * k + i]), u2b(y[i]))));
    }
    const float2 ps = row_part_stats(hreg);
    if (tq == 0) sm.st[row][gqi] = ps;
    STAMP(13);
    bar_sync(7, 320);
    row_normalize(sm.st[row], hreg, hnreg);
    float cr[4][4];
#pragma unroll
    for (int k = 0; k < 4; k++) {
      cr[k][0] = cr[k][1] = cr[k][2] = cr[k][3] = 0.f;
      const uint4 w4 = sm.wr[4 * (4 * gqi + k) + tq];
      mma_bf16(cr[k], hnreg[4 * k + 0], hnreg[4 * k + 1], w4.x, w4.y);
      mma_bf16(cr[k], hnreg[4 * k + 2], hnreg[4 * k + 3], w4.z, w4.w);
    }
    if (tq == 0) sm.rp[row][gqi] = (cr[0][0] + cr[1][0]) + (cr[2][0] + cr[3][0]);
  }
  STAMP(14);
  __syncthreads();
  uint32_t best;
  {
    const int rr = lane & 15;
    const float r = ((sm.rp[rr][0] + sm.rp[rr][1]) + (sm.rp[rr][2] + sm.rp[rr][3])) + sm.rp[rr][4];
    const uint32_t bits = __bfloat16_as_ushort(__float2bfloat16_rn(r));
    const uint32_t ord = (bits & 0x8000u) ? (bits ^ 0xFFFFu) : (bits ^ 0x8000u);
    const uint32_t key = (ord << 16) | 0x8000u | (uint32_t)(2047 - (cta * 16 + rr));
    best = __reduce_max_sync(0xffffffffu, key);
  }
  if (wid >= 8) asm volatile("st.relaxed.gpu.global.u32 [%0], %1;" ::"l"(&g_keys[tid - 256][cta]), "r"(best) : "memory");
  STAMP(15);
  const int brow = (2047 - (int)(best & 0x7FFu)) - cta * 16;
  if (wid < 10 && row == brow) {
#pragma unroll
    for (int k = 0; k < 4; k++)
      st_pub4(&g_cand[cta][0][4 * (4 * gqi + k) + tq], enc4(make_uint4(hnreg[4 * k], hnreg[4 * k + 1], hnreg[4 * k + 2], hnreg[4 * k + 3])));
#pragma unroll
    for (int k = 0; k < 4; k++)
      st_pub4(&g_cand[cta][1][4 * (4 * gqi + k) + tq], enc4(make_uint4(hreg[4 * k], hreg[4 * k + 1], hreg[4 * k + 2], hreg[4 * k + 3])));
  }
#pragma unroll
  for (int i = 0; i < 16; i++) hreg[i] = b2u(__hadd2_rn(u2b(hreg[i]), u2b(hnreg[i])));
  STAMP(6);
  if (ABL == 2) { if (cta < N1 + N2) mbar_wait(&sm.mbarw); return; }
  if (wid == 11) {
    const uint4* kp = reinterpret_cast<const uint4*>(&g_keys[cta][0]) + lane;
    uint4 v = ld_poll4(kp);
    int it = 0;
    while (!ready4(v) && ++it < SPIN_LIMIT) v = ld_poll4(kp);
    const uint32_t m = max(max(v.x, v.y), max(v.z, v.w));
    const uint32_t wk = __reduce_max_sync(0xffffffffu, m);
    if (lane == 0) sm.win = wk;
  }
  __syncthreads();
  const uint32_t win = sm.win;
  const int wrow = 2047 - (int)(win & 0x7FFu);
  const int wcta = wrow >> 4;
  const bool st_out = wid < 10 && (cta * 16 + row) != wrow;
  uint4* outp = reinterpret_cast<uint4*>(gout + (size_t)(cta * 16 + row) * D_) + 16 * gqi + tq;
  if (cta >= N1 && st_out) {
#pragma unroll
    for (int k = 0; k < 4; k++) outp[4 * k] = make_uint4(hreg[4 * k], hreg[4 * k + 1], hreg[4 * k + 2], hreg[4 * k + 3]);
  }
  if (cta >= N1 || ABL == 1) {
#pragma unroll
    for (int i = 0; i < 4; i++) if (i < 3 || tid < 128) g_y2[cta * 1280 + tid + NTHR * i] = make_uint4(0, 0, 0, 0);
  }
  STAMP(7);
  if (ABL == 1) { if (cta < N1 + N2) mbar_wait(&sm.mbarw); return; }
  if (cta < N1 + N2) mbar_wait(&sm.mbarw);
  float* xs = &sm.z[0][0][0];
  float* part = xs + 2048;
  if (cta < N1) {
    if (tid < 80) {
      const uint4 v = poll4(&g_cand[wcta][0][tid]);
      float4* xp = reinterpret_cast<float4*>(xs + tid * 8);
      xp[0] = make_float4(lo_f(v.x), hi_f(v.x), lo_f(v.y), hi_f(v.y));
      xp[1] = make_float4(lo_f(v.z), hi_f(v.z), lo_f(v.w), hi_f(v.w));
    }
    __syncthreads();
    const int m = wid / 6, hc = (wid % 6) >> 1, rs = (wid & 1) * 32 + lane;
    float a[8];
#pragma unroll
    for (int j = 0; j < 8; j++) a[j] = 0.f;
#pragma unroll
    for (int it = 0; it < 10; it++) {
      const int r = rs + 64 * it;
      const uint4 wv = sm.w[m * 1920 + r * 3 + hc];
      const float x = xs[r];
      a[0] = fmaf(x, lo_f(wv.x), a[0]); a[1] = fmaf(x, hi_f(wv.x), a[1]);
      a[2] = fmaf(x, lo_f(wv.y), a[2]); a[3] = fmaf(x, hi_f(wv.y), a[3]);
      a[4] = fmaf(x, lo_f(wv.z), a[4]); a[5] = fmaf(x, hi_f(wv.z), a[5]);
      a[6] = fmaf(x, lo_f(wv.w), a[6]); a[7] = fmaf(x, hi_f(wv.w), a[7]);
    }
    {
      const bool up = lane & 16;
#pragma unroll
      for (int j = 0; j < 4; j++) {
        const float send = up ? a[j] : a[j + 4], keep = up ? a[j + 4] : a[j];
        a[j] = keep + __shfl_xor_sync(0xffffffffu, send, 16);
      }
      const bool up2 = lane & 8;
#pragma unroll
      for (int j = 0; j < 2; j++) {
        const float send = up2 ? a[j] : a[j + 2], keep = up2 ? a[j + 2] : a[j];
        a[j] = keep + __shfl_xor_sync(0xffffffffu, send, 8);
      }
      const bool up3 = lane & 4;
      const float send = up3 ? a[0] : a[1], keep = up3 ? a[1] : a[0];
      a[0] = keep + __shfl_xor_sync(0xffffffffu, send, 4);
      a[0] += __shfl_xor_sync(0xffffffffu, a[0], 2);
      a[0] += __shfl_xor_sync(0xffffffffu, a[0], 1);
      if ((lane & 3) == 0) part[wid * 8 + (lane >> 2)] = a[0];
    }
    __syncthreads();
    if (wid == 0) {
      uint32_t bits = 0;
      if (lane < 24) {
        const int hc2 = lane >> 3, j = lane & 7;
        const float gt = rbf(part[(2 * hc2) * 8 + j] + part[(2 * hc2 + 1) * 8 + j]);
        const float up = rbf(part[(6 + 2 * hc2) * 8 + j] + part[(6 + 2 * hc2 + 1) * 8 + j]);
        const float sg = rbf(gt / (1.f + __expf(-gt)));
        bits = __bfloat16_as_ushort(__float2bfloat16_rn(sg * up));
      }
      const uint32_t nb = __shfl_down_sync(0xffffffffu, bits, 1);
      const uint32_t pw = bits | (nb << 16);
      const uint32_t w1 = __shfl_down_sync(0xffffffffu, pw, 2), w2 = __shfl_down_sync(0xffffffffu, pw, 4), w3 = __shfl_down_sync(0xffffffffu, pw, 6);
      const uint4 mine = enc4(make_uint4(pw, w1, w2, w3));
#pragma unroll
      for (int i = 0; i < 4; i++) {
        const int t = lane + 32 * i;
        const int cons = t / 3, ck = t - 3 * cons;
        uint4 v;
        v.x = __shfl_sync(0xffffffffu, mine.x, 8 * ck); v.y = __shfl_sync(0xffffffffu, mine.y, 8 * ck);
        v.z = __shfl_sync(0xffffffffu, mine.z, 8 * ck); v.w = __shfl_sync(0xffffffffu, mine.w, 8 * ck);
        if (t < 3 * N2) st_pub4(&g_act[cons][cta * 3 + ck], v);
      }
      __syncwarp();
      bar_arrive(7, 384);
    } else {
      bar_sync(7, 384);
    }
#pragma unroll
    for (int i = 0; i < 4; i++) if (i < 3 || tid < 128) g_y2[cta * 1280 + tid + NTHR * i] = make_uint4(0, 0, 0, 0);
    if (st_out) {
#pragma unroll
      for (int k = 0; k < 4; k++) outp[4 * k] = make_uint4(hreg[4 * k], hreg[4 * k + 1], hreg[4 * k + 2], hreg[4 * k + 3]);
    }
  } else if (cta < N1 + N2 && ABL != 6) {
    const int j2 = cta - N1;
    uint4 rowv = make_uint4(0, 0, 0, 0);
    if (tid < 192) {
      const uint4 v = poll4(&g_act[j2][tid]);
      float4* xp = reinterpret_cast<float4*>(xs + tid * 8);
      xp[0] = make_float4(lo_f(v.x), hi_f(v.x), lo_f(v.y), hi_f(v.y));
      xp[1] = make_float4(lo_f(v.z), hi_f(v.z), lo_f(v.w), hi_f(v.w));
    } else if (tid < 196) {
      const int t = tid - 192;
      rowv = poll4(&g_cand[wcta][t >> 1][j2 * 2 + (t & 1)]);
      reinterpret_cast<uint4*>(part + 256)[t] = rowv;
    }
    __syncthreads();
    const int hc = lane & 1, rs = wid * 16 + (lane >> 1);
    float a[8];
#pragma unroll
    for (int j = 0; j < 8; j++) a[j] = 0.f;
#pragma unroll
    for (int it = 0; it < 8; it++) {
      const int r = rs + 192 * it;
      const uint4 wv = sm.w[r * 2 + hc];
      const float x = xs[r];
      a[0] = fmaf(x, lo_f(wv.x), a[0]); a[1] = fmaf(x, hi_f(wv.x), a[1]);
      a[2] = fmaf(x, lo_f(wv.y), a[2]); a[3] = fmaf(x, hi_f(wv.y), a[3]);
      a[4] = fmaf(x, lo_f(wv.z), a[4]); a[5] = fmaf(x, hi_f(wv.z), a[5]);
      a[6] = fmaf(x, lo_f(wv.w), a[6]); a[7] = fmaf(x, hi_f(wv.w), a[7]);
    }
    {
      const bool up = lane & 16;
#pragma unroll
      for (int j = 0; j < 4; j++) {
        const float send = up ? a[j] : a[j + 4], keep = up ? a[j + 4] : a[j];
        a[j] = keep + __shfl_xor_sync(0xffffffffu, send, 16);
      }
      const bool up2 = lane & 8;
#pragma unroll
      for (int j = 0; j < 2; j++) {
        const float send = up2 ? a[j] : a[j + 2], keep = up2 ? a[j + 2] : a[j];
        a[j] = keep + __shfl_xor_sync(0xffffffffu, send, 8);
      }
      const bool up3 = lane & 4;
      const float send = up3 ? a[0] : a[1], keep = up3 ? a[1] : a[0];
      a[0] = keep + __shfl_xor_sync(0xffffffffu, send, 4);
      a[0] += __shfl_xor_sync(0xffffffffu, a[0], 2);
      if ((lane & 2) == 0) part[wid * 16 + hc * 8 + (lane >> 2)] = a[0];
    }
    __syncthreads();
    if (tid < 16) {
      float y = 0.f;
#pragma unroll
      for (int i = 0; i < 12; i++) y += part[i * 16 + tid];
      const uint32_t ord = win >> 16;
      const uint32_t rb = (ord & 0x8000u) ? (ord ^ 0x8000u) : (ord ^ 0xFFFFu);
      const float r = __uint_as_float(rb << 16);
      const float sg = rbf(1.f / (1.f + __expf(-r)));
      const float yy = rbf(rbf(y) * sg);
      const unsigned short* rv = reinterpret_cast<const unsigned short*>(part + 256);
      const float hn = __uint_as_float((uint32_t)rv[tid] << 16), h = __uint_as_float((uint32_t)rv[16 + tid] << 16);
      gout[(size_t)wrow * D_ + j2 * 16 + tid] = __float2bfloat16_rn(h + rbf(hn + yy));
    }
  }
  STAMP(8);
}

}

typedef CUresult (*EncodeFn)(CUtensorMap*, CUtensorMapDataType, cuuint32_t, void*, const cuuint64_t*, const cuuint64_t*,
                             const cuuint32_t*, const cuuint32_t*, CUtensorMapInterleave, CUtensorMapSwizzle,
                             CUtensorMapL2promotion, CUtensorMapFloatOOBfill);

extern "C" void kernel_launch(void* const* d_in, const int* in_sizes, int n_in, void* d_out, int out_size) {
  (void)in_sizes; (void)n_in; (void)out_size;
  static EncodeFn encode = nullptr;
  static CUtensorMap tmg, tmu, tmd;
  static void* cached[3] = {nullptr, nullptr, nullptr};
  if (!encode) {
    cudaFuncSetAttribute(fused_kernel, cudaFuncAttributeMaxDynamicSharedMemorySize, (int)sizeof(Smem));
    void* fn = nullptr;
    cudaDriverEntryPointQueryResult qr;
    cudaGetDriverEntryPoint("cuTensorMapEncodeTiled", &fn, cudaEnableDefault, &qr);
    encode = (EncodeFn)fn;
  }
  if (cached[0] != d_in[8] || cached[1] != d_in[9] || cached[2] != d_in[10]) {
    const cuuint32_t es[2] = {1, 1};
    {
      const cuuint64_t dims[2] = {F_, D_}, strides[1] = {F_ * 2};
      const cuuint32_t box[2] = {24, 160};
      encode(&tmg, CU_TENSOR_MAP_DATA_TYPE_BFLOAT16, 2, d_in[8], dims, strides, box, es, CU_TENSOR_MAP_INTERLEAVE_NONE,
             CU_TENSOR_MAP_SWIZZLE_NONE, CU_TENSOR_MAP_L2_PROMOTION_NONE, CU_TENSOR_MAP_FLOAT_OOB_FILL_NONE);
      encode(&tmu, CU_TENSOR_MAP_DATA_TYPE_BFLOAT16, 2, d_in[9], dims, strides, box, es, CU_TENSOR_MAP_INTERLEAVE_NONE,
             CU_TENSOR_MAP_SWIZZLE_NONE, CU_TENSOR_MAP_L2_PROMOTION_NONE, CU_TENSOR_MAP_FLOAT_OOB_FILL_NONE);
    }
    {
      const cuuint64_t dims[2] = {D_, F_}, strides[1] = {D_ * 2};
      const cuuint32_t box[2] = {16, 256};
      encode(&tmd, CU_TENSOR_MAP_DATA_TYPE_BFLOAT16, 2, d_in[10], dims, strides, box, es, CU_TENSOR_MAP_INTERLEAVE_NONE,
             CU_TENSOR_MAP_SWIZZLE_NONE, CU_TENSOR_MAP_L2_PROMOTION_NONE, CU_TENSOR_MAP_FLOAT_OOB_FILL_NONE);
    }
    cached[0] = d_in[8]; cached[1] = d_in[9]; cached[2] = d_in[10];
  }
  fused_kernel<<<NCTA, NTHR, sizeof(Smem), cudaStreamPerThread>>>(
      tmg, tmu, tmd, (const bf16*)d_in[0], (const bf16*)d_in[1], (const bf16*)d_in[2], (const bf16*)d_in[3],
      (const bf16*)d_in[4], (const bf16*)d_in[5], (const bf16*)d_in[7], (bf16*)d_out);
}
```

```cpp
#include <cuda_runtime.h>
#include <cuda_bf16.h>
#include <cuda.h>
#include <stdint.h>

namespace {

typedef __nv_bfloat16 bf16;
typedef __nv_bfloat162 bf162;

constexpr int S_ = 2048, D_ = 640, F_ = 1536;
constexpr int NCTA = 128, CPC = 5, NTHR = 384;
constexpr int UPAD = 136, USTR = 2192;
constexpr int TABW = 1040;
constexpr int ZPB = 132;
constexpr int QSTR = 648;
constexpr int N1 = 64;
constexpr int N2 = 40;
constexpr int SPIN_LIMIT = 1 << 19;
#define LN2_EXACT 1
#define ABL 0
#define CTR_NS 0
#define C_DELAY 0
#define TESTV 0
#define TESTC 0
#define POLL_NS 100
#define H_DELAY 0
#define Q_DELAY 4500

struct __align__(128) Smem {
  uint32_t tabA[3][2][TABW];
  uint32_t extra[1024];
  uint32_t tabB[2][2][TABW];
  bf16 u[CPC][USTR];
  float z[2][4][ZPB * 16];
  bf16 q[16][QSTR];
  alignas(128) uint4 w[3840];
  uint4 wr[80];
  float2 st[16][5];
  float2 stq[16][5];
  float rp[16][5];
  unsigned long long mbar;
  unsigned long long mbarw;
  unsigned long long mbarc;
  unsigned long long mbary;
  unsigned long long mbarh;
  uint32_t target;
  uint32_t target2;
  uint32_t target3;
  uint32_t best;
  uint32_t win;
};

__device__ uint4 g_kv[D_ * S_ / 8];
__device__ uint4 g_y2[D_ * S_ / 8];
__device__ uint32_t g_keys[NCTA][NCTA];
__device__ uint4 g_cand[NCTA][2][80];
__device__ uint4 g_act[N2][F_ / 8];
__device__ unsigned int g_ctr;
__device__ unsigned int g_ctr2;
__device__ unsigned int g_ctr3;
#define STAMP(i)
#define CST(c, i)

__device__ __forceinline__ uint32_t smem_u32(const void* p) { return (uint32_t)__cvta_generic_to_shared(p); }
__device__ __forceinline__ void wg_fence() { asm volatile("wgmma.fence.sync.aligned;" ::: "memory"); }
__device__ __forceinline__ void wg_commit() { asm volatile("wgmma.commit_group.sync.aligned;" ::: "memory"); }
template <int N> __device__ __forceinline__ void wg_wait() { asm volatile("wgmma.wait_group.sync.aligned %0;" ::"n"(N) : "memory"); }
__device__ __forceinline__ void bar_sync(int id, int n) { asm volatile("bar.sync %0, %1;" ::"r"(id), "r"(n) : "memory"); }
__device__ __forceinline__ void bar_arrive(int id, int n) { asm volatile("bar.arrive %0, %1;" ::"r"(id), "r"(n) : "memory"); }
__device__ __forceinline__ bf162 u2b(uint32_t u) { return *reinterpret_cast<bf162*>(&u); }
__device__ __forceinline__ uint32_t b2u(bf162 b) { return *reinterpret_cast<uint32_t*>(&b); }
__device__ __forceinline__ float lo_f(uint32_t u) { return __uint_as_float(u << 16); }
__device__ __forceinline__ float hi_f(uint32_t u) { return __uint_as_float(u & 0xFFFF0000u); }
__device__ __forceinline__ float rbf(float x) { return __bfloat162float(__float2bfloat16_rn(x)); }
__device__ __forceinline__ uint32_t pack2(float a, float b) { return b2u(__floats2bfloat162_rn(a, b)); }
__device__ __forceinline__ uint32_t enc(uint32_t w) { return max(~w, 1u); }
__device__ __forceinline__ uint4 enc4(uint4 v) { return make_uint4(enc(v.x), enc(v.y), enc(v.z), enc(v.w)); }
__device__ __forceinline__ uint4 ld_poll4(const uint4* p) {
  uint4 v;
  asm volatile("ld.relaxed.gpu.global.v4.u32 {%0,%1,%2,%3}, [%4];" : "=r"(v.x), "=r"(v.y), "=r"(v.z), "=r"(v.w) : "l"(p) : "memory");
  return v;
}
__device__ __forceinline__ bool ready4(uint4 v) { return v.x != 0u && v.y != 0u && v.z != 0u && v.w != 0u; }
__device__ __forceinline__ uint4 poll4(const uint4* p) {
  uint4 v = ld_poll4(p);
  int it = 0;
  while (!ready4(v) && ++it < SPIN_LIMIT) v = ld_poll4(p);
  return make_uint4(~v.x, ~v.y, ~v.z, ~v.w);
}
__device__ __forceinline__ void st_pub4(uint4* p, uint4 v) {
  asm volatile("st.relaxed.gpu.global.v4.u32 [%0], {%1,%2,%3,%4};" ::"l"(p), "r"(v.x), "r"(v.y), "r"(v.z), "r"(v.w) : "memory");
}
__device__ __forceinline__ void st_pub2(uint2* p, uint32_t a, uint32_t b) {
  asm volatile("st.relaxed.gpu.global.v2.u32 [%0], {%1,%2};" ::"l"(p), "r"(a), "r"(b) : "memory");
}
__device__ __forceinline__ void mma_bf16(float (&c)[4], uint32_t a0, uint32_t a2, uint32_t b0, uint32_t b1) {
  asm volatile("mma.sync.aligned.m16n8k16.row.col.f32.bf16.bf16.f32 {%0,%1,%2,%3}, {%4,%5,%6,%5}, {%7,%8}, {%0,%1,%2,%3};"
               : "+f"(c[0]), "+f"(c[1]), "+f"(c[2]), "+f"(c[3]) : "r"(a0), "r"(0u), "r"(a2), "r"(b0), "r"(b1));
}
__device__ __forceinline__ void mbar_wait(const unsigned long long* bar) {
  const uint32_t mb = smem_u32(bar);
  uint32_t ok = 0;
  int it = 0;
  while (!ok && ++it < SPIN_LIMIT)
    asm volatile("{ .reg .pred p; mbarrier.try_wait.parity.shared.b64 p, [%1], 0; selp.u32 %0, 1, 0, p; }" : "=r"(ok) : "r"(mb) : "memory");
}
__device__ __forceinline__ void bulk_g2s(void* dst, const void* src, uint32_t bytes, const unsigned long long* bar) {
  asm volatile("cp.async.bulk.shared::cluster.global.mbarrier::complete_tx::bytes [%0], [%1], %2, [%3];" ::"r"(smem_u32(dst)),
               "l"(src), "r"(bytes), "r"(smem_u32(bar)) : "memory");
}
__device__ __forceinline__ void mbar_expect(const unsigned long long* bar, uint32_t bytes) {
  asm volatile("mbarrier.arrive.expect_tx.shared.b64 _, [%0], %1;" ::"r"(smem_u32(bar)), "r"(bytes) : "memory");
}
__device__ __forceinline__ void mma_bf16x(float (&c)[4], uint32_t a0, uint32_t a1, uint32_t a2, uint32_t a3, uint32_t b0, uint32_t b1) {
  asm volatile("mma.sync.aligned.m16n8k16.row.col.f32.bf16.bf16.f32 {%0,%1,%2,%3}, {%4,%5,%6,%7}, {%8,%9}, {%0,%1,%2,%3};"
               : "+f"(c[0]), "+f"(c[1]), "+f"(c[2]), "+f"(c[3]) : "r"(a0), "r"(a1), "r"(a2), "r"(a3), "r"(b0), "r"(b1));
}
__device__ __forceinline__ float fdivr(float a, float d, float r) {
  float q = a * r;
  float e = fmaf(-q, d, a);
  return fmaf(e, r, q);
}

template <bool FIRST> __device__ __forceinline__ void wgmma32(float (&d)[16], const uint32_t* a, uint64_t desc) {
  if (FIRST) {
    asm volatile("wgmma.mma_async.sync.aligned.m64n32k16.f32.bf16.bf16 {%0,%1,%2,%3,%4,%5,%6,%7,%8,%9,%10,%11,%12,%13,%14,%15}, {%16,%17,%18,%19}, %20, 0, 1, 1, 0;"
                 : "+f"(d[0]), "+f"(d[1]), "+f"(d[2]), "+f"(d[3]), "+f"(d[4]), "+f"(d[5]), "+f"(d[6]), "+f"(d[7]),
                   "+f"(d[8]), "+f"(d[9]), "+f"(d[10]), "+f"(d[11]), "+f"(d[12]), "+f"(d[13]), "+f"(d[14]), "+f"(d[15])
                 : "r"(a[0]), "r"(a[1]), "r"(a[2]), "r"(a[3]), "l"(desc));
  } else {
    asm volatile("wgmma.mma_async.sync.aligned.m64n32k16.f32.bf16.bf16 {%0,%1,%2,%3,%4,%5,%6,%7,%8,%9,%10,%11,%12,%13,%14,%15}, {%16,%17,%18,%19}, %20, 1, 1, 1, 0;"
                 : "+f"(d[0]), "+f"(d[1]), "+f"(d[2]), "+f"(d[3]), "+f"(d[4]), "+f"(d[5]), "+f"(d[6]), "+f"(d[7]),
                   "+f"(d[8]), "+f"(d[9]), "+f"(d[10]), "+f"(d[11]), "+f"(d[12]), "+f"(d[13]), "+f"(d[14]), "+f"(d[15])
                 : "r"(a[0]), "r"(a[1]), "r"(a[2]), "r"(a[3]), "l"(desc));
  }
}

template <int G> __device__ __forceinline__ void load_a(uint32_t (&a)[8], const uint32_t* tp) {
#pragma unroll
  for (int q = 0; q < 2; q++) {
    const int e = 2 * G + q;
    a[4 * q + 0] = tp[-64 * e];
    a[4 * q + 1] = tp[-64 * e - 32];
    a[4 * q + 2] = tp[-64 * e + 4];
    a[4 * q + 3] = tp[-64 * e - 28];
  }
}
__device__ __forceinline__ void load_a_all(uint32_t (&a)[8][8], const uint32_t* tp) {
  load_a<0>(a[0], tp); load_a<1>(a[1], tp); load_a<2>(a[2], tp); load_a<3>(a[3], tp);
  load_a<4>(a[4], tp); load_a<5>(a[5], tp); load_a<6>(a[6], tp); load_a<7>(a[7], tp);
}
template <int G> __device__ __forceinline__ void issue_g(float (&acc)[8][16], uint32_t (&a)[8], uint64_t desc0) {
  wg_fence();
#pragma unroll
  for (int q = 0; q < 2; q++) {
#pragma unroll
    for (int b = G; b < 8; b++) {
      const int delta = 2 * b - (2 * G + q);
      if (G == 0 && q == 0) wgmma32<true>(acc[b], &a[4 * q], desc0 + (uint64_t)(int64_t)(16 * delta));
      else wgmma32<false>(acc[b], &a[4 * q], desc0 + (uint64_t)(int64_t)(16 * delta));
    }
  }
  wg_commit();
}
template <int B> __device__ __forceinline__ void fence_blk(float (&acc)[8][16]) {
#pragma unroll
  for (int i = 0; i < 16; i++) asm volatile("" : "+f"(acc[B][i])::"memory");
}
__device__ __forceinline__ void fence_a(uint32_t (&a)[8]) {
#pragma unroll
  for (int i = 0; i < 8; i++) asm volatile("" : "+r"(a[i])::"memory");
}
template <int B> __device__ __forceinline__ void sts_blk(float (&acc)[8][16], float* zw, int off_even, int off_odd) {
#pragma unroll
  for (int jj = 0; jj < 4; jj++) {
    const int j = 4 * B + jj;
    float p0 = acc[B][4 * jj + 0], p1 = acc[B][4 * jj + 1];
    if (jj > 0) { p0 += acc[B][4 * (jj - 1) + 2]; p1 += acc[B][4 * (jj - 1) + 3]; }
    else if (B > 0) { p0 += acc[B > 0 ? B - 1 : 0][14]; p1 += acc[B > 0 ? B - 1 : 0][15]; }
    zw[64 * j + off_even] = p0;
    zw[64 * j + off_odd] = p1;
  }
}
__device__ __forceinline__ int tab_off(int c) { return c == 4 ? 0 : (c + 1) * 2 * TABW + (c >= 2 ? 1024 : 0); }
__device__ __forceinline__ int tile_perm(int ch) { return ch ^ (((ch >> 3) & 3) << 1); }

__device__ __forceinline__ void wait_ctr(const unsigned int* ctr, uint32_t target) {
  uint32_t v;
  int it = 0;
  do {
    asm volatile("ld.acquire.gpu.global.u32 %0, [%1];" : "=r"(v) : "l"(ctr) : "memory");
  } while ((int)(v - target) < 0 && ++it < SPIN_LIMIT);
}

__device__ __forceinline__ float2 row_part_stats(const uint32_t (&x)[16]) {
  float cs[4][4];
#pragma unroll
  for (int k = 0; k < 4; k++) {
    cs[k][0] = cs[k][1] = cs[k][2] = cs[k][3] = 0.f;
    mma_bf16x(cs[k], x[4 * k + 0], x[4 * k + 2], x[4 * k + 1], x[4 * k + 3], 0x3F803F80u, 0x3F803F80u);
  }
  const float mean = (((cs[0][0] + cs[0][2]) + (cs[1][0] + cs[1][2])) + ((cs[2][0] + cs[2][2]) + (cs[3][0] + cs[3][2]))) * (1.f / 128.f);
  float m2a = 0.f, m2b = 0.f, m2c = 0.f, m2d = 0.f;
#pragma unroll
  for (int i = 0; i < 16; i += 2) {
    const float a = lo_f(x[i]) - mean, b = hi_f(x[i]) - mean, c = lo_f(x[i + 1]) - mean, d = hi_f(x[i + 1]) - mean;
    m2a = fmaf(a, a, m2a); m2b = fmaf(b, b, m2b); m2c = fmaf(c, c, m2c); m2d = fmaf(d, d, m2d);
  }
  float m2 = (m2a + m2b) + (m2c + m2d);
  m2 += __shfl_xor_sync(0xffffffffu, m2, 1);
  m2 += __shfl_xor_sync(0xffffffffu, m2, 2);
  return make_float2(mean, m2);
}
__device__ __forceinline__ void row_normalize(const float2* st, const uint32_t (&x)[16], uint32_t (&y)[16]) {
  float mean = 0.f, m2 = 0.f;
  float2 p[5];
#pragma unroll
  for (int i = 0; i < 5; i++) { p[i] = st[i]; mean += p[i].x; }
  mean *= 0.2f;
#pragma unroll
  for (int i = 0; i < 5; i++) { const float dl = p[i].x - mean; m2 += p[i].y + 128.f * dl * dl; }
  const float hd = rbf(sqrtf(rbf(rbf(m2 * (1.f / D_)) + 1e-5f)));
  const float hr = 1.f / hd;
  const bf162 hm2 = __float2bfloat162_rn(mean);
#pragma unroll
  for (int i = 0; i < 16; i++) {
    const uint32_t d = b2u(__hsub2_rn(u2b(x[i]), hm2));
    y[i] = pack2(fdivr(lo_f(d), hd, hr), fdivr(hi_f(d), hd, hr));
  }
}

__device__ __forceinline__ void gather_kv(Smem& sm, int c0, int tid) {
  mbar_wait(&sm.mbarc);
  uint4 v[4];
  uint4* src = g_kv + c0 * 256 + tid;
#pragma unroll
  for (int i = 0; i < 4; i++) if (i < 3 || tid >= 256) v[i] = ld_poll4(src + NTHR * i - (i == 3 ? 256 : 0));
#pragma unroll
  for (int i = 0; i < 4; i++) {
    if (i < 3 || tid >= 256) {
      const int t = tid + NTHR * i - (i == 3 ? 256 : 0);
      int it = 0;
      while (!ready4(v[i]) && ++it < SPIN_LIMIT) { __nanosleep(POLL_NS); v[i] = ld_poll4(g_kv + c0 * 256 + t); }
      *reinterpret_cast<uint4*>(&sm.u[t >> 8][UPAD + (t & 255) * 8]) = make_uint4(~v[i].x, ~v[i].y, ~v[i].z, ~v[i].w);
    }
  }
  asm volatile("fence.proxy.async.shared::cta;" ::: "memory");
  __syncthreads();
}

__global__ void __launch_bounds__(NTHR, 1)
fused_kernel(const __grid_constant__ CUtensorMap tmg, const __grid_constant__ CUtensorMap tmu,
             const __grid_constant__ CUtensorMap tmd, const bf16* __restrict__ gq, const bf16* __restrict__ gk, const bf16* __restrict__ gv,
             const bf16* __restrict__ gsk, const bf16* __restrict__ gh, const bf16* __restrict__ gD,
             const bf16* __restrict__ gwr, bf16* __restrict__ gout) {
  extern __shared__ __align__(128) unsigned char smraw[];
  Smem& sm = *reinterpret_cast<Smem*>(smraw);
  const int tid = threadIdx.x;
  const int cta = blockIdx.x;
  const int c0 = cta * CPC;
  const int lane = tid & 31;
  const int wid = tid >> 5;
  STAMP(0);
  const long long tstart = clock64();

  {
    uint4* hs = reinterpret_cast<uint4*>(&sm.z[0][0][0]);
    const int oc = tid >> 2;
    const int r0 = cta * 16 + (tid & 3) * 4;
    uint4 kk[7], vv[4], sk[4];
    if (tid < 320) {
      const uint4* kp = reinterpret_cast<const uint4*>(gk) + (size_t)r0 * 80 + oc;
      const uint4* vp = reinterpret_cast<const uint4*>(gv) + (size_t)r0 * 80 + oc;
#pragma unroll
      for (int i = 0; i < 7; i++) kk[i] = (i >= 3 || r0 > 0) ? __ldg(kp + (i - 3) * 80) : make_uint4(0, 0, 0, 0);
#pragma unroll
      for (int i = 0; i < 4; i++) vv[i] = __ldg(vp + i * 80);
#pragma unroll
      for (int i = 0; i < 4; i++) sk[i] = __ldg(reinterpret_cast<const uint4*>(gsk) + oc * 4 + i);
    } else if (tid == 320) {
      asm volatile("mbarrier.init.shared.b64 [%0], 1;" ::"r"(smem_u32(&sm.mbarh)) : "memory");
      asm volatile("mbarrier.init.shared.b64 [%0], 1;" ::"r"(smem_u32(&sm.mbar)) : "memory");
      asm volatile("mbarrier.init.shared.b64 [%0], 1;" ::"r"(smem_u32(&sm.mbarw)) : "memory");
      asm volatile("mbarrier.init.shared.b64 [%0], 1;" ::"r"(smem_u32(&sm.mbarc)) : "memory");
      asm volatile("mbarrier.init.shared.b64 [%0], 1;" ::"r"(smem_u32(&sm.mbary)) : "memory");
      asm volatile("fence.proxy.async.shared::cta;" ::: "memory");
    } else if (tid == 352) {
      uint32_t v2, v3;
      asm volatile("ld.relaxed.gpu.global.u32 %0, [%1];" : "=r"(v2) : "l"(&g_ctr2) : "memory");
      asm volatile("ld.relaxed.gpu.global.u32 %0, [%1];" : "=r"(v3) : "l"(&g_ctr3) : "memory");
      sm.target2 = (v2 / NCTA + 1u) * NCTA;
      sm.target3 = (v3 / NCTA + 1u) * NCTA;
    }
    if (tid < 320) bar_sync(6, 384); else { bar_arrive(6, 384); bar_sync(5, 64); }
    STAMP(9);
    if (tid < 320) {
      uint32_t o[4][4];
#pragma unroll
      for (int p = 0; p < 4; p++) {
        const bf162 w0 = u2b(__byte_perm(sk[p].x, sk[p].z, 0x5410)), w1 = u2b(__byte_perm(sk[p].x, sk[p].z, 0x7632));
        const bf162 w2 = u2b(__byte_perm(sk[p].y, sk[p].w, 0x5410)), w3 = u2b(__byte_perm(sk[p].y, sk[p].w, 0x7632));
        uint32_t kv[4];
#pragma unroll
        for (int i = 0; i < 4; i++) {
          const uint32_t k0 = p == 0 ? kk[i].x : p == 1 ? kk[i].y : p == 2 ? kk[i].z : kk[i].w;
          const uint32_t k1 = p == 0 ? kk[i + 1].x : p == 1 ? kk[i + 1].y : p == 2 ? kk[i + 1].z : kk[i + 1].w;
          const uint32_t k2 = p == 0 ? kk[i + 2].x : p == 1 ? kk[i + 2].y : p == 2 ? kk[i + 2].z : kk[i + 2].w;
          const uint32_t k3 = p == 0 ? kk[i + 3].x : p == 1 ? kk[i + 3].y : p == 2 ? kk[i + 3].z : kk[i + 3].w;
          const uint32_t vx = p == 0 ? vv[i].x : p == 1 ? vv[i].y : p == 2 ? vv[i].z : vv[i].w;
          bf162 a = __hmul2_rn(u2b(k0), w3);
          a = __hadd2_rn(a, __hmul2_rn(u2b(k1), w2));
          a = __hadd2_rn(a, __hmul2_rn(u2b(k2), w1));
          a = __hadd2_rn(a, __hmul2_rn(u2b(k3), w0));
          kv[i] = b2u(__hmul2_rn(a, u2b(vx)));
        }
        o[p][0] = enc(__byte_perm(kv[0], kv[1], 0x5410)); o[p][1] = enc(__byte_perm(kv[2], kv[3], 0x5410));
        o[p][2] = enc(__byte_perm(kv[0], kv[1], 0x7632)); o[p][3] = enc(__byte_perm(kv[2], kv[3], 0x7632));
      }
      uint2* dst = reinterpret_cast<uint2*>(g_kv) + (size_t)(oc * 8) * 512 + (r0 >> 2);
#pragma unroll
      for (int p = 0; p < 4; p++) {
        st_pub2(dst + (2 * p) * 512, o[p][0], o[p][1]);
        st_pub2(dst + (2 * p + 1) * 512, o[p][2], o[p][3]);
      }
      STAMP(10);
      if (wid == 0) bar_sync(4, 320); else bar_arrive(4, 320);
      if (tid == 0) {
        asm volatile("red.relaxed.gpu.global.add.u32 [%0], 1;" ::"l"(&g_ctr2) : "memory");
      }
      __syncwarp();
    } else {
      const int t0 = tid - 320;
      const uint4 zz = make_uint4(0, 0, 0, 0);
      if (tid == 320) {
        while (clock64() - tstart < H_DELAY) {}
        mbar_expect(&sm.mbarh, CPC * S_ * 2);
        bulk_g2s(hs, gh + (size_t)c0 * S_, CPC * S_ * 2, &sm.mbarh);
      }
      __syncwarp();
      for (int t = t0; t < CPC * 17; t += 64) *reinterpret_cast<uint4*>(&sm.u[t / 17][(t % 17) * 8]) = zz;
      if (t0 < 40) *reinterpret_cast<uint4*>(&sm.tabA[0][0][0] + tab_off(t0 >> 3) + ((t0 >> 2) & 1) * TABW + 1024 + 4 * (t0 & 3)) = zz;
      while (clock64() - tstart < C_DELAY) {}
      (&g_cand[cta][0][0])[t0] = zz;
      (&g_cand[cta][0][0])[64 + t0] = zz;
      if (t0 < 32) (&g_cand[cta][0][0])[128 + t0] = zz;
      else reinterpret_cast<uint4*>(&g_keys[cta][0])[t0 - 32] = zz;
      if (cta >= N1 && cta < N1 + N2) {
#pragma unroll
        for (int i = 0; i < 3; i++) g_act[cta - N1][t0 + 64 * i] = zz;
      }
      bar_sync(5, 64);
      if (tid == 352) {
        __threadfence();
        const unsigned old = atomicAdd(&g_ctr, 1u);
        sm.target = (old / NCTA + 1u) * NCTA;
      }
      __syncwarp();
    }
    mbar_wait(&sm.mbarh);
#pragma unroll
    for (int i = 0; i < 4; i++) {
      const int t = (NTHR - 1 - tid) + NTHR * i;
      if (t < CPC * 256) {
        uint32_t* tb = &sm.tabA[0][0][0] + tab_off(t >> 8) + (255 - (t & 255)) * 4;
        const uint4 h = hs[t];
        const uint32_t hp = (t & 255) ? reinterpret_cast<const uint32_t*>(hs)[4 * t - 1] : 0u;
        uint4 r1, rr;
        r1.x = __byte_perm(h.w, 0, 0x1032); r1.y = __byte_perm(h.z, 0, 0x1032);
        r1.z = __byte_perm(h.y, 0, 0x1032); r1.w = __byte_perm(h.x, 0, 0x1032);
        rr.x = __byte_perm(h.w, h.z, 0x7610); rr.y = __byte_perm(h.z, h.y, 0x7610);
        rr.z = __byte_perm(h.y, h.x, 0x7610); rr.w = __byte_perm(h.x, hp, 0x7610);
        *reinterpret_cast<uint4*>(tb) = rr;
        *reinterpret_cast<uint4*>(tb + TABW) = r1;
      }
    }
    STAMP(12);
  }
  __syncthreads();

  const int wg = __shfl_sync(0xffffffffu, tid >> 7, 0);
  const int wtid = tid & 127;
  uint4* tile = reinterpret_cast<uint4*>(&sm.tabB[0][0][0]);
  if (wg < 2) {
    asm volatile("setmaxnreg.inc.sync.aligned.u32 224;");
    const int w = (tid >> 5) & 3, g = lane >> 2, tq = lane & 3;
    float* zw = sm.z[wg][w];
    const int sw = 3 * (((tq + w) >> 1) & 1);
    const int off_even = 16 * (tq + w) + 4 * ((0 + (g >> 2)) ^ sw) + (g & 3);
    const int off_odd = 16 * (tq + w) + 4 * ((2 + (g >> 2)) ^ sw) + (g & 3);
    uint32_t a[8][8];
    const uint32_t* tp0 = &sm.tabA[0][g & 1][1019 - 8 * w - (g >> 1) + tq];
    load_a_all(a, tp0 + tab_off(wg));
    float acc[8][16];
#pragma unroll
    for (int b = 0; b < 8; b++)
#pragma unroll
      for (int i = 0; i < 16; i++) acc[b][i] = 0.f;
    gather_kv(sm, c0, tid);
    STAMP(1);
#pragma unroll 1
    for (int c = wg; c < CPC; c += 2) {
      const uint64_t desc = (uint64_t)((smem_u32(&sm.u[c][UPAD - 8]) & 0x3FFFF) >> 4) | ((uint64_t)1 << 16) | ((uint64_t)8 << 32);
      CST(c, 0);
      if (c > 0) bar_sync(1 + wg, 256);
      issue_g<0>(acc, a[0], desc);
      CST(c, 1);
      issue_g<1>(acc, a[1], desc);
      issue_g<2>(acc, a[2], desc);
      issue_g<3>(acc, a[3], desc);
      issue_g<4>(acc, a[4], desc);
      issue_g<5>(acc, a[5], desc);
      if (c + 1 < CPC) bar_arrive(1 + (wg ^ 1), 256);
      issue_g<6>(acc, a[6], desc);
      issue_g<7>(acc, a[7], desc);
      CST(c, 2);
      if (c >= 2) bar_sync(5 + wg, 256);
      wg_wait<4>();
      fence_blk<0>(acc); fence_blk<1>(acc); fence_blk<2>(acc); fence_blk<3>(acc);
      sts_blk<0>(acc, zw, off_even, off_odd);
      sts_blk<1>(acc, zw, off_even, off_odd);
      sts_blk<2>(acc, zw, off_even, off_odd);
      sts_blk<3>(acc, zw, off_even, off_odd);
      bar_arrive(9 + wg, 256);
      CST(c, 3);
      wg_wait<0>();
      fence_blk<4>(acc); fence_blk<5>(acc); fence_blk<6>(acc); fence_blk<7>(acc);
#pragma unroll
      for (int i = 0; i < 8; i++) fence_a(a[i]);
      sts_blk<4>(acc, zw, off_even, off_odd);
      sts_blk<5>(acc, zw, off_even, off_odd);
      sts_blk<6>(acc, zw, off_even, off_odd);
      sts_blk<7>(acc, zw, off_even, off_odd);
      bar_arrive(3 + wg, 256);
      CST(c, 4);
      if (c + 2 < CPC) load_a_all(a, tp0 + tab_off(c + 2));
    }
    STAMP(2 + wg);
    asm volatile("setmaxnreg.dec.sync.aligned.u32 168;");
  } else {
    asm volatile("setmaxnreg.dec.sync.aligned.u32 56;");
    if (((wtid & 15) >> 2) < ((wtid >> 4) & 3))
      *reinterpret_cast<uint4*>(&sm.z[wtid >> 6][(wtid >> 4) & 3][(wtid & 15) * 4]) = make_uint4(0, 0, 0, 0);
    if (wtid == 64) {
      const unsigned target = sm.target2;
      uint32_t v;
      int it = 0;
      do {
        asm volatile("ld.relaxed.gpu.global.u32 %0, [%1];" : "=r"(v) : "l"(&g_ctr2) : "memory");
      } while ((int)(v - target) < 0 && ++it < SPIN_LIMIT);
      asm volatile("mbarrier.arrive.shared.b64 _, [%0];" ::"r"(smem_u32(&sm.mbarc)) : "memory");
    }
    __syncwarp();
    gather_kv(sm, c0, tid);
#pragma unroll
    for (int i = 0; i < 10; i++) g_kv[c0 * 256 + wtid + 128 * i] = make_uint4(0, 0, 0, 0);
    if (wtid == 96) wait_ctr(&g_ctr, sm.target);
    __syncwarp();
    if (wtid == 32) {
      const uint32_t mw = smem_u32(&sm.mbarw);
      mbar_expect(&sm.mbar, 17 * D_ * 2);
#pragma unroll 1
      for (int r = 0; r < 16; r++) bulk_g2s(&sm.q[r][0], gq + (size_t)(cta * 16 + r) * D_, D_ * 2, &sm.mbar);
      bulk_g2s(&sm.wr[0], gwr, D_ * 2, &sm.mbar);
      if (cta < N1) {
        asm volatile("mbarrier.arrive.expect_tx.shared.b64 _, [%0], %1;" ::"r"(mw), "r"(3840 * 16) : "memory");
#pragma unroll 1
        for (int i = 0; i < 4; i++) {
          asm volatile("cp.async.bulk.tensor.2d.shared::cluster.global.mbarrier::complete_tx::bytes [%0], [%1, {%3, %4}], [%2];" ::"r"(smem_u32(&sm.w[i * 480])),
                       "l"(&tmg), "r"(mw), "r"(cta * 24), "r"(i * 160) : "memory");
          asm volatile("cp.async.bulk.tensor.2d.shared::cluster.global.mbarrier::complete_tx::bytes [%0], [%1, {%3, %4}], [%2];" ::"r"(smem_u32(&sm.w[1920 + i * 480])),
                       "l"(&tmu), "r"(mw), "r"(cta * 24), "r"(i * 160) : "memory");
        }
      } else if (cta < N1 + N2) {
        asm volatile("mbarrier.arrive.expect_tx.shared.b64 _, [%0], %1;" ::"r"(mw), "r"(3072 * 16) : "memory");
#pragma unroll 1
        for (int i = 0; i < 6; i++)
          asm volatile("cp.async.bulk.tensor.2d.shared::cluster.global.mbarrier::complete_tx::bytes [%0], [%1, {%3, %4}], [%2];" ::"r"(smem_u32(&sm.w[i * 512])),
                       "l"(&tmd), "r"(mw), "r"((cta - N1) * 16), "r"(i * 256) : "memory");
      }
    }
    const int rpb = wtid >> 1, re2 = wtid & 1;
    const int rsw = 3 * ((rpb >> 1) & 1);
    const int roff0 = 16 * rpb + 4 * ((2 * re2 + 0) ^ rsw);
    const int roff1 = 16 * rpb + 4 * ((2 * re2 + 1) ^ rsw);
    const uint32_t dvl = reinterpret_cast<const unsigned short*>(gD)[c0 + (lane < CPC ? lane : 0)];
#pragma unroll 1
    for (int c = 0; c < CPC; c++) {
      const int zg = c & 1;
      const uint32_t dvc = __shfl_sync(0xffffffffu, dvl, c);
      const bf162 d2 = u2b(dvc | (dvc << 16));
      CST(c, 5);
#pragma unroll
      for (int half = 0; half < 2; half++) {
        bar_sync((half ? 3 : 9) + zg, 256);
        const float* zb = sm.z[zg][0] + half * 1024;
        float4 x[4][2];
#pragma unroll
        for (int ww = 0; ww < 4; ww++) {
          x[ww][0] = *reinterpret_cast<const float4*>(zb + ww * ZPB * 16 + roff0);
          x[ww][1] = *reinterpret_cast<const float4*>(zb + ww * ZPB * 16 + roff1);
        }
        const int sidx = half * 1024 + wtid * 8;
        const uint4 kvv = *reinterpret_cast<const uint4*>(&sm.u[c][UPAD + sidx]);
        if (half == 1 && c + 2 < CPC) bar_arrive(5 + zg, 256);
        uint4 o;
        o.x = pack2((x[0][0].x + x[1][0].x) + (x[2][0].x + x[3][0].x), (x[0][0].y + x[1][0].y) + (x[2][0].y + x[3][0].y));
        o.y = pack2((x[0][0].z + x[1][0].z) + (x[2][0].z + x[3][0].z), (x[0][0].w + x[1][0].w) + (x[2][0].w + x[3][0].w));
        o.z = pack2((x[0][1].x + x[1][1].x) + (x[2][1].x + x[3][1].x), (x[0][1].y + x[1][1].y) + (x[2][1].y + x[3][1].y));
        o.w = pack2((x[0][1].z + x[1][1].z) + (x[2][1].z + x[3][1].z), (x[0][1].w + x[1][1].w) + (x[2][1].w + x[3][1].w));
        o.x = b2u(__hadd2_rn(u2b(o.x), __hmul2_rn(u2b(kvv.x), d2)));
        o.y = b2u(__hadd2_rn(u2b(o.y), __hmul2_rn(u2b(kvv.y), d2)));
        o.z = b2u(__hadd2_rn(u2b(o.z), __hmul2_rn(u2b(kvv.z), d2)));
        o.w = b2u(__hadd2_rn(u2b(o.w), __hmul2_rn(u2b(kvv.w), d2)));
        st_pub4(g_y2 + ((64 * half + rpb) * 640 + c0 + c) * 2 + re2, enc4(o));
        CST(c, 6 + half);
      }
    }
    if (wid == 11) bar_sync(8, 128); else bar_arrive(8, 128);
    STAMP(4);
    asm volatile("setmaxnreg.inc.sync.aligned.u32 168;");
  }

  if (tid == 352) {
    asm volatile("red.relaxed.gpu.global.add.u32 [%0], 1;" ::"l"(&g_ctr3) : "memory");
    wait_ctr(&g_ctr3, sm.target3);
    asm volatile("mbarrier.arrive.shared.b64 _, [%0];" ::"r"(smem_u32(&sm.mbary)) : "memory");
  }
  __syncwarp();
  if (ABL == 4) { if (cta < N1 + N2) mbar_wait(&sm.mbarw); mbar_wait(&sm.mbar); return; }
  const int g = lane >> 2, tq = lane & 3;
  const int hh = wid & 1, gqi = wid >> 1;
  const int row = hh * 8 + g;
  uint32_t hreg[16], hnreg[16];
  {
    const uint4* src = g_y2 + cta * 1280 + tid;
    uint4 v[4];
    if (wid < 10) {
      mbar_wait(&sm.mbar);
#pragma unroll
      for (int k = 0; k < 4; k++) {
        const uint4 qv4 = *reinterpret_cast<const uint4*>(&sm.q[row][32 * (4 * gqi + k) + 8 * tq]);
        hreg[4 * k] = qv4.x; hreg[4 * k + 1] = qv4.y; hreg[4 * k + 2] = qv4.z; hreg[4 * k + 3] = qv4.w;
      }
      const float2 ps = row_part_stats(hreg);
      if (tq == 0) sm.stq[row][gqi] = ps;
      bar_sync(7, 320);
      row_normalize(sm.stq[row], hreg, hnreg);
    }
    mbar_wait(&sm.mbary);
#pragma unroll
    for (int i = 0; i < 4; i++) if (i < 3 || tid < 128) v[i] = ld_poll4(src + NTHR * i);
    int it = 0;
    bool all;
    do {
      all = true;
#pragma unroll
      for (int i = 0; i < 4; i++)
        if ((i < 3 || tid < 128) && !ready4(v[i])) { v[i] = ld_poll4(src + NTHR * i); all = false; }
    } while (!all && ++it < SPIN_LIMIT);
#pragma unroll
    for (int i = 0; i < 4; i++) {
      if (i < 3 || tid < 128) {
        const int t = tid + NTHR * i;
        tile[(t & 1) * 640 + tile_perm(t >> 1)] = make_uint4(~v[i].x, ~v[i].y, ~v[i].z, ~v[i].w);
      }
    }
  }
  __syncthreads();
  STAMP(5);
  if (ABL == 3) { if (cta < N1 + N2) mbar_wait(&sm.mbarw); return; }

  if (wid < 10) {
#pragma unroll
    for (int k = 0; k < 4; k++) {
      const int base = 32 * (4 * gqi + k);
      const int lch = base + 8 * ((lane & 7) >> 1) + 2 * (lane >> 3) + (lane & 1);
      uint32_t y[4];
      asm volatile("ldmatrix.sync.aligned.m8n8.x4.trans.shared.b16 {%0,%1,%2,%3}, [%4];"
                   : "=r"(y[0]), "=r"(y[1]), "=r"(y[2]), "=r"(y[3]) : "r"(smem_u32(&tile[hh * 640 + tile_perm(lch)])) : "memory");
#pragma unroll
      for (int i = 0; i < 4; i++)
        hreg[4 * k + i] = b2u(__hadd2_rn(u2b(hreg[4 * k + i]), __hmul2_rn(u2b(hnreg[4 * k + i]), u2b(y[i]))));
    }
    const float2 ps = row_part_stats(hreg);
    if (tq == 0) sm.st[row][gqi] = ps;
    STAMP(13);
    bar_sync(7, 320);
    row_normalize(sm.st[row], hreg, hnreg);
    float cr[4][4];
#pragma unroll
    for (int k = 0; k < 4; k++) {
      cr[k][0] = cr[k][1] = cr[k][2] = cr[k][3] = 0.f;
      const uint4 w4 = sm.wr[4 * (4 * gqi + k) + tq];
      mma_bf16(cr[k], hnreg[4 * k + 0], hnreg[4 * k + 1], w4.x, w4.y);
      mma_bf16(cr[k], hnreg[4 * k + 2], hnreg[4 * k + 3], w4.z, w4.w);
    }
    if (tq == 0) sm.rp[row][gqi] = (cr[0][0] + cr[1][0]) + (cr[2][0] + cr[3][0]);
  }
  STAMP(14);
  __syncthreads();
  uint32_t best;
  {
    const int rr = lane & 15;
    const float r = ((sm.rp[rr][0] + sm.rp[rr][1]) + (sm.rp[rr][2] + sm.rp[rr][3])) + sm.rp[rr][4];
    const uint32_t bits = __bfloat16_as_ushort(__float2bfloat16_rn(r));
    const uint32_t ord = (bits & 0x8000u) ? (bits ^ 0xFFFFu) : (bits ^ 0x8000u);
    const uint32_t key = (ord << 16) | 0x8000u | (uint32_t)(2047 - (cta * 16 + rr));
    best = __reduce_max_sync(0xffffffffu, key);
  }
  if (wid >= 8) asm volatile("st.relaxed.gpu.global.u32 [%0], %1;" ::"l"(&g_keys[tid - 256][cta]), "r"(best) : "memory");
  STAMP(15);
  const int brow = (2047 - (int)(best & 0x7FFu)) - cta * 16;
  if (wid < 10 && row == brow) {
#pragma unroll
    for (int k = 0; k < 4; k++)
      st_pub4(&g_cand[cta][0][4 * (4 * gqi + k) + tq], enc4(make_uint4(hnreg[4 * k], hnreg[4 * k + 1], hnreg[4 * k + 2], hnreg[4 * k + 3])));
#pragma unroll
    for (int k = 0; k < 4; k++)
      st_pub4(&g_cand[cta][1][4 * (4 * gqi + k) + tq], enc4(make_uint4(hreg[4 * k], hreg[4 * k + 1], hreg[4 * k + 2], hreg[4 * k + 3])));
  }
#pragma unroll
  for (int i = 0; i < 16; i++) hreg[i] = b2u(__hadd2_rn(u2b(hreg[i]), u2b(hnreg[i])));
  STAMP(6);
  if (ABL == 2) { if (cta < N1 + N2) mbar_wait(&sm.mbarw); return; }
  if (wid == 11) {
    const uint4* kp = reinterpret_cast<const uint4*>(&g_keys[cta][0]) + lane;
    uint4 v = ld_poll4(kp);
    int it = 0;
    while (!ready4(v) && ++it < SPIN_LIMIT) v = ld_poll4(kp);
    const uint32_t m = max(max(v.x, v.y), max(v.z, v.w));
    const uint32_t wk = __reduce_max_sync(0xffffffffu, m);
    if (lane == 0) sm.win = wk;
  }
  __syncthreads();
  const uint32_t win = sm.win;
  const int wrow = 2047 - (int)(win & 0x7FFu);
  const int wcta = wrow >> 4;
  const bool st_out = wid < 10 && (cta * 16 + row) != wrow;
  uint4* outp = reinterpret_cast<uint4*>(gout + (size_t)(cta * 16 + row) * D_) + 16 * gqi + tq;
  if (cta >= N1 && st_out) {
#pragma unroll
    for (int k = 0; k < 4; k++) outp[4 * k] = make_uint4(hreg[4 * k], hreg[4 * k + 1], hreg[4 * k + 2], hreg[4 * k + 3]);
  }
  if (cta >= N1 || ABL == 1) {
#pragma unroll
    for (int i = 0; i < 4; i++) if (i < 3 || tid < 128) g_y2[cta * 1280 + tid + NTHR * i] = make_uint4(0, 0, 0, 0);
  }
  STAMP(7);
  if (ABL == 1) { if (cta < N1 + N2) mbar_wait(&sm.mbarw); return; }
  if (cta < N1 + N2) mbar_wait(&sm.mbarw);
  float* xs = &sm.z[0][0][0];
  float* part = xs + 2048;
  if (cta < N1) {
    if (tid < 80) {
      const uint4 v = poll4(&g_cand[wcta][0][tid]);
      float4* xp = reinterpret_cast<float4*>(xs + tid * 8);
      xp[0] = make_float4(lo_f(v.x), hi_f(v.x), lo_f(v.y), hi_f(v.y));
      xp[1] = make_float4(lo_f(v.z), hi_f(v.z), lo_f(v.w), hi_f(v.w));
    }
    __syncthreads();
    const int m = wid / 6, hc = (wid % 6) >> 1, rs = (wid & 1) * 32 + lane;
    float a[8];
#pragma unroll
    for (int j = 0; j < 8; j++) a[j] = 0.f;
#pragma unroll
    for (int it = 0; it < 10; it++) {
      const int r = rs + 64 * it;
      const uint4 wv = sm.w[m * 1920 + r * 3 + hc];
      const float x = xs[r];
      a[0] = fmaf(x, lo_f(wv.x), a[0]); a[1] = fmaf(x, hi_f(wv.x), a[1]);
      a[2] = fmaf(x, lo_f(wv.y), a[2]); a[3] = fmaf(x, hi_f(wv.y), a[3]);
      a[4] = fmaf(x, lo_f(wv.z), a[4]); a[5] = fmaf(x, hi_f(wv.z), a[5]);
      a[6] = fmaf(x, lo_f(wv.w), a[6]); a[7] = fmaf(x, hi_f(wv.w), a[7]);
    }
    {
      const bool up = lane & 16;
#pragma unroll
      for (int j = 0; j < 4; j++) {
        const float send = up ? a[j] : a[j + 4], keep = up ? a[j + 4] : a[j];
        a[j] = keep + __shfl_xor_sync(0xffffffffu, send, 16);
      }
      const bool up2 = lane & 8;
#pragma unroll
      for (int j = 0; j < 2; j++) {
        const float send = up2 ? a[j] : a[j + 2], keep = up2 ? a[j + 2] : a[j];
        a[j] = keep + __shfl_xor_sync(0xffffffffu, send, 8);
      }
      const bool up3 = lane & 4;
      const float send = up3 ? a[0] : a[1], keep = up3 ? a[1] : a[0];
      a[0] = keep + __shfl_xor_sync(0xffffffffu, send, 4);
      a[0] += __shfl_xor_sync(0xffffffffu, a[0], 2);
      a[0] += __shfl_xor_sync(0xffffffffu, a[0], 1);
      if ((lane & 3) == 0) part[wid * 8 + (lane >> 2)] = a[0];
    }
    __syncthreads();
    if (wid == 0) {
      uint32_t bits = 0;
      if (lane < 24) {
        const int hc2 = lane >> 3, j = lane & 7;
        const float gt = rbf(part[(2 * hc2) * 8 + j] + part[(2 * hc2 + 1) * 8 + j]);
        const float up = rbf(part[(6 + 2 * hc2) * 8 + j] + part[(6 + 2 * hc2 + 1) * 8 + j]);
        const float sg = rbf(gt / (1.f + __expf(-gt)));
        bits = __bfloat16_as_ushort(__float2bfloat16_rn(sg * up));
      }
      const uint32_t nb = __shfl_down_sync(0xffffffffu, bits, 1);
      const uint32_t pw = bits | (nb << 16);
      const uint32_t w1 = __shfl_down_sync(0xffffffffu, pw, 2), w2 = __shfl_down_sync(0xffffffffu, pw, 4), w3 = __shfl_down_sync(0xffffffffu, pw, 6);
      const uint4 mine = enc4(make_uint4(pw, w1, w2, w3));
#pragma unroll
      for (int i = 0; i < 4; i++) {
        const int t = lane + 32 * i;
        const int cons = t / 3, ck = t - 3 * cons;
        uint4 v;
        v.x = __shfl_sync(0xffffffffu, mine.x, 8 * ck); v.y = __shfl_sync(0xffffffffu, mine.y, 8 * ck);
        v.z = __shfl_sync(0xffffffffu, mine.z, 8 * ck); v.w = __shfl_sync(0xffffffffu, mine.w, 8 * ck);
        if (t < 3 * N2) st_pub4(&g_act[cons][cta * 3 + ck], v);
      }
      __syncwarp();
      bar_arrive(7, 384);
    } else {
      bar_sync(7, 384);
    }
#pragma unroll
    for (int i = 0; i < 4; i++) if (i < 3 || tid < 128) g_y2[cta * 1280 + tid + NTHR * i] = make_uint4(0, 0, 0, 0);
    if (st_out) {
#pragma unroll
      for (int k = 0; k < 4; k++) outp[4 * k] = make_uint4(hreg[4 * k], hreg[4 * k + 1], hreg[4 * k + 2], hreg[4 * k + 3]);
    }
  } else if (cta < N1 + N2 && ABL != 6) {
    const int j2 = cta - N1;
    uint4 rowv = make_uint4(0, 0, 0, 0);
    if (tid < 192) {
      const uint4 v = poll4(&g_act[j2][tid]);
      float4* xp = reinterpret_cast<float4*>(xs + tid * 8);
      xp[0] = make_float4(lo_f(v.x), hi_f(v.x), lo_f(v.y), hi_f(v.y));
      xp[1] = make_float4(lo_f(v.z), hi_f(v.z), lo_f(v.w), hi_f(v.w));
    } else if (tid < 196) {
      const int t = tid - 192;
      rowv = poll4(&g_cand[wcta][t >> 1][j2 * 2 + (t & 1)]);
      reinterpret_cast<uint4*>(part + 256)[t] = rowv;
    }
    __syncthreads();
    const int hc = lane & 1, rs = wid * 16 + (lane >> 1);
    float a[8];
#pragma unroll
    for (int j = 0; j < 8; j++) a[j] = 0.f;
#pragma unroll
    for (int it = 0; it < 8; it++) {
      const int r = rs + 192 * it;
      const uint4 wv = sm.w[r * 2 + hc];
      const float x = xs[r];
      a[0] = fmaf(x, lo_f(wv.x), a[0]); a[1] = fmaf(x, hi_f(wv.x), a[1]);
      a[2] = fmaf(x, lo_f(wv.y), a[2]); a[3] = fmaf(x, hi_f(wv.y), a[3]);
      a[4] = fmaf(x, lo_f(wv.z), a[4]); a[5] = fmaf(x, hi_f(wv.z), a[5]);
      a[6] = fmaf(x, lo_f(wv.w), a[6]); a[7] = fmaf(x, hi_f(wv.w), a[7]);
    }
    {
      const bool up = lane & 16;
#pragma unroll
      for (int j = 0; j < 4; j++) {
        const float send = up ? a[j] : a[j + 4], keep = up ? a[j + 4] : a[j];
        a[j] = keep + __shfl_xor_sync(0xffffffffu, send, 16);
      }
      const bool up2 = lane & 8;
#pragma unroll
      for (int j = 0; j < 2; j++) {
        const float send = up2 ? a[j] : a[j + 2], keep = up2 ? a[j + 2] : a[j];
        a[j] = keep + __shfl_xor_sync(0xffffffffu, send, 8);
      }
      const bool up3 = lane & 4;
      const float send = up3 ? a[0] : a[1], keep = up3 ? a[1] : a[0];
      a[0] = keep + __shfl_xor_sync(0xffffffffu, send, 4);
      a[0] += __shfl_xor_sync(0xffffffffu, a[0], 2);
      if ((lane & 2) == 0) part[wid * 16 + hc * 8 + (lane >> 2)] = a[0];
    }
    __syncthreads();
    if (tid < 16) {
      float y = 0.f;
#pragma unroll
      for (int i = 0; i < 12; i++) y += part[i * 16 + tid];
      const uint32_t ord = win >> 16;
      const uint32_t rb = (ord & 0x8000u) ? (ord ^ 0x8000u) : (ord ^ 0xFFFFu);
      const float r = __uint_as_float(rb << 16);
      const float sg = rbf(1.f / (1.f + __expf(-r)));
      const float yy = rbf(rbf(y) * sg);
      const unsigned short* rv = reinterpret_cast<const unsigned short*>(part + 256);
      const float hn = __uint_as_float((uint32_t)rv[tid] << 16), h = __uint_as_float((uint32_t)rv[16 + tid] << 16);
      gout[(size_t)wrow * D_ + j2 * 16 + tid] = __float2bfloat16_rn(h + rbf(hn + yy));
    }
  }
  STAMP(8);
}

}

typedef CUresult (*EncodeFn)(CUtensorMap*, CUtensorMapDataType, cuuint32_t, void*, const cuuint64_t*, const cuuint64_t*,
                             const cuuint32_t*, const cuuint32_t*, CUtensorMapInterleave, CUtensorMapSwizzle,
                             CUtensorMapL2promotion, CUtensorMapFloatOOBfill);

extern "C" void kernel_launch(void* const* d_in, const int* in_sizes, int n_in, void* d_out, int out_size) {
  (void)in_sizes; (void)n_in; (void)out_size;
  static EncodeFn encode = nullptr;
  static CUtensorMap tmg, tmu, tmd;
  static void* cached[3] = {nullptr, nullptr, nullptr};
  if (!encode) {
    cudaFuncSetAttribute(fused_kernel, cudaFuncAttributeMaxDynamicSharedMemorySize, (int)sizeof(Smem));
    void* fn = nullptr;
    cudaDriverEntryPointQueryResult qr;
    cudaGetDriverEntryPoint("cuTensorMapEncodeTiled", &fn, cudaEnableDefault, &qr);
    encode = (EncodeFn)fn;
  }
  if (cached[0] != d_in[8] || cached[1] != d_in[9] || cached[2] != d_in[10]) {
    const cuuint32_t es[2] = {1, 1};
    {
      const cuuint64_t dims[2] = {F_, D_}, strides[1] = {F_ * 2};
      const cuuint32_t box[2] = {24, 160};
      encode(&tmg, CU_TENSOR_MAP_DATA_TYPE_BFLOAT16, 2, d_in[8], dims, strides, box, es, CU_TENSOR_MAP_INTERLEAVE_NONE,
             CU_TENSOR_MAP_SWIZZLE_NONE, CU_TENSOR_MAP_L2_PROMOTION_NONE, CU_TENSOR_MAP_FLOAT_OOB_FILL_NONE);
      encode(&tmu, CU_TENSOR_MAP_DATA_TYPE_BFLOAT16, 2, d_in[9], dims, strides, box, es, CU_TENSOR_MAP_INTERLEAVE_NONE,
             CU_TENSOR_MAP_SWIZZLE_NONE, CU_TENSOR_MAP_L2_PROMOTION_NONE, CU_TENSOR_MAP_FLOAT_OOB_FILL_NONE);
    }
    {
      const cuuint64_t dims[2] = {D_, F_}, strides[1] = {D_ * 2};
      const cuuint32_t box[2] = {16, 256};
      encode(&tmd, CU_TENSOR_MAP_DATA_TYPE_BFLOAT16, 2, d_in[10], dims, strides, box, es, CU_TENSOR_MAP_INTERLEAVE_NONE,
             CU_TENSOR_MAP_SWIZZLE_NONE, CU_TENSOR_MAP_L2_PROMOTION_NONE, CU_TENSOR_MAP_FLOAT_OOB_FILL_NONE);
    }
    cached[0] = d_in[8]; cached[1] = d_in[9]; cached[2] = d_in[10];
  }
  fused_kernel<<<NCTA, NTHR, sizeof(Smem), cudaStreamPerThread>>>(
      tmg, tmu, tmd, (const bf16*)d_in[0], (const bf16*)d_in[1], (const bf16*)d_in[2], (const bf16*)d_in[3],
      (const bf16*)d_in[4], (const bf16*)d_in[5], (const bf16*)d_in[7], (bf16*)d_out);
}
```

```cpp
#include <cuda_runtime.h>
#include <cuda_bf16.h>
#include <cuda.h>
#include <stdint.h>

namespace {

typedef __nv_bfloat16 bf16;
typedef __nv_bfloat162 bf162;

constexpr int S_ = 2048, D_ = 640, F_ = 1536;
constexpr int NCTA = 128, CPC = 5, NTHR = 384;
constexpr int UPAD = 136, USTR = 2192;
constexpr int TABW = 1040;
constexpr int ZPB = 132;
constexpr int QSTR = 648;
constexpr int N1 = 64;
constexpr int N2 = 40;
constexpr int SPIN_LIMIT = 1 << 19;
#define LN2_EXACT 1
#define ABL 0
#define CTR_NS 0
#define C_DELAY 0
#define TESTV 0
#define TESTC 0
#define POLL_NS 100
#define H_DELAY 0
#define Q_DELAY 4500

struct __align__(128) Smem {
  uint32_t tabA[3][2][TABW];
  uint32_t extra[1024];
  uint32_t tabB[2][2][TABW];
  bf16 u[CPC][USTR];
  float z[2][4][ZPB * 16];
  bf16 q[16][QSTR];
  alignas(128) uint4 w[3840];
  uint4 wr[80];
  alignas(16) float2 st[16][4];
  alignas(16) float2 stq[16][4];
  alignas(16) float rp[16][4];
  unsigned long long mbar;
  unsigned long long mbarw;
  unsigned long long mbarc;
  unsigned long long mbary;
  unsigned long long mbarh;
  uint32_t target;
  uint32_t target2;
  uint32_t target3;
  uint32_t best;
  uint32_t win;
};

__device__ uint4 g_kv[D_ * S_ / 8];
__device__ uint4 g_y2[D_ * S_ / 8];
__device__ uint32_t g_keys[NCTA][NCTA];
__device__ uint4 g_cand[NCTA][2][80];
__device__ uint4 g_act[N2][F_ / 8];
__device__ unsigned int g_ctr;
__device__ unsigned int g_ctr2;
__device__ unsigned int g_ctr3;
#define STAMP(i)
#define RT(i)
#define CST(c, i)

__device__ __forceinline__ uint32_t smem_u32(const void* p) { return (uint32_t)__cvta_generic_to_shared(p); }
__device__ __forceinline__ void wg_fence() { asm volatile("wgmma.fence.sync.aligned;" ::: "memory"); }
__device__ __forceinline__ void wg_commit() { asm volatile("wgmma.commit_group.sync.aligned;" ::: "memory"); }
template <int N> __device__ __forceinline__ void wg_wait() { asm volatile("wgmma.wait_group.sync.aligned %0;" ::"n"(N) : "memory"); }
__device__ __forceinline__ void bar_sync(int id, int n) { asm volatile("bar.sync %0, %1;" ::"r"(id), "r"(n) : "memory"); }
__device__ __forceinline__ void bar_arrive(int id, int n) { asm volatile("bar.arrive %0, %1;" ::"r"(id), "r"(n) : "memory"); }
__device__ __forceinline__ bf162 u2b(uint32_t u) { return *reinterpret_cast<bf162*>(&u); }
__device__ __forceinline__ uint32_t b2u(bf162 b) { return *reinterpret_cast<uint32_t*>(&b); }
__device__ __forceinline__ float lo_f(uint32_t u) { return __uint_as_float(u << 16); }
__device__ __forceinline__ float hi_f(uint32_t u) { return __uint_as_float(u & 0xFFFF0000u); }
__device__ __forceinline__ float rbf(float x) { return __bfloat162float(__float2bfloat16_rn(x)); }
__device__ __forceinline__ uint32_t pack2(float a, float b) { return b2u(__floats2bfloat162_rn(a, b)); }
__device__ __forceinline__ uint32_t enc(uint32_t w) { return max(~w, 1u); }
__device__ __forceinline__ uint4 enc4(uint4 v) { return make_uint4(enc(v.x), enc(v.y), enc(v.z), enc(v.w)); }
__device__ __forceinline__ uint4 ld_poll4(const uint4* p) {
  uint4 v;
  asm volatile("ld.relaxed.gpu.global.v4.u32 {%0,%1,%2,%3}, [%4];" : "=r"(v.x), "=r"(v.y), "=r"(v.z), "=r"(v.w) : "l"(p) : "memory");
  return v;
}
__device__ __forceinline__ bool ready4(uint4 v) { return v.x != 0u && v.y != 0u && v.z != 0u && v.w != 0u; }
__device__ __forceinline__ uint4 poll4(const uint4* p) {
  uint4 v = ld_poll4(p);
  int it = 0;
  while (!ready4(v) && ++it < SPIN_LIMIT) v = ld_poll4(p);
  return make_uint4(~v.x, ~v.y, ~v.z, ~v.w);
}
__device__ __forceinline__ void st_pub4(uint4* p, uint4 v) {
  asm volatile("st.relaxed.gpu.global.v4.u32 [%0], {%1,%2,%3,%4};" ::"l"(p), "r"(v.x), "r"(v.y), "r"(v.z), "r"(v.w) : "memory");
}
__device__ __forceinline__ void st_pub2(uint2* p, uint32_t a, uint32_t b) {
  asm volatile("st.relaxed.gpu.global.v2.u32 [%0], {%1,%2};" ::"l"(p), "r"(a), "r"(b) : "memory");
}
__device__ __forceinline__ void mma_bf16(float (&c)[4], uint32_t a0, uint32_t a2, uint32_t b0, uint32_t b1) {
  asm volatile("mma.sync.aligned.m16n8k16.row.col.f32.bf16.bf16.f32 {%0,%1,%2,%3}, {%4,%5,%6,%5}, {%7,%8}, {%0,%1,%2,%3};"
               : "+f"(c[0]), "+f"(c[1]), "+f"(c[2]), "+f"(c[3]) : "r"(a0), "r"(0u), "r"(a2), "r"(b0), "r"(b1));
}
__device__ __forceinline__ void mbar_wait(const unsigned long long* bar) {
  const uint32_t mb = smem_u32(bar);
  uint32_t ok = 0;
  int it = 0;
  while (!ok && ++it < SPIN_LIMIT)
    asm volatile("{ .reg .pred p; mbarrier.try_wait.parity.shared.b64 p, [%1], 0; selp.u32 %0, 1, 0, p; }" : "=r"(ok) : "r"(mb) : "memory");
}
__device__ __forceinline__ void bulk_g2s(void* dst, const void* src, uint32_t bytes, const unsigned long long* bar) {
  asm volatile("cp.async.bulk.shared::cluster.global.mbarrier::complete_tx::bytes [%0], [%1], %2, [%3];" ::"r"(smem_u32(dst)),
               "l"(src), "r"(bytes), "r"(smem_u32(bar)) : "memory");
}
__device__ __forceinline__ void mbar_expect(const unsigned long long* bar, uint32_t bytes) {
  asm volatile("mbarrier.arrive.expect_tx.shared.b64 _, [%0], %1;" ::"r"(smem_u32(bar)), "r"(bytes) : "memory");
}
__device__ __forceinline__ void mma_bf16x(float (&c)[4], uint32_t a0, uint32_t a1, uint32_t a2, uint32_t a3, uint32_t b0, uint32_t b1) {
  asm volatile("mma.sync.aligned.m16n8k16.row.col.f32.bf16.bf16.f32 {%0,%1,%2,%3}, {%4,%5,%6,%7}, {%8,%9}, {%0,%1,%2,%3};"
               : "+f"(c[0]), "+f"(c[1]), "+f"(c[2]), "+f"(c[3]) : "r"(a0), "r"(a1), "r"(a2), "r"(a3), "r"(b0), "r"(b1));
}
__device__ __forceinline__ float fdivr(float a, float d, float r) {
  float q = a * r;
  float e = fmaf(-q, d, a);
  return fmaf(e, r, q);
}

template <bool FIRST> __device__ __forceinline__ void wgmma32(float (&d)[16], const uint32_t* a, uint64_t desc) {
  if (FIRST) {
    asm volatile("wgmma.mma_async.sync.aligned.m64n32k16.f32.bf16.bf16 {%0,%1,%2,%3,%4,%5,%6,%7,%8,%9,%10,%11,%12,%13,%14,%15}, {%16,%17,%18,%19}, %20, 0, 1, 1, 0;"
                 : "+f"(d[0]), "+f"(d[1]), "+f"(d[2]), "+f"(d[3]), "+f"(d[4]), "+f"(d[5]), "+f"(d[6]), "+f"(d[7]),
                   "+f"(d[8]), "+f"(d[9]), "+f"(d[10]), "+f"(d[11]), "+f"(d[12]), "+f"(d[13]), "+f"(d[14]), "+f"(d[15])
                 : "r"(a[0]), "r"(a[1]), "r"(a[2]), "r"(a[3]), "l"(desc));
  } else {
    asm volatile("wgmma.mma_async.sync.aligned.m64n32k16.f32.bf16.bf16 {%0,%1,%2,%3,%4,%5,%6,%7,%8,%9,%10,%11,%12,%13,%14,%15}, {%16,%17,%18,%19}, %20, 1, 1, 1, 0;"
                 : "+f"(d[0]), "+f"(d[1]), "+f"(d[2]), "+f"(d[3]), "+f"(d[4]), "+f"(d[5]), "+f"(d[6]), "+f"(d[7]),
                   "+f"(d[8]), "+f"(d[9]), "+f"(d[10]), "+f"(d[11]), "+f"(d[12]), "+f"(d[13]), "+f"(d[14]), "+f"(d[15])
                 : "r"(a[0]), "r"(a[1]), "r"(a[2]), "r"(a[3]), "l"(desc));
  }
}

template <int G> __device__ __forceinline__ void load_a(uint32_t (&a)[8], const uint32_t* tp) {
#pragma unroll
  for (int q = 0; q < 2; q++) {
    const int e = 2 * G + q;
    a[4 * q + 0] = tp[-64 * e];
    a[4 * q + 1] = tp[-64 * e - 32];
    a[4 * q + 2] = tp[-64 * e + 4];
    a[4 * q + 3] = tp[-64 * e - 28];
  }
}
__device__ __forceinline__ void load_a_all(uint32_t (&a)[8][8], const uint32_t* tp) {
  load_a<0>(a[0], tp); load_a<1>(a[1], tp); load_a<2>(a[2], tp); load_a<3>(a[3], tp);
  load_a<4>(a[4], tp); load_a<5>(a[5], tp); load_a<6>(a[6], tp); load_a<7>(a[7], tp);
}
template <int G> __device__ __forceinline__ void issue_g(float (&acc)[8][16], uint32_t (&a)[8], uint64_t desc0) {
  wg_fence();
#pragma unroll
  for (int q = 0; q < 2; q++) {
#pragma unroll
    for (int b = G; b < 8; b++) {
      const int delta = 2 * b - (2 * G + q);
      if (G == 0 && q == 0) wgmma32<true>(acc[b], &a[4 * q], desc0 + (uint64_t)(int64_t)(16 * delta));
      else wgmma32<false>(acc[b], &a[4 * q], desc0 + (uint64_t)(int64_t)(16 * delta));
    }
  }
  wg_commit();
}
template <int B> __device__ __forceinline__ void fence_blk(float (&acc)[8][16]) {
#pragma unroll
  for (int i = 0; i < 16; i++) asm volatile("" : "+f"(acc[B][i])::"memory");
}
__device__ __forceinline__ void fence_a(uint32_t (&a)[8]) {
#pragma unroll
  for (int i = 0; i < 8; i++) asm volatile("" : "+r"(a[i])::"memory");
}
template <int B> __device__ __forceinline__ void sts_blk(float (&acc)[8][16], float* zw, int off_even, int off_odd) {
#pragma unroll
  for (int jj = 0; jj < 4; jj++) {
    const int j = 4 * B + jj;
    float p0 = acc[B][4 * jj + 0], p1 = acc[B][4 * jj + 1];
    if (jj > 0) { p0 += acc[B][4 * (jj - 1) + 2]; p1 += acc[B][4 * (jj - 1) + 3]; }
    else if (B > 0) { p0 += acc[B > 0 ? B - 1 : 0][14]; p1 += acc[B > 0 ? B - 1 : 0][15]; }
    zw[64 * j + off_even] = p0;
    zw[64 * j + off_odd] = p1;
  }
}
__device__ __forceinline__ int tab_off(int c) { return c == 4 ? 0 : (c + 1) * 2 * TABW + (c >= 2 ? 1024 : 0); }
__device__ __forceinline__ int tile_perm(int ch) { return ch ^ (((ch >> 3) & 3) << 1); }

__device__ __forceinline__ void wait_ctr(const unsigned int* ctr, uint32_t target) {
  uint32_t v;
  int it = 0;
  do {
    asm volatile("ld.acquire.gpu.global.u32 %0, [%1];" : "=r"(v) : "l"(ctr) : "memory");
  } while ((int)(v - target) < 0 && ++it < SPIN_LIMIT);
}

__device__ __forceinline__ float2 row_part_stats(const uint32_t (&x)[20]) {
  float cs[5][4];
#pragma unroll
  for (int k = 0; k < 5; k++) {
    cs[k][0] = cs[k][1] = cs[k][2] = cs[k][3] = 0.f;
    mma_bf16x(cs[k], x[4 * k + 0], x[4 * k + 2], x[4 * k + 1], x[4 * k + 3], 0x3F803F80u, 0x3F803F80u);
  }
  const float mean = ((((cs[0][0] + cs[0][2]) + (cs[1][0] + cs[1][2])) + ((cs[2][0] + cs[2][2]) + (cs[3][0] + cs[3][2]))) + (cs[4][0] + cs[4][2])) * (1.f / 160.f);
  float m2a = 0.f, m2b = 0.f, m2c = 0.f, m2d = 0.f;
#pragma unroll
  for (int i = 0; i < 20; i += 2) {
    const float a = lo_f(x[i]) - mean, b = hi_f(x[i]) - mean, c = lo_f(x[i + 1]) - mean, d = hi_f(x[i + 1]) - mean;
    m2a = fmaf(a, a, m2a); m2b = fmaf(b, b, m2b); m2c = fmaf(c, c, m2c); m2d = fmaf(d, d, m2d);
  }
  float m2 = (m2a + m2b) + (m2c + m2d);
  m2 += __shfl_xor_sync(0xffffffffu, m2, 1);
  m2 += __shfl_xor_sync(0xffffffffu, m2, 2);
  return make_float2(mean, m2);
}
__device__ __forceinline__ void row_normalize(const float4* st, const uint32_t (&x)[20], uint32_t (&y)[20]) {
  const float4 p = st[0], q = st[1];
  const float mean = ((p.x + p.z) + (q.x + q.z)) * 0.25f;
  const float d0 = p.x - mean, d1 = p.z - mean, d2 = q.x - mean, d3 = q.z - mean;
  const float m2 = ((p.y + p.w) + (q.y + q.w)) + 160.f * ((d0 * d0 + d1 * d1) + (d2 * d2 + d3 * d3));
  const float hd = rbf(sqrtf(rbf(rbf(m2 * (1.f / D_)) + 1e-5f)));
  const float hr = __frcp_rn(hd);
  const bf162 hm2 = __float2bfloat162_rn(mean);
#pragma unroll
  for (int i = 0; i < 20; i++) {
    const uint32_t d = b2u(__hsub2_rn(u2b(x[i]), hm2));
    y[i] = LN2_EXACT ? pack2(fdivr(lo_f(d), hd, hr), fdivr(hi_f(d), hd, hr)) : pack2(lo_f(d) * hr, hi_f(d) * hr);
  }
}

__device__ __forceinline__ void gather_kv(Smem& sm, int c0, int tid) {
  mbar_wait(&sm.mbarc);
  uint4 v[4];
  uint4* src = g_kv + c0 * 256 + tid;
#pragma unroll
  for (int i = 0; i < 4; i++) if (i < 3 || tid >= 256) v[i] = ld_poll4(src + NTHR * i - (i == 3 ? 256 : 0));
#pragma unroll
  for (int i = 0; i < 4; i++) {
    if (i < 3 || tid >= 256) {
      const int t = tid + NTHR * i - (i == 3 ? 256 : 0);
      int it = 0;
      while (!ready4(v[i]) && ++it < SPIN_LIMIT) { __nanosleep(POLL_NS); v[i] = ld_poll4(g_kv + c0 * 256 + t); }
      *reinterpret_cast<uint4*>(&sm.u[t >> 8][UPAD + (t & 255) * 8]) = make_uint4(~v[i].x, ~v[i].y, ~v[i].z, ~v[i].w);
    }
  }
  asm volatile("fence.proxy.async.shared::cta;" ::: "memory");
  __syncthreads();
}

__global__ void __launch_bounds__(NTHR, 1)
fused_kernel(const __grid_constant__ CUtensorMap tmg, const __grid_constant__ CUtensorMap tmu,
             const __grid_constant__ CUtensorMap tmd, const bf16* __restrict__ gq, const bf16* __restrict__ gk, const bf16* __restrict__ gv,
             const bf16* __restrict__ gsk, const bf16* __restrict__ gh, const bf16* __restrict__ gD,
             const bf16* __restrict__ gwr, bf16* __restrict__ gout) {
  extern __shared__ __align__(128) unsigned char smraw[];
  Smem& sm = *reinterpret_cast<Smem*>(smraw);
  const int tid = threadIdx.x;
  const int cta = blockIdx.x;
  const int c0 = cta * CPC;
  const int lane = tid & 31;
  const int wid = tid >> 5;
  STAMP(0);
  const long long tstart = clock64();

  {
    uint4* hs = reinterpret_cast<uint4*>(&sm.z[0][0][0]);
    const int oc = tid >> 2;
    const int r0 = cta * 16 + (tid & 3) * 4;
    uint4 kk[7], vv[4], sk[4];
    if (tid < 320) {
      const uint4* kp = reinterpret_cast<const uint4*>(gk) + (size_t)r0 * 80 + oc;
      const uint4* vp = reinterpret_cast<const uint4*>(gv) + (size_t)r0 * 80 + oc;
#pragma unroll
      for (int i = 0; i < 7; i++) kk[i] = (i >= 3 || r0 > 0) ? __ldg(kp + (i - 3) * 80) : make_uint4(0, 0, 0, 0);
#pragma unroll
      for (int i = 0; i < 4; i++) vv[i] = __ldg(vp + i * 80);
#pragma unroll
      for (int i = 0; i < 4; i++) sk[i] = __ldg(reinterpret_cast<const uint4*>(gsk) + oc * 4 + i);
    } else if (tid == 320) {
      asm volatile("mbarrier.init.shared.b64 [%0], 1;" ::"r"(smem_u32(&sm.mbarh)) : "memory");
      asm volatile("mbarrier.init.shared.b64 [%0], 1;" ::"r"(smem_u32(&sm.mbar)) : "memory");
      asm volatile("mbarrier.init.shared.b64 [%0], 1;" ::"r"(smem_u32(&sm.mbarw)) : "memory");
      asm volatile("mbarrier.init.shared.b64 [%0], 1;" ::"r"(smem_u32(&sm.mbarc)) : "memory");
      asm volatile("mbarrier.init.shared.b64 [%0], 1;" ::"r"(smem_u32(&sm.mbary)) : "memory");
      asm volatile("fence.proxy.async.shared::cta;" ::: "memory");
    } else if (tid == 352) {
      uint32_t v2, v3;
      asm volatile("ld.relaxed.gpu.global.u32 %0, [%1];" : "=r"(v2) : "l"(&g_ctr2) : "memory");
      asm volatile("ld.relaxed.gpu.global.u32 %0, [%1];" : "=r"(v3) : "l"(&g_ctr3) : "memory");
      sm.target2 = (v2 / NCTA + 1u) * NCTA;
      sm.target3 = (v3 / NCTA + 1u) * NCTA;
    }
    if (tid < 320) bar_sync(6, 384); else { bar_arrive(6, 384); bar_sync(5, 64); }
    STAMP(9);
    if (tid < 320) {
      uint32_t o[4][4];
#pragma unroll
      for (int p = 0; p < 4; p++) {
        const bf162 w0 = u2b(__byte_perm(sk[p].x, sk[p].z, 0x5410)), w1 = u2b(__byte_perm(sk[p].x, sk[p].z, 0x7632));
        const bf162 w2 = u2b(__byte_perm(sk[p].y, sk[p].w, 0x5410)), w3 = u2b(__byte_perm(sk[p].y, sk[p].w, 0x7632));
        uint32_t kv[4];
#pragma unroll
        for (int i = 0; i < 4; i++) {
          const uint32_t k0 = p == 0 ? kk[i].x : p == 1 ? kk[i].y : p == 2 ? kk[i].z : kk[i].w;
          const uint32_t k1 = p == 0 ? kk[i + 1].x : p == 1 ? kk[i + 1].y : p == 2 ? kk[i + 1].z : kk[i + 1].w;
          const uint32_t k2 = p == 0 ? kk[i + 2].x : p == 1 ? kk[i + 2].y : p == 2 ? kk[i + 2].z : kk[i + 2].w;
          const uint32_t k3 = p == 0 ? kk[i + 3].x : p == 1 ? kk[i + 3].y : p == 2 ? kk[i + 3].z : kk[i + 3].w;
          const uint32_t vx = p == 0 ? vv[i].x : p == 1 ? vv[i].y : p == 2 ? vv[i].z : vv[i].w;
          bf162 a = __hmul2_rn(u2b(k0), w3);
          a = __hadd2_rn(a, __hmul2_rn(u2b(k1), w2));
          a = __hadd2_rn(a, __hmul2_rn(u2b(k2), w1));
          a = __hadd2_rn(a, __hmul2_rn(u2b(k3), w0));
          kv[i] = b2u(__hmul2_rn(a, u2b(vx)));
        }
        o[p][0] = enc(__byte_perm(kv[0], kv[1], 0x5410)); o[p][1] = enc(__byte_perm(kv[2], kv[3], 0x5410));
        o[p][2] = enc(__byte_perm(kv[0], kv[1], 0x7632)); o[p][3] = enc(__byte_perm(kv[2], kv[3], 0x7632));
      }
      uint2* dst = reinterpret_cast<uint2*>(g_kv) + (size_t)(oc * 8) * 512 + (r0 >> 2);
#pragma unroll
      for (int p = 0; p < 4; p++) {
        st_pub2(dst + (2 * p) * 512, o[p][0], o[p][1]);
        st_pub2(dst + (2 * p + 1) * 512, o[p][2], o[p][3]);
      }
      STAMP(10);
      if (wid == 0) bar_sync(4, 320); else bar_arrive(4, 320);
      if (tid == 0) {
        asm volatile("red.relaxed.gpu.global.add.u32 [%0], 1;" ::"l"(&g_ctr2) : "memory");
      }
      __syncwarp();
    } else {
      const int t0 = tid - 320;
      const uint4 zz = make_uint4(0, 0, 0, 0);
      if (tid == 320) {
        while (clock64() - tstart < H_DELAY) {}
        mbar_expect(&sm.mbarh, CPC * S_ * 2);
        bulk_g2s(hs, gh + (size_t)c0 * S_, CPC * S_ * 2, &sm.mbarh);
      }
      __syncwarp();
      for (int t = t0; t < CPC * 17; t += 64) *reinterpret_cast<uint4*>(&sm.u[t / 17][(t % 17) * 8]) = zz;
      if (t0 < 40) *reinterpret_cast<uint4*>(&sm.tabA[0][0][0] + tab_off(t0 >> 3) + ((t0 >> 2) & 1) * TABW + 1024 + 4 * (t0 & 3)) = zz;
      while (clock64() - tstart < C_DELAY) {}
      (&g_cand[cta][0][0])[t0] = zz;
      (&g_cand[cta][0][0])[64 + t0] = zz;
      if (t0 < 32) (&g_cand[cta][0][0])[128 + t0] = zz;
      else reinterpret_cast<uint4*>(&g_keys[cta][0])[t0 - 32] = zz;
      if (cta >= N1 && cta < N1 + N2) {
#pragma unroll
        for (int i = 0; i < 3; i++) g_act[cta - N1][t0 + 64 * i] = zz;
      }
      bar_sync(5, 64);
      if (tid == 352) {
        __threadfence();
        const unsigned old = atomicAdd(&g_ctr, 1u);
        sm.target = (old / NCTA + 1u) * NCTA;
      }
      __syncwarp();
    }
    mbar_wait(&sm.mbarh);
#pragma unroll
    for (int i = 0; i < 4; i++) {
      const int t = (NTHR - 1 - tid) + NTHR * i;
      if (t < CPC * 256) {
        uint32_t* tb = &sm.tabA[0][0][0] + tab_off(t >> 8) + (255 - (t & 255)) * 4;
        const uint4 h = hs[t];
        const uint32_t hp = (t & 255) ? reinterpret_cast<const uint32_t*>(hs)[4 * t - 1] : 0u;
        uint4 r1, rr;
        r1.x = __byte_perm(h.w, 0, 0x1032); r1.y = __byte_perm(h.z, 0, 0x1032);
        r1.z = __byte_perm(h.y, 0, 0x1032); r1.w = __byte_perm(h.x, 0, 0x1032);
        rr.x = __byte_perm(h.w, h.z, 0x7610); rr.y = __byte_perm(h.z, h.y, 0x7610);
        rr.z = __byte_perm(h.y, h.x, 0x7610); rr.w = __byte_perm(h.x, hp, 0x7610);
        *reinterpret_cast<uint4*>(tb) = rr;
        *reinterpret_cast<uint4*>(tb + TABW) = r1;
      }
    }
    STAMP(12);
  }
  __syncthreads();

  const int wg = __shfl_sync(0xffffffffu, tid >> 7, 0);
  const int wtid = tid & 127;
  uint4* tile = reinterpret_cast<uint4*>(&sm.tabB[0][0][0]);
  if (wg < 2) {
    asm volatile("setmaxnreg.inc.sync.aligned.u32 224;");
    const int w = (tid >> 5) & 3, g = lane >> 2, tq = lane & 3;
    float* zw = sm.z[wg][w];
    const int sw = 3 * (((tq + w) >> 1) & 1);
    const int off_even = 16 * (tq + w) + 4 * ((0 + (g >> 2)) ^ sw) + (g & 3);
    const int off_odd = 16 * (tq + w) + 4 * ((2 + (g >> 2)) ^ sw) + (g & 3);
    uint32_t a[8][8];
    const uint32_t* tp0 = &sm.tabA[0][g & 1][1019 - 8 * w - (g >> 1) + tq];
    load_a_all(a, tp0 + tab_off(wg));
    float acc[8][16];
#pragma unroll
    for (int b = 0; b < 8; b++)
#pragma unroll
      for (int i = 0; i < 16; i++) acc[b][i] = 0.f;
    gather_kv(sm, c0, tid);
    STAMP(1);
#pragma unroll 1
    for (int c = wg; c < CPC; c += 2) {
      const uint64_t desc = (uint64_t)((smem_u32(&sm.u[c][UPAD - 8]) & 0x3FFFF) >> 4) | ((uint64_t)1 << 16) | ((uint64_t)8 << 32);
      CST(c, 0);
      if (c > 0) bar_sync(1 + wg, 256);
      issue_g<0>(acc, a[0], desc);
      CST(c, 1);
      issue_g<1>(acc, a[1], desc);
      issue_g<2>(acc, a[2], desc);
      issue_g<3>(acc, a[3], desc);
      issue_g<4>(acc, a[4], desc);
      issue_g<5>(acc, a[5], desc);
      if (c + 1 < CPC) bar_arrive(1 + (wg ^ 1), 256);
      issue_g<6>(acc, a[6], desc);
      issue_g<7>(acc, a[7], desc);
      CST(c, 2);
      if (c >= 2) bar_sync(5 + wg, 256);
      wg_wait<4>();
      fence_blk<0>(acc); fence_blk<1>(acc); fence_blk<2>(acc); fence_blk<3>(acc);
      sts_blk<0>(acc, zw, off_even, off_odd);
      sts_blk<1>(acc, zw, off_even, off_odd);
      sts_blk<2>(acc, zw, off_even, off_odd);
      sts_blk<3>(acc, zw, off_even, off_odd);
      bar_arrive(9 + wg, 256);
      CST(c, 3);
      wg_wait<0>();
      fence_blk<4>(acc); fence_blk<5>(acc); fence_blk<6>(acc); fence_blk<7>(acc);
#pragma unroll
      for (int i = 0; i < 8; i++) fence_a(a[i]);
      sts_blk<4>(acc, zw, off_even, off_odd);
      sts_blk<5>(acc, zw, off_even, off_odd);
      sts_blk<6>(acc, zw, off_even, off_odd);
      sts_blk<7>(acc, zw, off_even, off_odd);
      bar_arrive(3 + wg, 256);
      CST(c, 4);
      if (c + 2 < CPC) load_a_all(a, tp0 + tab_off(c + 2));
    }
    STAMP(2 + wg);
    asm volatile("setmaxnreg.dec.sync.aligned.u32 168;");
  } else {
    asm volatile("setmaxnreg.dec.sync.aligned.u32 56;");
    if (((wtid & 15) >> 2) < ((wtid >> 4) & 3))
      *reinterpret_cast<uint4*>(&sm.z[wtid >> 6][(wtid >> 4) & 3][(wtid & 15) * 4]) = make_uint4(0, 0, 0, 0);
    if (wtid == 64) {
      const unsigned target = sm.target2;
      uint32_t v;
      int it = 0;
      do {
        asm volatile("ld.relaxed.gpu.global.u32 %0, [%1];" : "=r"(v) : "l"(&g_ctr2) : "memory");
      } while ((int)(v - target) < 0 && ++it < SPIN_LIMIT);
      asm volatile("mbarrier.arrive.shared.b64 _, [%0];" ::"r"(smem_u32(&sm.mbarc)) : "memory");
    }
    __syncwarp();
    gather_kv(sm, c0, tid);
#pragma unroll
    for (int i = 0; i < 10; i++) g_kv[c0 * 256 + wtid + 128 * i] = make_uint4(0, 0, 0, 0);
    if (wtid == 96) wait_ctr(&g_ctr, sm.target);
    __syncwarp();
    if (wtid == 32) {
      const uint32_t mw = smem_u32(&sm.mbarw);
      mbar_expect(&sm.mbar, 17 * D_ * 2);
#pragma unroll 1
      for (int r = 0; r < 16; r++) bulk_g2s(&sm.q[r][0], gq + (size_t)(cta * 16 + r) * D_, D_ * 2, &sm.mbar);
      bulk_g2s(&sm.wr[0], gwr, D_ * 2, &sm.mbar);
      if (cta < N1) {
        asm volatile("mbarrier.arrive.expect_tx.shared.b64 _, [%0], %1;" ::"r"(mw), "r"(3840 * 16) : "memory");
#pragma unroll 1
        for (int i = 0; i < 4; i++) {
          asm volatile("cp.async.bulk.tensor.2d.shared::cluster.global.mbarrier::complete_tx::bytes [%0], [%1, {%3, %4}], [%2];" ::"r"(smem_u32(&sm.w[i * 480])),
                       "l"(&tmg), "r"(mw), "r"(cta * 24), "r"(i * 160) : "memory");
          asm volatile("cp.async.bulk.tensor.2d.shared::cluster.global.mbarrier::complete_tx::bytes [%0], [%1, {%3, %4}], [%2];" ::"r"(smem_u32(&sm.w[1920 + i * 480])),
                       "l"(&tmu), "r"(mw), "r"(cta * 24), "r"(i * 160) : "memory");
        }
      } else if (cta < N1 + N2) {
        asm volatile("mbarrier.arrive.expect_tx.shared.b64 _, [%0], %1;" ::"r"(mw), "r"(3072 * 16) : "memory");
#pragma unroll 1
        for (int i = 0; i < 6; i++)
          asm volatile("cp.async.bulk.tensor.2d.shared::cluster.global.mbarrier::complete_tx::bytes [%0], [%1, {%3, %4}], [%2];" ::"r"(smem_u32(&sm.w[i * 512])),
                       "l"(&tmd), "r"(mw), "r"((cta - N1) * 16), "r"(i * 256) : "memory");
      }
    }
    const int rpb = wtid >> 1, re2 = wtid & 1;
    const int rsw = 3 * ((rpb >> 1) & 1);
    const int roff0 = 16 * rpb + 4 * ((2 * re2 + 0) ^ rsw);
    const int roff1 = 16 * rpb + 4 * ((2 * re2 + 1) ^ rsw);
    const uint32_t dvl = reinterpret_cast<const unsigned short*>(gD)[c0 + (lane < CPC ? lane : 0)];
#pragma unroll 1
    for (int c = 0; c < CPC; c++) {
      const int zg = c & 1;
      const uint32_t dvc = __shfl_sync(0xffffffffu, dvl, c);
      const bf162 d2 = u2b(dvc | (dvc << 16));
      CST(c, 5);
#pragma unroll
      for (int half = 0; half < 2; half++) {
        bar_sync((half ? 3 : 9) + zg, 256);
        const float* zb = sm.z[zg][0] + half * 1024;
        float4 x[4][2];
#pragma unroll
        for (int ww = 0; ww < 4; ww++) {
          x[ww][0] = *reinterpret_cast<const float4*>(zb + ww * ZPB * 16 + roff0);
          x[ww][1] = *reinterpret_cast<const float4*>(zb + ww * ZPB * 16 + roff1);
        }
        const int sidx = half * 1024 + wtid * 8;
        const uint4 kvv = *reinterpret_cast<const uint4*>(&sm.u[c][UPAD + sidx]);
        if (half == 1 && c + 2 < CPC) bar_arrive(5 + zg, 256);
        uint4 o;
        o.x = pack2((x[0][0].x + x[1][0].x) + (x[2][0].x + x[3][0].x), (x[0][0].y + x[1][0].y) + (x[2][0].y + x[3][0].y));
        o.y = pack2((x[0][0].z + x[1][0].z) + (x[2][0].z + x[3][0].z), (x[0][0].w + x[1][0].w) + (x[2][0].w + x[3][0].w));
        o.z = pack2((x[0][1].x + x[1][1].x) + (x[2][1].x + x[3][1].x), (x[0][1].y + x[1][1].y) + (x[2][1].y + x[3][1].y));
        o.w = pack2((x[0][1].z + x[1][1].z) + (x[2][1].z + x[3][1].z), (x[0][1].w + x[1][1].w) + (x[2][1].w + x[3][1].w));
        o.x = b2u(__hadd2_rn(u2b(o.x), __hmul2_rn(u2b(kvv.x), d2)));
        o.y = b2u(__hadd2_rn(u2b(o.y), __hmul2_rn(u2b(kvv.y), d2)));
        o.z = b2u(__hadd2_rn(u2b(o.z), __hmul2_rn(u2b(kvv.z), d2)));
        o.w = b2u(__hadd2_rn(u2b(o.w), __hmul2_rn(u2b(kvv.w), d2)));
        st_pub4(g_y2 + ((64 * half + rpb) * 640 + c0 + c) * 2 + re2, enc4(o));
        CST(c, 6 + half);
      }
    }
    if (wid == 11) bar_sync(8, 128); else bar_arrive(8, 128);
    STAMP(4);
    asm volatile("setmaxnreg.inc.sync.aligned.u32 168;");
  }

  if (tid == 352) {
    asm volatile("red.relaxed.gpu.global.add.u32 [%0], 1;" ::"l"(&g_ctr3) : "memory");
    wait_ctr(&g_ctr3, sm.target3);
    asm volatile("mbarrier.arrive.shared.b64 _, [%0];" ::"r"(smem_u32(&sm.mbary)) : "memory");
  }
  __syncwarp();
  if (ABL == 4) { mbar_wait(&sm.mbary); for (int i = tid; i < 1280; i += NTHR) g_y2[cta * 1280 + i] = make_uint4(0, 0, 0, 0); if (cta < N1 + N2) mbar_wait(&sm.mbarw); mbar_wait(&sm.mbar); return; }
  RT(0);
  const int g = lane >> 2, tq = lane & 3;
  const int hh = wid & 1, gqi = wid >> 1;
  const int row = hh * 8 + g;
  uint32_t hreg[20], hnreg[20];
  {
    const uint4* src = g_y2 + cta * 1280 + tid;
    uint4 v[4];
    if (wid < 8) {
      mbar_wait(&sm.mbar);
#pragma unroll
      for (int k = 0; k < 5; k++) {
        const uint4 qv4 = *reinterpret_cast<const uint4*>(&sm.q[row][32 * (5 * gqi + k) + 8 * tq]);
        hreg[4 * k] = qv4.x; hreg[4 * k + 1] = qv4.y; hreg[4 * k + 2] = qv4.z; hreg[4 * k + 3] = qv4.w;
      }
      const float2 ps = row_part_stats(hreg);
      if (tq == 0) sm.stq[row][gqi] = ps;
      bar_sync(7, 256);
      row_normalize(reinterpret_cast<const float4*>(sm.stq[row]), hreg, hnreg);
    }
    RT(1);
    mbar_wait(&sm.mbary);
    RT(2);
#pragma unroll
    for (int i = 0; i < 4; i++) if (i < 3 || tid < 128) v[i] = ld_poll4(src + NTHR * i);
    int it = 0;
    bool all;
    do {
      all = true;
#pragma unroll
      for (int i = 0; i < 4; i++)
        if ((i < 3 || tid < 128) && !ready4(v[i])) { v[i] = ld_poll4(src + NTHR * i); all = false; }
    } while (!all && ++it < SPIN_LIMIT);
#pragma unroll
    for (int i = 0; i < 4; i++) {
      if (i < 3 || tid < 128) {
        const int t = tid + NTHR * i;
        tile[(t & 1) * 640 + tile_perm(t >> 1)] = make_uint4(~v[i].x, ~v[i].y, ~v[i].z, ~v[i].w);
      }
    }
  }
  __syncthreads();
  STAMP(5);
  RT(3);
  if (ABL == 3) { for (int i = tid; i < 1280; i += NTHR) g_y2[cta * 1280 + i] = make_uint4(0, 0, 0, 0); if (cta < N1 + N2) mbar_wait(&sm.mbarw); return; }

  if (wid < 8) {
#pragma unroll
    for (int k = 0; k < 5; k++) {
      const int base = 32 * (5 * gqi + k);
      const int lch = base + 8 * ((lane & 7) >> 1) + 2 * (lane >> 3) + (lane & 1);
      uint32_t y[4];
      asm volatile("ldmatrix.sync.aligned.m8n8.x4.trans.shared.b16 {%0,%1,%2,%3}, [%4];"
                   : "=r"(y[0]), "=r"(y[1]), "=r"(y[2]), "=r"(y[3]) : "r"(smem_u32(&tile[hh * 640 + tile_perm(lch)])) : "memory");
#pragma unroll
      for (int i = 0; i < 4; i++)
        hreg[4 * k + i] = b2u(__hadd2_rn(u2b(hreg[4 * k + i]), __hmul2_rn(u2b(hnreg[4 * k + i]), u2b(y[i]))));
    }
    RT(4);
    const float2 ps = row_part_stats(hreg);
    if (tq == 0) sm.st[row][gqi] = ps;
    STAMP(13);
    RT(5);
    bar_sync(7, 256);
    row_normalize(reinterpret_cast<const float4*>(sm.st[row]), hreg, hnreg);
    RT(6);
    float cr[5][4];
#pragma unroll
    for (int k = 0; k < 5; k++) {
      cr[k][0] = cr[k][1] = cr[k][2] = cr[k][3] = 0.f;
      const uint4 w4 = sm.wr[4 * (5 * gqi + k) + tq];
      mma_bf16(cr[k], hnreg[4 * k + 0], hnreg[4 * k + 1], w4.x, w4.y);
      mma_bf16(cr[k], hnreg[4 * k + 2], hnreg[4 * k + 3], w4.z, w4.w);
    }
    if (tq == 0) sm.rp[row][gqi] = ((cr[0][0] + cr[1][0]) + (cr[2][0] + cr[3][0])) + cr[4][0];
  }
  STAMP(14);
  RT(7);
  __syncthreads();
  uint32_t best;
  {
    const int rr = lane & 15;
    const float4 rp4 = *reinterpret_cast<const float4*>(sm.rp[rr]);
    const float r = (rp4.x + rp4.y) + (rp4.z + rp4.w);
    const uint32_t bits = __bfloat16_as_ushort(__float2bfloat16_rn(r));
    const uint32_t ord = (bits & 0x8000u) ? (bits ^ 0xFFFFu) : (bits ^ 0x8000u);
    const uint32_t key = (ord << 16) | 0x8000u | (uint32_t)(2047 - (cta * 16 + rr));
    best = __reduce_max_sync(0xffffffffu, key);
  }
  if (wid >= 8) asm volatile("st.relaxed.gpu.global.u32 [%0], %1;" ::"l"(&g_keys[tid - 256][cta]), "r"(best) : "memory");
  STAMP(15);
  RT(8);
  const int brow = (2047 - (int)(best & 0x7FFu)) - cta * 16;
  if (wid < 8 && row == brow) {
#pragma unroll
    for (int k = 0; k < 5; k++)
      st_pub4(&g_cand[cta][0][4 * (5 * gqi + k) + tq], enc4(make_uint4(hnreg[4 * k], hnreg[4 * k + 1], hnreg[4 * k + 2], hnreg[4 * k + 3])));
#pragma unroll
    for (int k = 0; k < 5; k++)
      st_pub4(&g_cand[cta][1][4 * (5 * gqi + k) + tq], enc4(make_uint4(hreg[4 * k], hreg[4 * k + 1], hreg[4 * k + 2], hreg[4 * k + 3])));
  }
#pragma unroll
  for (int i = 0; i < 20; i++) hreg[i] = b2u(__hadd2_rn(u2b(hreg[i]), u2b(hnreg[i])));
  STAMP(6);
  RT(9);
  if (ABL == 2) { for (int i = tid; i < 1280; i += NTHR) g_y2[cta * 1280 + i] = make_uint4(0, 0, 0, 0); if (cta < N1 + N2) mbar_wait(&sm.mbarw); return; }
  if (wid == 11) {
    const uint4* kp = reinterpret_cast<const uint4*>(&g_keys[cta][0]) + lane;
    uint4 v = ld_poll4(kp);
    int it = 0;
    while (!ready4(v) && ++it < SPIN_LIMIT) v = ld_poll4(kp);
    const uint32_t m = max(max(v.x, v.y), max(v.z, v.w));
    const uint32_t wk = __reduce_max_sync(0xffffffffu, m);
    if (lane == 0) sm.win = wk;
  }
  __syncthreads();
  const uint32_t win = sm.win;
  const int wrow = 2047 - (int)(win & 0x7FFu);
  const int wcta = wrow >> 4;
  const bool st_out = wid < 8 && (cta * 16 + row) != wrow;
  uint4* outp = reinterpret_cast<uint4*>(gout + (size_t)(cta * 16 + row) * D_) + 20 * gqi + tq;
  if (cta >= N1) {
    if (st_out) {
#pragma unroll
      for (int k = 0; k < 5; k++) outp[4 * k] = make_uint4(hreg[4 * k], hreg[4 * k + 1], hreg[4 * k + 2], hreg[4 * k + 3]);
    }
  }
  if (cta >= N1 || ABL == 1) {
#pragma unroll
    for (int i = 0; i < 4; i++) if (i < 3 || tid < 128) g_y2[cta * 1280 + tid + NTHR * i] = make_uint4(0, 0, 0, 0);
  }
  STAMP(7);
  RT(10);
  if (ABL == 1) { if (cta < N1 + N2) mbar_wait(&sm.mbarw); return; }
  uint4* xs = reinterpret_cast<uint4*>(&sm.z[0][0][0]);
  const uint32_t* xw = reinterpret_cast<const uint32_t*>(xs);
  float* part = reinterpret_cast<float*>(xs + 256);
  if (cta < N1) {
    if (tid < 80) xs[tid] = poll4(&g_cand[wcta][0][tid]);
    mbar_wait(&sm.mbarw);
    __syncthreads();
    const int m = wid / 6, nt = (wid % 6) >> 1, kh = wid & 1;
    float c0a[4] = {0.f, 0.f, 0.f, 0.f}, c1a[4] = {0.f, 0.f, 0.f, 0.f};
    const uint32_t wbase = smem_u32(&sm.w[m * 1920 + (kh * 320 + lane) * 3 + nt]);
#pragma unroll
    for (int it = 0; it < 10; it++) {
      uint32_t b[4];
      asm volatile("ldmatrix.sync.aligned.m8n8.x4.trans.shared.b16 {%0,%1,%2,%3}, [%4];"
                   : "=r"(b[0]), "=r"(b[1]), "=r"(b[2]), "=r"(b[3]) : "r"(wbase + it * 32 * 48) : "memory");
      const uint32_t* xp = xw + kh * 160 + it * 16 + tq;
      mma_bf16(c0a, xp[0], xp[4], b[0], b[1]);
      mma_bf16(c1a, xp[8], xp[12], b[2], b[3]);
    }
    if (g == 0) *reinterpret_cast<float2*>(part + wid * 8 + 2 * tq) = make_float2(c0a[0] + c1a[0], c0a[1] + c1a[1]);
    __syncthreads();
    if (wid == 0) {
      uint32_t bits = 0;
      if (lane < 24) {
        const int hc2 = lane >> 3, j = lane & 7;
        const float gt = rbf(part[(2 * hc2) * 8 + j] + part[(2 * hc2 + 1) * 8 + j]);
        const float up = rbf(part[(6 + 2 * hc2) * 8 + j] + part[(6 + 2 * hc2 + 1) * 8 + j]);
        const float sg = rbf(gt / (1.f + __expf(-gt)));
        bits = __bfloat16_as_ushort(__float2bfloat16_rn(sg * up));
      }
      const uint32_t nb = __shfl_down_sync(0xffffffffu, bits, 1);
      const uint32_t pw = enc(bits | (nb << 16));
#pragma unroll
      for (int i = 0; i < 4; i++) {
        const int t = lane + 32 * i;
        const int cons = t / 3, ck = t - 3 * cons;
        uint4 v;
        v.x = __shfl_sync(0xffffffffu, pw, 8 * ck); v.y = __shfl_sync(0xffffffffu, pw, 8 * ck + 2);
        v.z = __shfl_sync(0xffffffffu, pw, 8 * ck + 4); v.w = __shfl_sync(0xffffffffu, pw, 8 * ck + 6);
        if (t < 3 * N2) st_pub4(&g_act[cons][cta * 3 + ck], v);
      }
      __syncwarp();
      bar_arrive(7, 384);
    } else {
      bar_sync(7, 384);
    }
#pragma unroll
    for (int i = 0; i < 4; i++) if (i < 3 || tid < 128) g_y2[cta * 1280 + tid + NTHR * i] = make_uint4(0, 0, 0, 0);
    if (st_out) {
#pragma unroll
      for (int k = 0; k < 5; k++) outp[4 * k] = make_uint4(hreg[4 * k], hreg[4 * k + 1], hreg[4 * k + 2], hreg[4 * k + 3]);
    }
  } else if (cta < N1 + N2 && ABL != 6) {
    const int j2 = cta - N1;
    if (tid < 192) xs[tid] = poll4(&g_act[j2][tid]);
    else if (tid < 196) {
      const int t = tid - 192;
      reinterpret_cast<uint4*>(part + 256)[t] = poll4(&g_cand[wcta][t >> 1][j2 * 2 + (t & 1)]);
    }
    mbar_wait(&sm.mbarw);
    __syncthreads();
    float c0a[4] = {0.f, 0.f, 0.f, 0.f}, c1a[4] = {0.f, 0.f, 0.f, 0.f};
    const uint32_t wbase = smem_u32(&sm.w[(wid * 128 + (lane & 15)) * 2 + (lane >> 4)]);
#pragma unroll
    for (int it = 0; it < 8; it++) {
      uint32_t b[4];
      asm volatile("ldmatrix.sync.aligned.m8n8.x4.trans.shared.b16 {%0,%1,%2,%3}, [%4];"
                   : "=r"(b[0]), "=r"(b[1]), "=r"(b[2]), "=r"(b[3]) : "r"(wbase + it * 16 * 32) : "memory");
      const uint32_t* xp = xw + wid * 64 + it * 8 + tq;
      const uint32_t x0 = xp[0], x1 = xp[4];
      mma_bf16(c0a, x0, x1, b[0], b[1]);
      mma_bf16(c1a, x0, x1, b[2], b[3]);
    }
    if (g == 0) {
      *reinterpret_cast<float2*>(part + wid * 16 + 2 * tq) = make_float2(c0a[0], c0a[1]);
      *reinterpret_cast<float2*>(part + wid * 16 + 8 + 2 * tq) = make_float2(c1a[0], c1a[1]);
    }
    __syncthreads();
    if (tid < 16) {
      float y0 = 0.f, y1 = 0.f, y2 = 0.f;
#pragma unroll
      for (int i = 0; i < 4; i++) { y0 += part[i * 16 + tid]; y1 += part[(4 + i) * 16 + tid]; y2 += part[(8 + i) * 16 + tid]; }
      const float y = (y0 + y1) + y2;
      const uint32_t ord = win >> 16;
      const uint32_t rb = (ord & 0x8000u) ? (ord ^ 0x8000u) : (ord ^ 0xFFFFu);
      const float r = __uint_as_float(rb << 16);
      const float sg = rbf(1.f / (1.f + __expf(-r)));
      const float yy = rbf(rbf(y) * sg);
      const unsigned short* rv = reinterpret_cast<const unsigned short*>(part + 256);
      const float hn = __uint_as_float((uint32_t)rv[tid] << 16), h = __uint_as_float((uint32_t)rv[16 + tid] << 16);
      gout[(size_t)wrow * D_ + j2 * 16 + tid] = __float2bfloat16_rn(h + rbf(hn + yy));
    }
  }
  STAMP(8);
  RT(11);
}

}

typedef CUresult (*EncodeFn)(CUtensorMap*, CUtensorMapDataType, cuuint32_t, void*, const cuuint64_t*, const cuuint64_t*,
                             const cuuint32_t*, const cuuint32_t*, CUtensorMapInterleave, CUtensorMapSwizzle,
                             CUtensorMapL2promotion, CUtensorMapFloatOOBfill);

extern "C" void kernel_launch(void* const* d_in, const int* in_sizes, int n_in, void* d_out, int out_size) {
  (void)in_sizes; (void)n_in; (void)out_size;
  static EncodeFn encode = nullptr;
  static CUtensorMap tmg, tmu, tmd;
  static void* cached[3] = {nullptr, nullptr, nullptr};
  if (!encode) {
    cudaFuncSetAttribute(fused_kernel, cudaFuncAttributeMaxDynamicSharedMemorySize, (int)sizeof(Smem));
    void* fn = nullptr;
    cudaDriverEntryPointQueryResult qr;
    cudaGetDriverEntryPoint("cuTensorMapEncodeTiled", &fn, cudaEnableDefault, &qr);
    encode = (EncodeFn)fn;
  }
  if (cached[0] != d_in[8] || cached[1] != d_in[9] || cached[2] != d_in[10]) {
    const cuuint32_t es[2] = {1, 1};
    {
      const cuuint64_t dims[2] = {F_, D_}, strides[1] = {F_ * 2};
      const cuuint32_t box[2] = {24, 160};
      encode(&tmg, CU_TENSOR_MAP_DATA_TYPE_BFLOAT16, 2, d_in[8], dims, strides, box, es, CU_TENSOR_MAP_INTERLEAVE_NONE,
             CU_TENSOR_MAP_SWIZZLE_NONE, CU_TENSOR_MAP_L2_PROMOTION_NONE, CU_TENSOR_MAP_FLOAT_OOB_FILL_NONE);
      encode(&tmu, CU_TENSOR_MAP_DATA_TYPE_BFLOAT16, 2, d_in[9], dims, strides, box, es, CU_TENSOR_MAP_INTERLEAVE_NONE,
             CU_TENSOR_MAP_SWIZZLE_NONE, CU_TENSOR_MAP_L2_PROMOTION_NONE, CU_TENSOR_MAP_FLOAT_OOB_FILL_NONE);
    }
    {
      const cuuint64_t dims[2] = {D_, F_}, strides[1] = {D_ * 2};
      const cuuint32_t box[2] = {16, 256};
      encode(&tmd, CU_TENSOR_MAP_DATA_TYPE_BFLOAT16, 2, d_in[10], dims, strides, box, es, CU_TENSOR_MAP_INTERLEAVE_NONE,
             CU_TENSOR_MAP_SWIZZLE_NONE, CU_TENSOR_MAP_L2_PROMOTION_NONE, CU_TENSOR_MAP_FLOAT_OOB_FILL_NONE);
    }
    cached[0] = d_in[8]; cached[1] = d_in[9]; cached[2] = d_in[10];
  }
  fused_kernel<<<NCTA, NTHR, sizeof(Smem), cudaStreamPerThread>>>(
      tmg, tmu, tmd, (const bf16*)d_in[0], (const bf16*)d_in[1], (const bf16*)d_in[2], (const bf16*)d_in[3],
      (const bf16*)d_in[4], (const bf16*)d_in[5], (const bf16*)d_in[7], (bf16*)d_out);
}
```

```cpp
#include <cuda_runtime.h>
#include <cuda_bf16.h>
#include <cuda.h>
#include <stdint.h>

namespace {

typedef __nv_bfloat16 bf16;
typedef __nv_bfloat162 bf162;

constexpr int S_ = 2048, D_ = 640, F_ = 1536;
constexpr int NCTA = 128, CPC = 5, NTHR = 384;
constexpr int UPAD = 136, USTR = 2192;
constexpr int TABW = 1040;
constexpr int ZPB = 132;
constexpr int QSTR = 648;
constexpr int N1 = 64;
constexpr int N2 = 40;
constexpr int SPIN_LIMIT = 1 << 19;
#define LN2_EXACT 1
#define ABL 0
#define CTR_NS 0
#define C_DELAY 0
#define TESTV 0
#define TESTC 0
#define POLL_NS 100
#define H_DELAY 0
#define Q_DELAY 4500

struct __align__(128) Smem {
  uint32_t tabA[3][2][TABW];
  uint32_t extra[1024];
  uint32_t tabB[2][2][TABW];
  bf16 u[CPC][USTR];
  float z[2][4][ZPB * 16];
  bf16 q[16][QSTR];
  alignas(128) uint4 w[3840];
  uint4 wr[80];
  alignas(16) float2 st[16][4];
  alignas(16) float2 stq[16][4];
  alignas(16) float rp[16][4];
  unsigned long long mbar;
  unsigned long long mbarw;
  unsigned long long mbarc;
  unsigned long long mbary;
  unsigned long long mbarh;
  uint32_t target;
  uint32_t target2;
  uint32_t target3;
  uint32_t best;
  uint32_t win;
};

__device__ uint4 g_kv[D_ * S_ / 8];
__device__ uint4 g_y2[D_ * S_ / 8];
__device__ uint32_t g_keys[NCTA][NCTA];
__device__ uint4 g_cand[NCTA][2][80];
__device__ uint4 g_act[N2][F_ / 8];
__device__ unsigned int g_ctr;
__device__ unsigned int g_ctr2;
__device__ unsigned int g_ctr3;
#define STAMP(i)
#define RT(i)
#define CST(c, i)

__device__ __forceinline__ uint32_t smem_u32(const void* p) { return (uint32_t)__cvta_generic_to_shared(p); }
__device__ __forceinline__ void wg_fence() { asm volatile("wgmma.fence.sync.aligned;" ::: "memory"); }
__device__ __forceinline__ void wg_commit() { asm volatile("wgmma.commit_group.sync.aligned;" ::: "memory"); }
template <int N> __device__ __forceinline__ void wg_wait() { asm volatile("wgmma.wait_group.sync.aligned %0;" ::"n"(N) : "memory"); }
__device__ __forceinline__ void bar_sync(int id, int n) { asm volatile("bar.sync %0, %1;" ::"r"(id), "r"(n) : "memory"); }
__device__ __forceinline__ void bar_arrive(int id, int n) { asm volatile("bar.arrive %0, %1;" ::"r"(id), "r"(n) : "memory"); }
__device__ __forceinline__ bf162 u2b(uint32_t u) { return *reinterpret_cast<bf162*>(&u); }
__device__ __forceinline__ uint32_t b2u(bf162 b) { return *reinterpret_cast<uint32_t*>(&b); }
__device__ __forceinline__ float lo_f(uint32_t u) { return __uint_as_float(u << 16); }
__device__ __forceinline__ float hi_f(uint32_t u) { return __uint_as_float(u & 0xFFFF0000u); }
__device__ __forceinline__ float rbf(float x) { return __bfloat162float(__float2bfloat16_rn(x)); }
__device__ __forceinline__ uint32_t pack2(float a, float b) { return b2u(__floats2bfloat162_rn(a, b)); }
__device__ __forceinline__ uint32_t enc(uint32_t w) { return max(~w, 1u); }
__device__ __forceinline__ uint4 enc4(uint4 v) { return make_uint4(enc(v.x), enc(v.y), enc(v.z), enc(v.w)); }
__device__ __forceinline__ uint4 ld_poll4(const uint4* p) {
  uint4 v;
  asm volatile("ld.relaxed.gpu.global.v4.u32 {%0,%1,%2,%3}, [%4];" : "=r"(v.x), "=r"(v.y), "=r"(v.z), "=r"(v.w) : "l"(p) : "memory");
  return v;
}
__device__ __forceinline__ bool ready4(uint4 v) { return v.x != 0u && v.y != 0u && v.z != 0u && v.w != 0u; }
__device__ __forceinline__ uint4 poll4(const uint4* p) {
  uint4 v = ld_poll4(p);
  int it = 0;
  while (!ready4(v) && ++it < SPIN_LIMIT) v = ld_poll4(p);
  return make_uint4(~v.x, ~v.y, ~v.z, ~v.w);
}
__device__ __forceinline__ void st_pub4(uint4* p, uint4 v) {
  asm volatile("st.relaxed.gpu.global.v4.u32 [%0], {%1,%2,%3,%4};" ::"l"(p), "r"(v.x), "r"(v.y), "r"(v.z), "r"(v.w) : "memory");
}
__device__ __forceinline__ void st_pub2(uint2* p, uint32_t a, uint32_t b) {
  asm volatile("st.relaxed.gpu.global.v2.u32 [%0], {%1,%2};" ::"l"(p), "r"(a), "r"(b) : "memory");
}
__device__ __forceinline__ void mma_bf16(float (&c)[4], uint32_t a0, uint32_t a2, uint32_t b0, uint32_t b1) {
  asm volatile("mma.sync.aligned.m16n8k16.row.col.f32.bf16.bf16.f32 {%0,%1,%2,%3}, {%4,%5,%6,%5}, {%7,%8}, {%0,%1,%2,%3};"
               : "+f"(c[0]), "+f"(c[1]), "+f"(c[2]), "+f"(c[3]) : "r"(a0), "r"(0u), "r"(a2), "r"(b0), "r"(b1));
}
__device__ __forceinline__ void mbar_wait(const unsigned long long* bar) {
  const uint32_t mb = smem_u32(bar);
  uint32_t ok = 0;
  int it = 0;
  while (!ok && ++it < SPIN_LIMIT)
    asm volatile("{ .reg .pred p; mbarrier.try_wait.parity.shared.b64 p, [%1], 0; selp.u32 %0, 1, 0, p; }" : "=r"(ok) : "r"(mb) : "memory");
}
__device__ __forceinline__ void bulk_g2s(void* dst, const void* src, uint32_t bytes, const unsigned long long* bar) {
  asm volatile("cp.async.bulk.shared::cluster.global.mbarrier::complete_tx::bytes [%0], [%1], %2, [%3];" ::"r"(smem_u32(dst)),
               "l"(src), "r"(bytes), "r"(smem_u32(bar)) : "memory");
}
__device__ __forceinline__ void mbar_expect(const unsigned long long* bar, uint32_t bytes) {
  asm volatile("mbarrier.arrive.expect_tx.shared.b64 _, [%0], %1;" ::"r"(smem_u32(bar)), "r"(bytes) : "memory");
}
__device__ __forceinline__ void mma_bf16x(float (&c)[4], uint32_t a0, uint32_t a1, uint32_t a2, uint32_t a3, uint32_t b0, uint32_t b1) {
  asm volatile("mma.sync.aligned.m16n8k16.row.col.f32.bf16.bf16.f32 {%0,%1,%2,%3}, {%4,%5,%6,%7}, {%8,%9}, {%0,%1,%2,%3};"
               : "+f"(c[0]), "+f"(c[1]), "+f"(c[2]), "+f"(c[3]) : "r"(a0), "r"(a1), "r"(a2), "r"(a3), "r"(b0), "r"(b1));
}
__device__ __forceinline__ float fdivr(float a, float d, float r) {
  float q = a * r;
  float e = fmaf(-q, d, a);
  return fmaf(e, r, q);
}

template <bool FIRST> __device__ __forceinline__ void wgmma32(float (&d)[16], const uint32_t* a, uint64_t desc) {
  if (FIRST) {
    asm volatile("wgmma.mma_async.sync.aligned.m64n32k16.f32.bf16.bf16 {%0,%1,%2,%3,%4,%5,%6,%7,%8,%9,%10,%11,%12,%13,%14,%15}, {%16,%17,%18,%19}, %20, 0, 1, 1, 0;"
                 : "+f"(d[0]), "+f"(d[1]), "+f"(d[2]), "+f"(d[3]), "+f"(d[4]), "+f"(d[5]), "+f"(d[6]), "+f"(d[7]),
                   "+f"(d[8]), "+f"(d[9]), "+f"(d[10]), "+f"(d[11]), "+f"(d[12]), "+f"(d[13]), "+f"(d[14]), "+f"(d[15])
                 : "r"(a[0]), "r"(a[1]), "r"(a[2]), "r"(a[3]), "l"(desc));
  } else {
    asm volatile("wgmma.mma_async.sync.aligned.m64n32k16.f32.bf16.bf16 {%0,%1,%2,%3,%4,%5,%6,%7,%8,%9,%10,%11,%12,%13,%14,%15}, {%16,%17,%18,%19}, %20, 1, 1, 1, 0;"
                 : "+f"(d[0]), "+f"(d[1]), "+f"(d[2]), "+f"(d[3]), "+f"(d[4]), "+f"(d[5]), "+f"(d[6]), "+f"(d[7]),
                   "+f"(d[8]), "+f"(d[9]), "+f"(d[10]), "+f"(d[11]), "+f"(d[12]), "+f"(d[13]), "+f"(d[14]), "+f"(d[15])
                 : "r"(a[0]), "r"(a[1]), "r"(a[2]), "r"(a[3]), "l"(desc));
  }
}

template <int G> __device__ __forceinline__ void load_a(uint32_t (&a)[8], const uint32_t* tp) {
#pragma unroll
  for (int q = 0; q < 2; q++) {
    const int e = 2 * G + q;
    a[4 * q + 0] = tp[-64 * e];
    a[4 * q + 1] = tp[-64 * e - 32];
    a[4 * q + 2] = tp[-64 * e + 4];
    a[4 * q + 3] = tp[-64 * e - 28];
  }
}
__device__ __forceinline__ void load_a_all(uint32_t (&a)[8][8], const uint32_t* tp) {
  load_a<0>(a[0], tp); load_a<1>(a[1], tp); load_a<2>(a[2], tp); load_a<3>(a[3], tp);
  load_a<4>(a[4], tp); load_a<5>(a[5], tp); load_a<6>(a[6], tp); load_a<7>(a[7], tp);
}
template <int G> __device__ __forceinline__ void issue_g(float (&acc)[8][16], uint32_t (&a)[8], uint64_t desc0) {
  wg_fence();
#pragma unroll
  for (int q = 0; q < 2; q++) {
#pragma unroll
    for (int b = G; b < 8; b++) {
      const int delta = 2 * b - (2 * G + q);
      if (G == 0 && q == 0) wgmma32<true>(acc[b], &a[4 * q], desc0 + (uint64_t)(int64_t)(16 * delta));
      else wgmma32<false>(acc[b], &a[4 * q], desc0 + (uint64_t)(int64_t)(16 * delta));
    }
  }
  wg_commit();
}
template <int B> __device__ __forceinline__ void fence_blk(float (&acc)[8][16]) {
#pragma unroll
  for (int i = 0; i < 16; i++) asm volatile("" : "+f"(acc[B][i])::"memory");
}
__device__ __forceinline__ void fence_a(uint32_t (&a)[8]) {
#pragma unroll
  for (int i = 0; i < 8; i++) asm volatile("" : "+r"(a[i])::"memory");
}
template <int B> __device__ __forceinline__ void sts_blk(float (&acc)[8][16], float* zw, int off_even, int off_odd) {
#pragma unroll
  for (int jj = 0; jj < 4; jj++) {
    const int j = 4 * B + jj;
    float p0 = acc[B][4 * jj + 0], p1 = acc[B][4 * jj + 1];
    if (jj > 0) { p0 += acc[B][4 * (jj - 1) + 2]; p1 += acc[B][4 * (jj - 1) + 3]; }
    else if (B > 0) { p0 += acc[B > 0 ? B - 1 : 0][14]; p1 += acc[B > 0 ? B - 1 : 0][15]; }
    zw[64 * j + off_even] = p0;
    zw[64 * j + off_odd] = p1;
  }
}
__device__ __forceinline__ int tab_off(int c) { return c == 4 ? 0 : (c + 1) * 2 * TABW + (c >= 2 ? 1024 : 0); }
__device__ __forceinline__ int tile_perm(int ch) { return ch ^ (((ch >> 3) & 3) << 1); }

__device__ __forceinline__ void wait_ctr(const unsigned int* ctr, uint32_t target) {
  uint32_t v;
  int it = 0;
  do {
    asm volatile("ld.acquire.gpu.global.u32 %0, [%1];" : "=r"(v) : "l"(ctr) : "memory");
  } while ((int)(v - target) < 0 && ++it < SPIN_LIMIT);
}

__device__ __forceinline__ float2 row_part_stats(const uint32_t (&x)[20]) {
  float cs[5][4];
#pragma unroll
  for (int k = 0; k < 5; k++) {
    cs[k][0] = cs[k][1] = cs[k][2] = cs[k][3] = 0.f;
    mma_bf16x(cs[k], x[4 * k + 0], x[4 * k + 2], x[4 * k + 1], x[4 * k + 3], 0x3F803F80u, 0x3F803F80u);
  }
  const float mean = ((((cs[0][0] + cs[0][2]) + (cs[1][0] + cs[1][2])) + ((cs[2][0] + cs[2][2]) + (cs[3][0] + cs[3][2]))) + (cs[4][0] + cs[4][2])) * (1.f / 160.f);
  float m2a = 0.f, m2b = 0.f, m2c = 0.f, m2d = 0.f;
#pragma unroll
  for (int i = 0; i < 20; i += 2) {
    const float a = lo_f(x[i]) - mean, b = hi_f(x[i]) - mean, c = lo_f(x[i + 1]) - mean, d = hi_f(x[i + 1]) - mean;
    m2a = fmaf(a, a, m2a); m2b = fmaf(b, b, m2b); m2c = fmaf(c, c, m2c); m2d = fmaf(d, d, m2d);
  }
  float m2 = (m2a + m2b) + (m2c + m2d);
  m2 += __shfl_xor_sync(0xffffffffu, m2, 1);
  m2 += __shfl_xor_sync(0xffffffffu, m2, 2);
  return make_float2(mean, m2);
}
__device__ __forceinline__ void row_normalize(const float4* st, const uint32_t (&x)[20], uint32_t (&y)[20]) {
  const float4 p = st[0], q = st[1];
  const float mean = ((p.x + p.z) + (q.x + q.z)) * 0.25f;
  const float d0 = p.x - mean, d1 = p.z - mean, d2 = q.x - mean, d3 = q.z - mean;
  const float m2 = ((p.y + p.w) + (q.y + q.w)) + 160.f * ((d0 * d0 + d1 * d1) + (d2 * d2 + d3 * d3));
  const float hd = rbf(sqrtf(rbf(rbf(m2 * (1.f / D_)) + 1e-5f)));
  const float hr = __frcp_rn(hd);
  const bf162 hm2 = __float2bfloat162_rn(mean);
#pragma unroll
  for (int i = 0; i < 20; i++) {
    const uint32_t d = b2u(__hsub2_rn(u2b(x[i]), hm2));
    y[i] = LN2_EXACT ? pack2(fdivr(lo_f(d), hd, hr), fdivr(hi_f(d), hd, hr)) : pack2(lo_f(d) * hr, hi_f(d) * hr);
  }
}

__device__ __forceinline__ void gather_kv(Smem& sm, int c0, int tid) {
  mbar_wait(&sm.mbarc);
  uint4 v[4];
  uint4* src = g_kv + c0 * 256 + tid;
#pragma unroll
  for (int i = 0; i < 4; i++) if (i < 3 || tid >= 256) v[i] = ld_poll4(src + NTHR * i - (i == 3 ? 256 : 0));
#pragma unroll
  for (int i = 0; i < 4; i++) {
    if (i < 3 || tid >= 256) {
      const int t = tid + NTHR * i - (i == 3 ? 256 : 0);
      int it = 0;
      while (!ready4(v[i]) && ++it < SPIN_LIMIT) { __nanosleep(POLL_NS); v[i] = ld_poll4(g_kv + c0 * 256 + t); }
      *reinterpret_cast<uint4*>(&sm.u[t >> 8][UPAD + (t & 255) * 8]) = make_uint4(~v[i].x, ~v[i].y, ~v[i].z, ~v[i].w);
    }
  }
  asm volatile("fence.proxy.async.shared::cta;" ::: "memory");
  __syncthreads();
}

__global__ void __launch_bounds__(NTHR, 1)
fused_kernel(const __grid_constant__ CUtensorMap tmg, const __grid_constant__ CUtensorMap tmu,
             const __grid_constant__ CUtensorMap tmd, const bf16* __restrict__ gq, const bf16* __restrict__ gk, const bf16* __restrict__ gv,
             const bf16* __restrict__ gsk, const bf16* __restrict__ gh, const bf16* __restrict__ gD,
             const bf16* __restrict__ gwr, bf16* __restrict__ gout) {
  extern __shared__ __align__(128) unsigned char smraw[];
  Smem& sm = *reinterpret_cast<Smem*>(smraw);
  const int tid = threadIdx.x;
  const int cta = blockIdx.x;
  const int c0 = cta * CPC;
  const int lane = tid & 31;
  const int wid = tid >> 5;
  STAMP(0);
  const long long tstart = clock64();

  {
    uint4* hs = reinterpret_cast<uint4*>(&sm.z[0][0][0]);
    const int oc = tid >> 2;
    const int r0 = cta * 16 + (tid & 3) * 4;
    uint4 kk[7], vv[4], sk[4];
    if (tid < 320) {
      const uint4* kp = reinterpret_cast<const uint4*>(gk) + (size_t)r0 * 80 + oc;
      const uint4* vp = reinterpret_cast<const uint4*>(gv) + (size_t)r0 * 80 + oc;
#pragma unroll
      for (int i = 0; i < 7; i++) kk[i] = (i >= 3 || r0 > 0) ? __ldg(kp + (i - 3) * 80) : make_uint4(0, 0, 0, 0);
#pragma unroll
      for (int i = 0; i < 4; i++) vv[i] = __ldg(vp + i * 80);
#pragma unroll
      for (int i = 0; i < 4; i++) sk[i] = __ldg(reinterpret_cast<const uint4*>(gsk) + oc * 4 + i);
    } else if (tid == 320) {
      asm volatile("mbarrier.init.shared.b64 [%0], 1;" ::"r"(smem_u32(&sm.mbarh)) : "memory");
      asm volatile("mbarrier.init.shared.b64 [%0], 1;" ::"r"(smem_u32(&sm.mbar)) : "memory");
      asm volatile("mbarrier.init.shared.b64 [%0], 1;" ::"r"(smem_u32(&sm.mbarw)) : "memory");
      asm volatile("mbarrier.init.shared.b64 [%0], 1;" ::"r"(smem_u32(&sm.mbarc)) : "memory");
      asm volatile("mbarrier.init.shared.b64 [%0], 1;" ::"r"(smem_u32(&sm.mbary)) : "memory");
      asm volatile("fence.proxy.async.shared::cta;" ::: "memory");
    } else if (tid == 352) {
      uint32_t v2, v3;
      asm volatile("ld.relaxed.gpu.global.u32 %0, [%1];" : "=r"(v2) : "l"(&g_ctr2) : "memory");
      asm volatile("ld.relaxed.gpu.global.u32 %0, [%1];" : "=r"(v3) : "l"(&g_ctr3) : "memory");
      sm.target2 = (v2 / NCTA + 1u) * NCTA;
      sm.target3 = (v3 / NCTA + 1u) * NCTA;
    }
    if (tid < 320) bar_sync(6, 384); else { bar_arrive(6, 384); bar_sync(5, 64); }
    STAMP(9);
    if (tid < 320) {
      uint32_t o[4][4];
#pragma unroll
      for (int p = 0; p < 4; p++) {
        const bf162 w0 = u2b(__byte_perm(sk[p].x, sk[p].z, 0x5410)), w1 = u2b(__byte_perm(sk[p].x, sk[p].z, 0x7632));
        const bf162 w2 = u2b(__byte_perm(sk[p].y, sk[p].w, 0x5410)), w3 = u2b(__byte_perm(sk[p].y, sk[p].w, 0x7632));
        uint32_t kv[4];
#pragma unroll
        for (int i = 0; i < 4; i++) {
          const uint32_t k0 = p == 0 ? kk[i].x : p == 1 ? kk[i].y : p == 2 ? kk[i].z : kk[i].w;
          const uint32_t k1 = p == 0 ? kk[i + 1].x : p == 1 ? kk[i + 1].y : p == 2 ? kk[i + 1].z : kk[i + 1].w;
          const uint32_t k2 = p == 0 ? kk[i + 2].x : p == 1 ? kk[i + 2].y : p == 2 ? kk[i + 2].z : kk[i + 2].w;
          const uint32_t k3 = p == 0 ? kk[i + 3].x : p == 1 ? kk[i + 3].y : p == 2 ? kk[i + 3].z : kk[i + 3].w;
          const uint32_t vx = p == 0 ? vv[i].x : p == 1 ? vv[i].y : p == 2 ? vv[i].z : vv[i].w;
          bf162 a = __hmul2_rn(u2b(k0), w3);
          a = __hadd2_rn(a, __hmul2_rn(u2b(k1), w2));
          a = __hadd2_rn(a, __hmul2_rn(u2b(k2), w1));
          a = __hadd2_rn(a, __hmul2_rn(u2b(k3), w0));
          kv[i] = b2u(__hmul2_rn(a, u2b(vx)));
        }
        o[p][0] = enc(__byte_perm(kv[0], kv[1], 0x5410)); o[p][1] = enc(__byte_perm(kv[2], kv[3], 0x5410));
        o[p][2] = enc(__byte_perm(kv[0], kv[1], 0x7632)); o[p][3] = enc(__byte_perm(kv[2], kv[3], 0x7632));
      }
      uint2* dst = reinterpret_cast<uint2*>(g_kv) + (size_t)(oc * 8) * 512 + (r0 >> 2);
#pragma unroll
      for (int p = 0; p < 4; p++) {
        st_pub2(dst + (2 * p) * 512, o[p][0], o[p][1]);
        st_pub2(dst + (2 * p + 1) * 512, o[p][2], o[p][3]);
      }
      STAMP(10);
      if (wid == 0) bar_sync(4, 320); else bar_arrive(4, 320);
      if (tid == 0) {
        asm volatile("red.relaxed.gpu.global.add.u32 [%0], 1;" ::"l"(&g_ctr2) : "memory");
      }
      __syncwarp();
    } else {
      const int t0 = tid - 320;
      const uint4 zz = make_uint4(0, 0, 0, 0);
      if (tid == 320) {
        while (clock64() - tstart < H_DELAY) {}
        mbar_expect(&sm.mbarh, CPC * S_ * 2);
        bulk_g2s(hs, gh + (size_t)c0 * S_, CPC * S_ * 2, &sm.mbarh);
      }
      __syncwarp();
      for (int t = t0; t < CPC * 17; t += 64) *reinterpret_cast<uint4*>(&sm.u[t / 17][(t % 17) * 8]) = zz;
      if (t0 < 40) *reinterpret_cast<uint4*>(&sm.tabA[0][0][0] + tab_off(t0 >> 3) + ((t0 >> 2) & 1) * TABW + 1024 + 4 * (t0 & 3)) = zz;
      while (clock64() - tstart < C_DELAY) {}
      (&g_cand[cta][0][0])[t0] = zz;
      (&g_cand[cta][0][0])[64 + t0] = zz;
      if (t0 < 32) (&g_cand[cta][0][0])[128 + t0] = zz;
      else reinterpret_cast<uint4*>(&g_keys[cta][0])[t0 - 32] = zz;
      if (cta >= N1 && cta < N1 + N2) {
#pragma unroll
        for (int i = 0; i < 3; i++) g_act[cta - N1][t0 + 64 * i] = zz;
      }
      bar_sync(5, 64);
      if (tid == 352) {
        __threadfence();
        const unsigned old = atomicAdd(&g_ctr, 1u);
        sm.target = (old / NCTA + 1u) * NCTA;
      }
      __syncwarp();
    }
    mbar_wait(&sm.mbarh);
#pragma unroll
    for (int i = 0; i < 4; i++) {
      const int t = (NTHR - 1 - tid) + NTHR * i;
      if (t < CPC * 256) {
        uint32_t* tb = &sm.tabA[0][0][0] + tab_off(t >> 8) + (255 - (t & 255)) * 4;
        const uint4 h = hs[t];
        const uint32_t hp = (t & 255) ? reinterpret_cast<const uint32_t*>(hs)[4 * t - 1] : 0u;
        uint4 r1, rr;
        r1.x = __byte_perm(h.w, 0, 0x1032); r1.y = __byte_perm(h.z, 0, 0x1032);
        r1.z = __byte_perm(h.y, 0, 0x1032); r1.w = __byte_perm(h.x, 0, 0x1032);
        rr.x = __byte_perm(h.w, h.z, 0x7610); rr.y = __byte_perm(h.z, h.y, 0x7610);
        rr.z = __byte_perm(h.y, h.x, 0x7610); rr.w = __byte_perm(h.x, hp, 0x7610);
        *reinterpret_cast<uint4*>(tb) = rr;
        *reinterpret_cast<uint4*>(tb + TABW) = r1;
      }
    }
    STAMP(12);
  }
  __syncthreads();

  const int wg = __shfl_sync(0xffffffffu, tid >> 7, 0);
  const int wtid = tid & 127;
  uint4* tile = reinterpret_cast<uint4*>(&sm.tabB[0][0][0]);
  if (wg < 2) {
    asm volatile("setmaxnreg.inc.sync.aligned.u32 224;");
    const int w = (tid >> 5) & 3, g = lane >> 2, tq = lane & 3;
    float* zw = sm.z[wg][w];
    const int sw = 3 * (((tq + w) >> 1) & 1);
    const int off_even = 16 * (tq + w) + 4 * ((0 + (g >> 2)) ^ sw) + (g & 3);
    const int off_odd = 16 * (tq + w) + 4 * ((2 + (g >> 2)) ^ sw) + (g & 3);
    uint32_t a[8][8];
    const uint32_t* tp0 = &sm.tabA[0][g & 1][1019 - 8 * w - (g >> 1) + tq];
    load_a_all(a, tp0 + tab_off(wg));
    float acc[8][16];
#pragma unroll
    for (int b = 0; b < 8; b++)
#pragma unroll
      for (int i = 0; i < 16; i++) acc[b][i] = 0.f;
    gather_kv(sm, c0, tid);
    STAMP(1);
#pragma unroll 1
    for (int c = wg; c < CPC; c += 2) {
      const uint64_t desc = (uint64_t)((smem_u32(&sm.u[c][UPAD - 8]) & 0x3FFFF) >> 4) | ((uint64_t)1 << 16) | ((uint64_t)8 << 32);
      CST(c, 0);
      if (c > 0) bar_sync(1 + wg, 256);
      issue_g<0>(acc, a[0], desc);
      CST(c, 1);
      issue_g<1>(acc, a[1], desc);
      issue_g<2>(acc, a[2], desc);
      issue_g<3>(acc, a[3], desc);
      issue_g<4>(acc, a[4], desc);
      issue_g<5>(acc, a[5], desc);
      if (c + 1 < CPC) bar_arrive(1 + (wg ^ 1), 256);
      issue_g<6>(acc, a[6], desc);
      issue_g<7>(acc, a[7], desc);
      CST(c, 2);
      if (c >= 2) bar_sync(5 + wg, 256);
      wg_wait<4>();
      fence_blk<0>(acc); fence_blk<1>(acc); fence_blk<2>(acc); fence_blk<3>(acc);
      sts_blk<0>(acc, zw, off_even, off_odd);
      sts_blk<1>(acc, zw, off_even, off_odd);
      sts_blk<2>(acc, zw, off_even, off_odd);
      sts_blk<3>(acc, zw, off_even, off_odd);
      bar_arrive(9 + wg, 256);
      CST(c, 3);
      wg_wait<0>();
      fence_blk<4>(acc); fence_blk<5>(acc); fence_blk<6>(acc); fence_blk<7>(acc);
#pragma unroll
      for (int i = 0; i < 8; i++) fence_a(a[i]);
      sts_blk<4>(acc, zw, off_even, off_odd);
      sts_blk<5>(acc, zw, off_even, off_odd);
      sts_blk<6>(acc, zw, off_even, off_odd);
      sts_blk<7>(acc, zw, off_even, off_odd);
      bar_arrive(3 + wg, 256);
      CST(c, 4);
      if (c + 2 < CPC) load_a_all(a, tp0 + tab_off(c + 2));
    }
    STAMP(2 + wg);
    asm volatile("setmaxnreg.dec.sync.aligned.u32 168;");
  } else {
    asm volatile("setmaxnreg.dec.sync.aligned.u32 56;");
    if (((wtid & 15) >> 2) < ((wtid >> 4) & 3))
      *reinterpret_cast<uint4*>(&sm.z[wtid >> 6][(wtid >> 4) & 3][(wtid & 15) * 4]) = make_uint4(0, 0, 0, 0);
    if (wtid == 64) {
      const unsigned target = sm.target2;
      uint32_t v;
      int it = 0;
      do {
        asm volatile("ld.relaxed.gpu.global.u32 %0, [%1];" : "=r"(v) : "l"(&g_ctr2) : "memory");
      } while ((int)(v - target) < 0 && ++it < SPIN_LIMIT);
      asm volatile("mbarrier.arrive.shared.b64 _, [%0];" ::"r"(smem_u32(&sm.mbarc)) : "memory");
    }
    __syncwarp();
    gather_kv(sm, c0, tid);
#pragma unroll
    for (int i = 0; i < 10; i++) g_kv[c0 * 256 + wtid + 128 * i] = make_uint4(0, 0, 0, 0);
    if (wtid == 96) wait_ctr(&g_ctr, sm.target);
    __syncwarp();
    if (wtid == 32) {
      const uint32_t mw = smem_u32(&sm.mbarw);
      mbar_expect(&sm.mbar, 17 * D_ * 2);
#pragma unroll 1
      for (int r = 0; r < 16; r++) bulk_g2s(&sm.q[r][0], gq + (size_t)(cta * 16 + r) * D_, D_ * 2, &sm.mbar);
      bulk_g2s(&sm.wr[0], gwr, D_ * 2, &sm.mbar);
      if (cta < N1) {
        asm volatile("mbarrier.arrive.expect_tx.shared.b64 _, [%0], %1;" ::"r"(mw), "r"(3840 * 16) : "memory");
#pragma unroll 1
        for (int i = 0; i < 4; i++) {
          asm volatile("cp.async.bulk.tensor.2d.shared::cluster.global.mbarrier::complete_tx::bytes [%0], [%1, {%3, %4}], [%2];" ::"r"(smem_u32(&sm.w[i * 480])),
                       "l"(&tmg), "r"(mw), "r"(cta * 24), "r"(i * 160) : "memory");
          asm volatile("cp.async.bulk.tensor.2d.shared::cluster.global.mbarrier::complete_tx::bytes [%0], [%1, {%3, %4}], [%2];" ::"r"(smem_u32(&sm.w[1920 + i * 480])),
                       "l"(&tmu), "r"(mw), "r"(cta * 24), "r"(i * 160) : "memory");
        }
      } else if (cta < N1 + N2) {
        asm volatile("mbarrier.arrive.expect_tx.shared.b64 _, [%0], %1;" ::"r"(mw), "r"(3072 * 16) : "memory");
#pragma unroll 1
        for (int i = 0; i < 6; i++)
          asm volatile("cp.async.bulk.tensor.2d.shared::cluster.global.mbarrier::complete_tx::bytes [%0], [%1, {%3, %4}], [%2];" ::"r"(smem_u32(&sm.w[i * 512])),
                       "l"(&tmd), "r"(mw), "r"((cta - N1) * 16), "r"(i * 256) : "memory");
      }
    }
    const int rpb = wtid >> 1, re2 = wtid & 1;
    const int rsw = 3 * ((rpb >> 1) & 1);
    const int roff0 = 16 * rpb + 4 * ((2 * re2 + 0) ^ rsw);
    const int roff1 = 16 * rpb + 4 * ((2 * re2 + 1) ^ rsw);
    const uint32_t dvl = reinterpret_cast<const unsigned short*>(gD)[c0 + (lane < CPC ? lane : 0)];
#pragma unroll 1
    for (int c = 0; c < CPC; c++) {
      const int zg = c & 1;
      const uint32_t dvc = __shfl_sync(0xffffffffu, dvl, c);
      const bf162 d2 = u2b(dvc | (dvc << 16));
      CST(c, 5);
#pragma unroll
      for (int half = 0; half < 2; half++) {
        bar_sync((half ? 3 : 9) + zg, 256);
        const float* zb = sm.z[zg][0] + half * 1024;
        float4 x[4][2];
#pragma unroll
        for (int ww = 0; ww < 4; ww++) {
          x[ww][0] = *reinterpret_cast<const float4*>(zb + ww * ZPB * 16 + roff0);
          x[ww][1] = *reinterpret_cast<const float4*>(zb + ww * ZPB * 16 + roff1);
        }
        const int sidx = half * 1024 + wtid * 8;
        const uint4 kvv = *reinterpret_cast<const uint4*>(&sm.u[c][UPAD + sidx]);
        if (half == 1 && c + 2 < CPC) bar_arrive(5 + zg, 256);
        uint4 o;
        o.x = pack2((x[0][0].x + x[1][0].x) + (x[2][0].x + x[3][0].x), (x[0][0].y + x[1][0].y) + (x[2][0].y + x[3][0].y));
        o.y = pack2((x[0][0].z + x[1][0].z) + (x[2][0].z + x[3][0].z), (x[0][0].w + x[1][0].w) + (x[2][0].w + x[3][0].w));
        o.z = pack2((x[0][1].x + x[1][1].x) + (x[2][1].x + x[3][1].x), (x[0][1].y + x[1][1].y) + (x[2][1].y + x[3][1].y));
        o.w = pack2((x[0][1].z + x[1][1].z) + (x[2][1].z + x[3][1].z), (x[0][1].w + x[1][1].w) + (x[2][1].w + x[3][1].w));
        o.x = b2u(__hadd2_rn(u2b(o.x), __hmul2_rn(u2b(kvv.x), d2)));
        o.y = b2u(__hadd2_rn(u2b(o.y), __hmul2_rn(u2b(kvv.y), d2)));
        o.z = b2u(__hadd2_rn(u2b(o.z), __hmul2_rn(u2b(kvv.z), d2)));
        o.w = b2u(__hadd2_rn(u2b(o.w), __hmul2_rn(u2b(kvv.w), d2)));
        st_pub4(g_y2 + ((64 * half + rpb) * 640 + c0 + c) * 2 + re2, enc4(o));
        CST(c, 6 + half);
      }
    }
    if (wid == 11) bar_sync(8, 128); else bar_arrive(8, 128);
    STAMP(4);
    asm volatile("setmaxnreg.inc.sync.aligned.u32 168;");
  }

  if (tid == 352) {
    asm volatile("red.relaxed.gpu.global.add.u32 [%0], 1;" ::"l"(&g_ctr3) : "memory");
    wait_ctr(&g_ctr3, sm.target3);
    asm volatile("mbarrier.arrive.shared.b64 _, [%0];" ::"r"(smem_u32(&sm.mbary)) : "memory");
  }
  __syncwarp();
  if (ABL == 4) { mbar_wait(&sm.mbary); for (int i = tid; i < 1280; i += NTHR) g_y2[cta * 1280 + i] = make_uint4(0, 0, 0, 0); if (cta < N1 + N2) mbar_wait(&sm.mbarw); mbar_wait(&sm.mbar); return; }
  RT(0);
  const int g = lane >> 2, tq = lane & 3;
  const int hh = wid & 1, gqi = wid >> 1;
  const int row = hh * 8 + g;
  uint32_t hreg[20], hnreg[20];
  {
    const uint4* src = g_y2 + cta * 1280 + tid;
    uint4 v[4];
    if (wid < 8) {
      mbar_wait(&sm.mbar);
#pragma unroll
      for (int k = 0; k < 5; k++) {
        const uint4 qv4 = *reinterpret_cast<const uint4*>(&sm.q[row][32 * (5 * gqi + k) + 8 * tq]);
        hreg[4 * k] = qv4.x; hreg[4 * k + 1] = qv4.y; hreg[4 * k + 2] = qv4.z; hreg[4 * k + 3] = qv4.w;
      }
      const float2 ps = row_part_stats(hreg);
      if (tq == 0) sm.stq[row][gqi] = ps;
      bar_sync(7, 256);
      row_normalize(reinterpret_cast<const float4*>(sm.stq[row]), hreg, hnreg);
    }
    RT(1);
    mbar_wait(&sm.mbary);
    RT(2);
#pragma unroll
    for (int i = 0; i < 4; i++) if (i < 3 || tid < 128) v[i] = ld_poll4(src + NTHR * i);
    int it = 0;
    bool all;
    do {
      all = true;
#pragma unroll
      for (int i = 0; i < 4; i++)
        if ((i < 3 || tid < 128) && !ready4(v[i])) { v[i] = ld_poll4(src + NTHR * i); all = false; }
    } while (!all && ++it < SPIN_LIMIT);
#pragma unroll
    for (int i = 0; i < 4; i++) {
      if (i < 3 || tid < 128) {
        const int t = tid + NTHR * i;
        tile[(t & 1) * 640 + tile_perm(t >> 1)] = make_uint4(~v[i].x, ~v[i].y, ~v[i].z, ~v[i].w);
      }
    }
  }
  __syncthreads();
  STAMP(5);
  RT(3);
  if (ABL == 3) { for (int i = tid; i < 1280; i += NTHR) g_y2[cta * 1280 + i] = make_uint4(0, 0, 0, 0); if (cta < N1 + N2) mbar_wait(&sm.mbarw); return; }

  if (wid < 8) {
#pragma unroll
    for (int k = 0; k < 5; k++) {
      const int base = 32 * (5 * gqi + k);
      const int lch = base + 8 * ((lane & 7) >> 1) + 2 * (lane >> 3) + (lane & 1);
      uint32_t y[4];
      asm volatile("ldmatrix.sync.aligned.m8n8.x4.trans.shared.b16 {%0,%1,%2,%3}, [%4];"
                   : "=r"(y[0]), "=r"(y[1]), "=r"(y[2]), "=r"(y[3]) : "r"(smem_u32(&tile[hh * 640 + tile_perm(lch)])) : "memory");
#pragma unroll
      for (int i = 0; i < 4; i++)
        hreg[4 * k + i] = b2u(__hadd2_rn(u2b(hreg[4 * k + i]), __hmul2_rn(u2b(hnreg[4 * k + i]), u2b(y[i]))));
    }
    RT(4);
    const float2 ps = row_part_stats(hreg);
    if (tq == 0) sm.st[row][gqi] = ps;
    STAMP(13);
    RT(5);
    bar_sync(7, 256);
    row_normalize(reinterpret_cast<const float4*>(sm.st[row]), hreg, hnreg);
    RT(6);
    float cr[5][4];
#pragma unroll
    for (int k = 0; k < 5; k++) {
      cr[k][0] = cr[k][1] = cr[k][2] = cr[k][3] = 0.f;
      const uint4 w4 = sm.wr[4 * (5 * gqi + k) + tq];
      mma_bf16(cr[k], hnreg[4 * k + 0], hnreg[4 * k + 1], w4.x, w4.y);
      mma_bf16(cr[k], hnreg[4 * k + 2], hnreg[4 * k + 3], w4.z, w4.w);
    }
    if (tq == 0) sm.rp[row][gqi] = ((cr[0][0] + cr[1][0]) + (cr[2][0] + cr[3][0])) + cr[4][0];
  }
  STAMP(14);
  RT(7);
  __syncthreads();
  uint32_t best;
  {
    const int rr = lane & 15;
    const float4 rp4 = *reinterpret_cast<const float4*>(sm.rp[rr]);
    const float r = (rp4.x + rp4.y) + (rp4.z + rp4.w);
    const uint32_t bits = __bfloat16_as_ushort(__float2bfloat16_rn(r));
    const uint32_t ord = (bits & 0x8000u) ? (bits ^ 0xFFFFu) : (bits ^ 0x8000u);
    const uint32_t key = (ord << 16) | 0x8000u | (uint32_t)(2047 - (cta * 16 + rr));
    best = __reduce_max_sync(0xffffffffu, key);
  }
  if (wid >= 8) asm volatile("st.relaxed.gpu.global.u32 [%0], %1;" ::"l"(&g_keys[tid - 256][cta]), "r"(best) : "memory");
  STAMP(15);
  RT(8);
  const int brow = (2047 - (int)(best & 0x7FFu)) - cta * 16;
  if (wid < 8 && row == brow) {
#pragma unroll
    for (int k = 0; k < 5; k++)
      st_pub4(&g_cand[cta][0][4 * (5 * gqi + k) + tq], enc4(make_uint4(hnreg[4 * k], hnreg[4 * k + 1], hnreg[4 * k + 2], hnreg[4 * k + 3])));
#pragma unroll
    for (int k = 0; k < 5; k++)
      st_pub4(&g_cand[cta][1][4 * (5 * gqi + k) + tq], enc4(make_uint4(hreg[4 * k], hreg[4 * k + 1], hreg[4 * k + 2], hreg[4 * k + 3])));
  }
#pragma unroll
  for (int i = 0; i < 20; i++) hreg[i] = b2u(__hadd2_rn(u2b(hreg[i]), u2b(hnreg[i])));
  STAMP(6);
  RT(9);
  if (ABL == 2) { for (int i = tid; i < 1280; i += NTHR) g_y2[cta * 1280 + i] = make_uint4(0, 0, 0, 0); if (cta < N1 + N2) mbar_wait(&sm.mbarw); return; }
  if (wid == 11) {
    const uint4* kp = reinterpret_cast<const uint4*>(&g_keys[cta][0]) + lane;
    uint4 v = ld_poll4(kp);
    int it = 0;
    while (!ready4(v) && ++it < SPIN_LIMIT) v = ld_poll4(kp);
    const uint32_t m = max(max(v.x, v.y), max(v.z, v.w));
    const uint32_t wk = __reduce_max_sync(0xffffffffu, m);
    if (lane == 0) sm.win = wk;
  }
  __syncthreads();
  const uint32_t win = sm.win;
  const int wrow = 2047 - (int)(win & 0x7FFu);
  const int wcta = wrow >> 4;
  const bool st_out = wid < 8 && (cta * 16 + row) != wrow;
  uint4* outp = reinterpret_cast<uint4*>(gout + (size_t)(cta * 16 + row) * D_) + 20 * gqi + tq;
  if (cta >= N1) {
    if (st_out) {
#pragma unroll
      for (int k = 0; k < 5; k++) outp[4 * k] = make_uint4(hreg[4 * k], hreg[4 * k + 1], hreg[4 * k + 2], hreg[4 * k + 3]);
    }
  }
  if (cta >= N1 || ABL == 1) {
#pragma unroll
    for (int i = 0; i < 4; i++) if (i < 3 || tid < 128) g_y2[cta * 1280 + tid + NTHR * i] = make_uint4(0, 0, 0, 0);
  }
  STAMP(7);
  RT(10);
  if (ABL == 1) { if (cta < N1 + N2) mbar_wait(&sm.mbarw); return; }
  uint4* xs = reinterpret_cast<uint4*>(&sm.z[0][0][0]);
  const uint32_t* xw = reinterpret_cast<const uint32_t*>(xs);
  float* part = reinterpret_cast<float*>(xs + 256);
  if (cta < N1) {
    if (tid < 80) xs[tid] = poll4(&g_cand[wcta][0][tid]);
    RT(12);
    mbar_wait(&sm.mbarw);
    __syncthreads();
    RT(13);
    const int m = wid / 6, nt = (wid % 6) >> 1, kh = wid & 1;
    float ca[4][4];
#pragma unroll
    for (int i = 0; i < 4; i++) ca[i][0] = ca[i][1] = ca[i][2] = ca[i][3] = 0.f;
    const uint32_t wbase = smem_u32(&sm.w[m * 1920 + (kh * 320 + lane) * 3 + nt]);
#pragma unroll
    for (int it = 0; it < 10; it++) {
      uint32_t b[4];
      asm volatile("ldmatrix.sync.aligned.m8n8.x4.trans.shared.b16 {%0,%1,%2,%3}, [%4];"
                   : "=r"(b[0]), "=r"(b[1]), "=r"(b[2]), "=r"(b[3]) : "r"(wbase + it * 32 * 48) : "memory");
      const uint32_t* xp = xw + kh * 160 + it * 16 + tq;
      mma_bf16(ca[2 * (it & 1)], xp[0], xp[4], b[0], b[1]);
      mma_bf16(ca[2 * (it & 1) + 1], xp[8], xp[12], b[2], b[3]);
    }
    if (g == 0)
      *reinterpret_cast<float2*>(part + wid * 8 + 2 * tq) =
          make_float2((ca[0][0] + ca[1][0]) + (ca[2][0] + ca[3][0]), (ca[0][1] + ca[1][1]) + (ca[2][1] + ca[3][1]));
    __syncthreads();
    {
      const int l24 = lane < 24 ? lane : 0;
      const int o = (l24 >> 3) * 16 + (l24 & 7);
      const float gt = rbf(part[o] + part[o + 8]);
      const float up = rbf(part[48 + o] + part[56 + o]);
      const float sg = rbf(__fdividef(gt, 1.f + __expf(-gt)));
      const uint32_t bits = __bfloat16_as_ushort(__float2bfloat16_rn(sg * up));
      const uint32_t nb = __shfl_down_sync(0xffffffffu, bits, 1);
      const uint32_t pw = enc(bits | (nb << 16));
      const int t = wid * 10 + (lane < 10 ? lane : 0);
      const int cons = t / 3, ck = t - 3 * cons;
      uint4 v;
      v.x = __shfl_sync(0xffffffffu, pw, 8 * ck); v.y = __shfl_sync(0xffffffffu, pw, 8 * ck + 2);
      v.z = __shfl_sync(0xffffffffu, pw, 8 * ck + 4); v.w = __shfl_sync(0xffffffffu, pw, 8 * ck + 6);
      if (lane < 10) st_pub4(&g_act[cons][cta * 3 + ck], v);
      RT(14);
    }
#pragma unroll
    for (int i = 0; i < 4; i++) if (i < 3 || tid < 128) g_y2[cta * 1280 + tid + NTHR * i] = make_uint4(0, 0, 0, 0);
    if (st_out) {
#pragma unroll
      for (int k = 0; k < 5; k++) outp[4 * k] = make_uint4(hreg[4 * k], hreg[4 * k + 1], hreg[4 * k + 2], hreg[4 * k + 3]);
    }
  } else if (cta < N1 + N2 && ABL != 6) {
    const int j2 = cta - N1;
    if (tid < 192) xs[tid] = poll4(&g_act[j2][tid]);
    else if (tid < 196) {
      const int t = tid - 192;
      reinterpret_cast<uint4*>(part + 256)[t] = poll4(&g_cand[wcta][t >> 1][j2 * 2 + (t & 1)]);
    }
    RT(12);
    mbar_wait(&sm.mbarw);
    __syncthreads();
    RT(13);
    float ca[4][4];
#pragma unroll
    for (int i = 0; i < 4; i++) ca[i][0] = ca[i][1] = ca[i][2] = ca[i][3] = 0.f;
    const uint32_t wbase = smem_u32(&sm.w[(wid * 128 + (lane & 15)) * 2 + (lane >> 4)]);
#pragma unroll
    for (int it = 0; it < 8; it++) {
      uint32_t b[4];
      asm volatile("ldmatrix.sync.aligned.m8n8.x4.trans.shared.b16 {%0,%1,%2,%3}, [%4];"
                   : "=r"(b[0]), "=r"(b[1]), "=r"(b[2]), "=r"(b[3]) : "r"(wbase + it * 16 * 32) : "memory");
      const uint32_t* xp = xw + wid * 64 + it * 8 + tq;
      const uint32_t x0 = xp[0], x1 = xp[4];
      mma_bf16(ca[2 * (it & 1)], x0, x1, b[0], b[1]);
      mma_bf16(ca[2 * (it & 1) + 1], x0, x1, b[2], b[3]);
    }
    if (g == 0) {
      *reinterpret_cast<float2*>(part + wid * 16 + 2 * tq) = make_float2(ca[0][0] + ca[2][0], ca[0][1] + ca[2][1]);
      *reinterpret_cast<float2*>(part + wid * 16 + 8 + 2 * tq) = make_float2(ca[1][0] + ca[3][0], ca[1][1] + ca[3][1]);
    }
    const uint32_t ord = win >> 16;
    const uint32_t rb = (ord & 0x8000u) ? (ord ^ 0x8000u) : (ord ^ 0xFFFFu);
    const float sg = rbf(__fdividef(1.f, 1.f + __expf(-__uint_as_float(rb << 16))));
    __syncthreads();
    if (tid < 16) {
      float y0 = 0.f, y1 = 0.f, y2 = 0.f;
#pragma unroll
      for (int i = 0; i < 4; i++) { y0 += part[i * 16 + tid]; y1 += part[(4 + i) * 16 + tid]; y2 += part[(8 + i) * 16 + tid]; }
      const float y = (y0 + y1) + y2;
      const float yy = rbf(rbf(y) * sg);
      const unsigned short* rv = reinterpret_cast<const unsigned short*>(part + 256);
      const float hn = __uint_as_float((uint32_t)rv[tid] << 16), h = __uint_as_float((uint32_t)rv[16 + tid] << 16);
      gout[(size_t)wrow * D_ + j2 * 16 + tid] = __float2bfloat16_rn(h + rbf(hn + yy));
    }
  }
  STAMP(8);
  RT(11);
}

}

typedef CUresult (*EncodeFn)(CUtensorMap*, CUtensorMapDataType, cuuint32_t, void*, const cuuint64_t*, const cuuint64_t*,
                             const cuuint32_t*, const cuuint32_t*, CUtensorMapInterleave, CUtensorMapSwizzle,
                             CUtensorMapL2promotion, CUtensorMapFloatOOBfill);

extern "C" void kernel_launch(void* const* d_in, const int* in_sizes, int n_in, void* d_out, int out_size) {
  (void)in_sizes; (void)n_in; (void)out_size;
  static EncodeFn encode = nullptr;
  static CUtensorMap tmg, tmu, tmd;
  static void* cached[3] = {nullptr, nullptr, nullptr};
  if (!encode) {
    cudaFuncSetAttribute(fused_kernel, cudaFuncAttributeMaxDynamicSharedMemorySize, (int)sizeof(Smem));
    void* fn = nullptr;
    cudaDriverEntryPointQueryResult qr;
    cudaGetDriverEntryPoint("cuTensorMapEncodeTiled", &fn, cudaEnableDefault, &qr);
    encode = (EncodeFn)fn;
  }
  if (cached[0] != d_in[8] || cached[1] != d_in[9] || cached[2] != d_in[10]) {
    const cuuint32_t es[2] = {1, 1};
    {
      const cuuint64_t dims[2] = {F_, D_}, strides[1] = {F_ * 2};
      const cuuint32_t box[2] = {24, 160};
      encode(&tmg, CU_TENSOR_MAP_DATA_TYPE_BFLOAT16, 2, d_in[8], dims, strides, box, es, CU_TENSOR_MAP_INTERLEAVE_NONE,
             CU_TENSOR_MAP_SWIZZLE_NONE, CU_TENSOR_MAP_L2_PROMOTION_NONE, CU_TENSOR_MAP_FLOAT_OOB_FILL_NONE);
      encode(&tmu, CU_TENSOR_MAP_DATA_TYPE_BFLOAT16, 2, d_in[9], dims, strides, box, es, CU_TENSOR_MAP_INTERLEAVE_NONE,
             CU_TENSOR_MAP_SWIZZLE_NONE, CU_TENSOR_MAP_L2_PROMOTION_NONE, CU_TENSOR_MAP_FLOAT_OOB_FILL_NONE);
    }
    {
      const cuuint64_t dims[2] = {D_, F_}, strides[1] = {D_ * 2};
      const cuuint32_t box[2] = {16, 256};
      encode(&tmd, CU_TENSOR_MAP_DATA_TYPE_BFLOAT16, 2, d_in[10], dims, strides, box, es, CU_TENSOR_MAP_INTERLEAVE_NONE,
             CU_TENSOR_MAP_SWIZZLE_NONE, CU_TENSOR_MAP_L2_PROMOTION_NONE, CU_TENSOR_MAP_FLOAT_OOB_FILL_NONE);
    }
    cached[0] = d_in[8]; cached[1] = d_in[9]; cached[2] = d_in[10];
  }
  fused_kernel<<<NCTA, NTHR, sizeof(Smem), cudaStreamPerThread>>>(
      tmg, tmu, tmd, (const bf16*)d_in[0], (const bf16*)d_in[1], (const bf16*)d_in[2], (const bf16*)d_in[3],
      (const bf16*)d_in[4], (const bf16*)d_in[5], (const bf16*)d_in[7], (bf16*)d_out);
}
```

```cpp
#include <cuda_runtime.h>
#include <cuda_bf16.h>
#include <cuda.h>
#include <stdint.h>

namespace {

typedef __nv_bfloat16 bf16;
typedef __nv_bfloat162 bf162;

constexpr int S_ = 2048, D_ = 640, F_ = 1536;
constexpr int NCTA = 128, CPC = 5, NTHR = 384;
constexpr int UPAD = 136, USTR = 2192;
constexpr int TABW = 1040;
constexpr int ZPB = 132;
constexpr int QSTR = 648;
constexpr int N1 = 64;
constexpr int N2 = 40;
constexpr int SPIN_LIMIT = 1 << 19;
#define LN2_EXACT 1
#define ABL 0
#define CTR_NS 0
#define C_DELAY 0
#define TESTV 0
#define TESTC 0
#define POLL_NS 100
#define H_DELAY 0
#define Q_DELAY 4500

struct __align__(128) Smem {
  uint32_t tabA[3][2][TABW];
  uint32_t extra[1024];
  uint32_t tabB[2][2][TABW];
  bf16 u[CPC][USTR];
  float z[2][4][ZPB * 16];
  bf16 q[16][QSTR];
  alignas(128) uint4 w[3840];
  uint4 wr[80];
  alignas(16) float2 st[16][4];
  alignas(16) float2 stq[16][4];
  alignas(16) float rp[16][4];
  unsigned long long mbar;
  unsigned long long mbarw;
  unsigned long long mbarc;
  unsigned long long mbary;
  unsigned long long mbarh;
  uint32_t target;
  uint32_t target2;
  uint32_t target3;
  uint32_t best;
  uint32_t win;
};

__device__ uint4 g_kv[D_ * S_ / 8];
__device__ uint4 g_y2[D_ * S_ / 8];
__device__ uint32_t g_keys[NCTA][NCTA];
__device__ uint4 g_cand[NCTA][2][80];
__device__ uint4 g_act[N2][F_ / 8];
__device__ unsigned int g_ctr;
__device__ unsigned int g_ctr2;
__device__ unsigned int g_ctr3;
#define STAMP(i)
#define RT(i)
#define CST(c, i)

__device__ __forceinline__ uint32_t smem_u32(const void* p) { return (uint32_t)__cvta_generic_to_shared(p); }
__device__ __forceinline__ void wg_fence() { asm volatile("wgmma.fence.sync.aligned;" ::: "memory"); }
__device__ __forceinline__ void wg_commit() { asm volatile("wgmma.commit_group.sync.aligned;" ::: "memory"); }
template <int N> __device__ __forceinline__ void wg_wait() { asm volatile("wgmma.wait_group.sync.aligned %0;" ::"n"(N) : "memory"); }
__device__ __forceinline__ void bar_sync(int id, int n) { asm volatile("bar.sync %0, %1;" ::"r"(id), "r"(n) : "memory"); }
__device__ __forceinline__ void bar_arrive(int id, int n) { asm volatile("bar.arrive %0, %1;" ::"r"(id), "r"(n) : "memory"); }
__device__ __forceinline__ bf162 u2b(uint32_t u) { return *reinterpret_cast<bf162*>(&u); }
__device__ __forceinline__ uint32_t b2u(bf162 b) { return *reinterpret_cast<uint32_t*>(&b); }
__device__ __forceinline__ float lo_f(uint32_t u) { return __uint_as_float(u << 16); }
__device__ __forceinline__ float hi_f(uint32_t u) { return __uint_as_float(u & 0xFFFF0000u); }
__device__ __forceinline__ float rbf(float x) { return __bfloat162float(__float2bfloat16_rn(x)); }
__device__ __forceinline__ uint32_t pack2(float a, float b) { return b2u(__floats2bfloat162_rn(a, b)); }
__device__ __forceinline__ uint32_t enc(uint32_t w) { return max(~w, 1u); }
__device__ __forceinline__ uint4 enc4(uint4 v) { return make_uint4(enc(v.x), enc(v.y), enc(v.z), enc(v.w)); }
__device__ __forceinline__ uint4 ld_poll4(const uint4* p) {
  uint4 v;
  asm volatile("ld.relaxed.gpu.global.v4.u32 {%0,%1,%2,%3}, [%4];" : "=r"(v.x), "=r"(v.y), "=r"(v.z), "=r"(v.w) : "l"(p) : "memory");
  return v;
}
__device__ __forceinline__ bool ready4(uint4 v) { return v.x != 0u && v.y != 0u && v.z != 0u && v.w != 0u; }
__device__ __forceinline__ uint4 poll4(const uint4* p) {
  uint4 v = ld_poll4(p);
  int it = 0;
  while (!ready4(v) && ++it < SPIN_LIMIT) v = ld_poll4(p);
  return make_uint4(~v.x, ~v.y, ~v.z, ~v.w);
}
__device__ __forceinline__ void st_pub4(uint4* p, uint4 v) {
  asm volatile("st.relaxed.gpu.global.v4.u32 [%0], {%1,%2,%3,%4};" ::"l"(p), "r"(v.x), "r"(v.y), "r"(v.z), "r"(v.w) : "memory");
}
__device__ __forceinline__ void st_pub2(uint2* p, uint32_t a, uint32_t b) {
  asm volatile("st.relaxed.gpu.global.v2.u32 [%0], {%1,%2};" ::"l"(p), "r"(a), "r"(b) : "memory");
}
__device__ __forceinline__ void mma_bf16(float (&c)[4], uint32_t a0, uint32_t a2, uint32_t b0, uint32_t b1) {
  asm volatile("mma.sync.aligned.m16n8k16.row.col.f32.bf16.bf16.f32 {%0,%1,%2,%3}, {%4,%5,%6,%5}, {%7,%8}, {%0,%1,%2,%3};"
               : "+f"(c[0]), "+f"(c[1]), "+f"(c[2]), "+f"(c[3]) : "r"(a0), "r"(0u), "r"(a2), "r"(b0), "r"(b1));
}
__device__ __forceinline__ void mbar_wait(const unsigned long long* bar) {
  const uint32_t mb = smem_u32(bar);
  uint32_t ok = 0;
  int it = 0;
  while (!ok && ++it < SPIN_LIMIT)
    asm volatile("{ .reg .pred p; mbarrier.try_wait.parity.shared.b64 p, [%1], 0; selp.u32 %0, 1, 0, p; }" : "=r"(ok) : "r"(mb) : "memory");
}
__device__ __forceinline__ void bulk_g2s(void* dst, const void* src, uint32_t bytes, const unsigned long long* bar) {
  asm volatile("cp.async.bulk.shared::cluster.global.mbarrier::complete_tx::bytes [%0], [%1], %2, [%3];" ::"r"(smem_u32(dst)),
               "l"(src), "r"(bytes), "r"(smem_u32(bar)) : "memory");
}
__device__ __forceinline__ void mbar_expect(const unsigned long long* bar, uint32_t bytes) {
  asm volatile("mbarrier.arrive.expect_tx.shared.b64 _, [%0], %1;" ::"r"(smem_u32(bar)), "r"(bytes) : "memory");
}
__device__ __forceinline__ void mma_bf16x(float (&c)[4], uint32_t a0, uint32_t a1, uint32_t a2, uint32_t a3, uint32_t b0, uint32_t b1) {
  asm volatile("mma.sync.aligned.m16n8k16.row.col.f32.bf16.bf16.f32 {%0,%1,%2,%3}, {%4,%5,%6,%7}, {%8,%9}, {%0,%1,%2,%3};"
               : "+f"(c[0]), "+f"(c[1]), "+f"(c[2]), "+f"(c[3]) : "r"(a0), "r"(a1), "r"(a2), "r"(a3), "r"(b0), "r"(b1));
}
__device__ __forceinline__ float fdivr(float a, float d, float r) {
  float q = a * r;
  float e = fmaf(-q, d, a);
  return fmaf(e, r, q);
}

template <bool FIRST> __device__ __forceinline__ void wgmma32(float (&d)[16], const uint32_t* a, uint64_t desc) {
  if (FIRST) {
    asm volatile("wgmma.mma_async.sync.aligned.m64n32k16.f32.bf16.bf16 {%0,%1,%2,%3,%4,%5,%6,%7,%8,%9,%10,%11,%12,%13,%14,%15}, {%16,%17,%18,%19}, %20, 0, 1, 1, 0;"
                 : "+f"(d[0]), "+f"(d[1]), "+f"(d[2]), "+f"(d[3]), "+f"(d[4]), "+f"(d[5]), "+f"(d[6]), "+f"(d[7]),
                   "+f"(d[8]), "+f"(d[9]), "+f"(d[10]), "+f"(d[11]), "+f"(d[12]), "+f"(d[13]), "+f"(d[14]), "+f"(d[15])
                 : "r"(a[0]), "r"(a[1]), "r"(a[2]), "r"(a[3]), "l"(desc));
  } else {
    asm volatile("wgmma.mma_async.sync.aligned.m64n32k16.f32.bf16.bf16 {%0,%1,%2,%3,%4,%5,%6,%7,%8,%9,%10,%11,%12,%13,%14,%15}, {%16,%17,%18,%19}, %20, 1, 1, 1, 0;"
                 : "+f"(d[0]), "+f"(d[1]), "+f"(d[2]), "+f"(d[3]), "+f"(d[4]), "+f"(d[5]), "+f"(d[6]), "+f"(d[7]),
                   "+f"(d[8]), "+f"(d[9]), "+f"(d[10]), "+f"(d[11]), "+f"(d[12]), "+f"(d[13]), "+f"(d[14]), "+f"(d[15])
                 : "r"(a[0]), "r"(a[1]), "r"(a[2]), "r"(a[3]), "l"(desc));
  }
}

template <int G> __device__ __forceinline__ void load_a(uint32_t (&a)[8], const uint32_t* tp) {
#pragma unroll
  for (int q = 0; q < 2; q++) {
    const int e = 2 * G + q;
    a[4 * q + 0] = tp[-64 * e];
    a[4 * q + 1] = tp[-64 * e - 32];
    a[4 * q + 2] = tp[-64 * e + 4];
    a[4 * q + 3] = tp[-64 * e - 28];
  }
}
__device__ __forceinline__ void load_a_all(uint32_t (&a)[8][8], const uint32_t* tp) {
  load_a<0>(a[0], tp); load_a<1>(a[1], tp); load_a<2>(a[2], tp); load_a<3>(a[3], tp);
  load_a<4>(a[4], tp); load_a<5>(a[5], tp); load_a<6>(a[6], tp); load_a<7>(a[7], tp);
}
template <int G> __device__ __forceinline__ void issue_g(float (&acc)[8][16], uint32_t (&a)[8], uint64_t desc0) {
  wg_fence();
#pragma unroll
  for (int q = 0; q < 2; q++) {
#pragma unroll
    for (int b = G; b < 8; b++) {
      const int delta = 2 * b - (2 * G + q);
      if (G == 0 && q == 0) wgmma32<true>(acc[b], &a[4 * q], desc0 + (uint64_t)(int64_t)(16 * delta));
      else wgmma32<false>(acc[b], &a[4 * q], desc0 + (uint64_t)(int64_t)(16 * delta));
    }
  }
  wg_commit();
}
template <int B> __device__ __forceinline__ void fence_blk(float (&acc)[8][16]) {
#pragma unroll
  for (int i = 0; i < 16; i++) asm volatile("" : "+f"(acc[B][i])::"memory");
}
__device__ __forceinline__ void fence_a(uint32_t (&a)[8]) {
#pragma unroll
  for (int i = 0; i < 8; i++) asm volatile("" : "+r"(a[i])::"memory");
}
template <int B> __device__ __forceinline__ void sts_blk(float (&acc)[8][16], float* zw, int off_even, int off_odd) {
#pragma unroll
  for (int jj = 0; jj < 4; jj++) {
    const int j = 4 * B + jj;
    float p0 = acc[B][4 * jj + 0], p1 = acc[B][4 * jj + 1];
    if (jj > 0) { p0 += acc[B][4 * (jj - 1) + 2]; p1 += acc[B][4 * (jj - 1) + 3]; }
    else if (B > 0) { p0 += acc[B > 0 ? B - 1 : 0][14]; p1 += acc[B > 0 ? B - 1 : 0][15]; }
    zw[64 * j + off_even] = p0;
    zw[64 * j + off_odd] = p1;
  }
}
__device__ __forceinline__ int tab_off(int c) { return c == 4 ? 0 : (c + 1) * 2 * TABW + (c >= 2 ? 1024 : 0); }
__device__ __forceinline__ int tile_perm(int ch) { return ch ^ (((ch >> 3) & 3) << 1); }

__device__ __forceinline__ void wait_ctr(const unsigned int* ctr, uint32_t target) {
  uint32_t v;
  int it = 0;
  do {
    asm volatile("ld.acquire.gpu.global.u32 %0, [%1];" : "=r"(v) : "l"(ctr) : "memory");
  } while ((int)(v - target) < 0 && ++it < SPIN_LIMIT);
}

__device__ __forceinline__ float2 row_part_stats(const uint32_t (&x)[20]) {
  float cs[5][4];
#pragma unroll
  for (int k = 0; k < 5; k++) {
    cs[k][0] = cs[k][1] = cs[k][2] = cs[k][3] = 0.f;
    mma_bf16x(cs[k], x[4 * k + 0], x[4 * k + 2], x[4 * k + 1], x[4 * k + 3], 0x3F803F80u, 0x3F803F80u);
  }
  const float mean = ((((cs[0][0] + cs[0][2]) + (cs[1][0] + cs[1][2])) + ((cs[2][0] + cs[2][2]) + (cs[3][0] + cs[3][2]))) + (cs[4][0] + cs[4][2])) * (1.f / 160.f);
  float m2a = 0.f, m2b = 0.f, m2c = 0.f, m2d = 0.f;
#pragma unroll
  for (int i = 0; i < 20; i += 2) {
    const float a = lo_f(x[i]) - mean, b = hi_f(x[i]) - mean, c = lo_f(x[i + 1]) - mean, d = hi_f(x[i + 1]) - mean;
    m2a = fmaf(a, a, m2a); m2b = fmaf(b, b, m2b); m2c = fmaf(c, c, m2c); m2d = fmaf(d, d, m2d);
  }
  float m2 = (m2a + m2b) + (m2c + m2d);
  m2 += __shfl_xor_sync(0xffffffffu, m2, 1);
  m2 += __shfl_xor_sync(0xffffffffu, m2, 2);
  return make_float2(mean, m2);
}
__device__ __forceinline__ void row_normalize(const float4* st, const uint32_t (&x)[20], uint32_t (&y)[20]) {
  const float4 p = st[0], q = st[1];
  const float mean = ((p.x + p.z) + (q.x + q.z)) * 0.25f;
  const float d0 = p.x - mean, d1 = p.z - mean, d2 = q.x - mean, d3 = q.z - mean;
  const float m2 = ((p.y + p.w) + (q.y + q.w)) + 160.f * ((d0 * d0 + d1 * d1) + (d2 * d2 + d3 * d3));
  const float hd = rbf(sqrtf(rbf(rbf(m2 * (1.f / D_)) + 1e-5f)));
  const float hr = __frcp_rn(hd);
  const bf162 hm2 = __float2bfloat162_rn(mean);
#pragma unroll
  for (int i = 0; i < 20; i++) {
    const uint32_t d = b2u(__hsub2_rn(u2b(x[i]), hm2));
    y[i] = LN2_EXACT ? pack2(fdivr(lo_f(d), hd, hr), fdivr(hi_f(d), hd, hr)) : pack2(lo_f(d) * hr, hi_f(d) * hr);
  }
}

__device__ __forceinline__ void gather_kv(Smem& sm, int c0, int tid) {
  mbar_wait(&sm.mbarc);
  uint4 v[4];
  uint4* src = g_kv + c0 * 256 + tid;
#pragma unroll
  for (int i = 0; i < 4; i++) if (i < 3 || tid >= 256) v[i] = ld_poll4(src + NTHR * i - (i == 3 ? 256 : 0));
#pragma unroll
  for (int i = 0; i < 4; i++) {
    if (i < 3 || tid >= 256) {
      const int t = tid + NTHR * i - (i == 3 ? 256 : 0);
      int it = 0;
      while (!ready4(v[i]) && ++it < SPIN_LIMIT) { __nanosleep(POLL_NS); v[i] = ld_poll4(g_kv + c0 * 256 + t); }
      *reinterpret_cast<uint4*>(&sm.u[t >> 8][UPAD + (t & 255) * 8]) = make_uint4(~v[i].x, ~v[i].y, ~v[i].z, ~v[i].w);
    }
  }
  asm volatile("fence.proxy.async.shared::cta;" ::: "memory");
  __syncthreads();
}

__global__ void __launch_bounds__(NTHR, 1)
fused_kernel(const __grid_constant__ CUtensorMap tmg, const __grid_constant__ CUtensorMap tmu,
             const __grid_constant__ CUtensorMap tmd, const bf16* __restrict__ gq, const bf16* __restrict__ gk, const bf16* __restrict__ gv,
             const bf16* __restrict__ gsk, const bf16* __restrict__ gh, const bf16* __restrict__ gD,
             const bf16* __restrict__ gwr, bf16* __restrict__ gout) {
  extern __shared__ __align__(128) unsigned char smraw[];
  Smem& sm = *reinterpret_cast<Smem*>(smraw);
  const int tid = threadIdx.x;
  const int cta = blockIdx.x;
  const int c0 = cta * CPC;
  const int lane = tid & 31;
  const int wid = tid >> 5;
  STAMP(0);
  const long long tstart = clock64();

  {
    uint4* hs = reinterpret_cast<uint4*>(&sm.z[0][0][0]);
    const int oc = tid >> 2;
    const int r0 = cta * 16 + (tid & 3) * 4;
    uint4 kk[7], vv[4], sk[4];
    if (tid < 320) {
      const uint4* kp = reinterpret_cast<const uint4*>(gk) + (size_t)r0 * 80 + oc;
      const uint4* vp = reinterpret_cast<const uint4*>(gv) + (size_t)r0 * 80 + oc;
#pragma unroll
      for (int i = 0; i < 7; i++) kk[i] = (i >= 3 || r0 > 0) ? __ldg(kp + (i - 3) * 80) : make_uint4(0, 0, 0, 0);
#pragma unroll
      for (int i = 0; i < 4; i++) vv[i] = __ldg(vp + i * 80);
#pragma unroll
      for (int i = 0; i < 4; i++) sk[i] = __ldg(reinterpret_cast<const uint4*>(gsk) + oc * 4 + i);
    } else if (tid == 320) {
      asm volatile("mbarrier.init.shared.b64 [%0], 1;" ::"r"(smem_u32(&sm.mbarh)) : "memory");
      asm volatile("mbarrier.init.shared.b64 [%0], 1;" ::"r"(smem_u32(&sm.mbar)) : "memory");
      asm volatile("mbarrier.init.shared.b64 [%0], 1;" ::"r"(smem_u32(&sm.mbarw)) : "memory");
      asm volatile("mbarrier.init.shared.b64 [%0], 1;" ::"r"(smem_u32(&sm.mbarc)) : "memory");
      asm volatile("mbarrier.init.shared.b64 [%0], 1;" ::"r"(smem_u32(&sm.mbary)) : "memory");
      asm volatile("fence.proxy.async.shared::cta;" ::: "memory");
    } else if (tid == 352) {
      uint32_t v2, v3;
      asm volatile("ld.relaxed.gpu.global.u32 %0, [%1];" : "=r"(v2) : "l"(&g_ctr2) : "memory");
      asm volatile("ld.relaxed.gpu.global.u32 %0, [%1];" : "=r"(v3) : "l"(&g_ctr3) : "memory");
      sm.target2 = (v2 / NCTA + 1u) * NCTA;
      sm.target3 = (v3 / NCTA + 1u) * NCTA;
    }
    if (tid < 320) bar_sync(6, 384); else { bar_arrive(6, 384); bar_sync(5, 64); }
    STAMP(9);
    if (tid < 320) {
      uint32_t o[4][4];
#pragma unroll
      for (int p = 0; p < 4; p++) {
        const bf162 w0 = u2b(__byte_perm(sk[p].x, sk[p].z, 0x5410)), w1 = u2b(__byte_perm(sk[p].x, sk[p].z, 0x7632));
        const bf162 w2 = u2b(__byte_perm(sk[p].y, sk[p].w, 0x5410)), w3 = u2b(__byte_perm(sk[p].y, sk[p].w, 0x7632));
        uint32_t kv[4];
#pragma unroll
        for (int i = 0; i < 4; i++) {
          const uint32_t k0 = p == 0 ? kk[i].x : p == 1 ? kk[i].y : p == 2 ? kk[i].z : kk[i].w;
          const uint32_t k1 = p == 0 ? kk[i + 1].x : p == 1 ? kk[i + 1].y : p == 2 ? kk[i + 1].z : kk[i + 1].w;
          const uint32_t k2 = p == 0 ? kk[i + 2].x : p == 1 ? kk[i + 2].y : p == 2 ? kk[i + 2].z : kk[i + 2].w;
          const uint32_t k3 = p == 0 ? kk[i + 3].x : p == 1 ? kk[i + 3].y : p == 2 ? kk[i + 3].z : kk[i + 3].w;
          const uint32_t vx = p == 0 ? vv[i].x : p == 1 ? vv[i].y : p == 2 ? vv[i].z : vv[i].w;
          bf162 a = __hmul2_rn(u2b(k0), w3);
          a = __hadd2_rn(a, __hmul2_rn(u2b(k1), w2));
          a = __hadd2_rn(a, __hmul2_rn(u2b(k2), w1));
          a = __hadd2_rn(a, __hmul2_rn(u2b(k3), w0));
          kv[i] = b2u(__hmul2_rn(a, u2b(vx)));
        }
        o[p][0] = enc(__byte_perm(kv[0], kv[1], 0x5410)); o[p][1] = enc(__byte_perm(kv[2], kv[3], 0x5410));
        o[p][2] = enc(__byte_perm(kv[0], kv[1], 0x7632)); o[p][3] = enc(__byte_perm(kv[2], kv[3], 0x7632));
      }
      uint2* dst = reinterpret_cast<uint2*>(g_kv) + (size_t)(oc * 8) * 512 + (r0 >> 2);
#pragma unroll
      for (int p = 0; p < 4; p++) {
        st_pub2(dst + (2 * p) * 512, o[p][0], o[p][1]);
        st_pub2(dst + (2 * p + 1) * 512, o[p][2], o[p][3]);
      }
      STAMP(10);
      if (wid == 0) bar_sync(4, 320); else bar_arrive(4, 320);
      if (tid == 0) {
        asm volatile("red.relaxed.gpu.global.add.u32 [%0], 1;" ::"l"(&g_ctr2) : "memory");
      }
      __syncwarp();
    } else {
      const int t0 = tid - 320;
      const uint4 zz = make_uint4(0, 0, 0, 0);
      if (tid == 320) {
        while (clock64() - tstart < H_DELAY) {}
        mbar_expect(&sm.mbarh, CPC * S_ * 2);
        bulk_g2s(hs, gh + (size_t)c0 * S_, CPC * S_ * 2, &sm.mbarh);
      }
      __syncwarp();
      for (int t = t0; t < CPC * 17; t += 64) *reinterpret_cast<uint4*>(&sm.u[t / 17][(t % 17) * 8]) = zz;
      if (t0 < 40) *reinterpret_cast<uint4*>(&sm.tabA[0][0][0] + tab_off(t0 >> 3) + ((t0 >> 2) & 1) * TABW + 1024 + 4 * (t0 & 3)) = zz;
      while (clock64() - tstart < C_DELAY) {}
      (&g_cand[cta][0][0])[t0] = zz;
      (&g_cand[cta][0][0])[64 + t0] = zz;
      if (t0 < 32) (&g_cand[cta][0][0])[128 + t0] = zz;
      else reinterpret_cast<uint4*>(&g_keys[cta][0])[t0 - 32] = zz;
      if (cta >= N1 && cta < N1 + N2) {
#pragma unroll
        for (int i = 0; i < 3; i++) g_act[cta - N1][t0 + 64 * i] = zz;
      }
      bar_sync(5, 64);
      if (tid == 352) {
        __threadfence();
        const unsigned old = atomicAdd(&g_ctr, 1u);
        sm.target = (old / NCTA + 1u) * NCTA;
      }
      __syncwarp();
    }
    mbar_wait(&sm.mbarh);
#pragma unroll
    for (int i = 0; i < 4; i++) {
      const int t = (NTHR - 1 - tid) + NTHR * i;
      if (t < CPC * 256) {
        uint32_t* tb = &sm.tabA[0][0][0] + tab_off(t >> 8) + (255 - (t & 255)) * 4;
        const uint4 h = hs[t];
        const uint32_t hp = (t & 255) ? reinterpret_cast<const uint32_t*>(hs)[4 * t - 1] : 0u;
        uint4 r1, rr;
        r1.x = __byte_perm(h.w, 0, 0x1032); r1.y = __byte_perm(h.z, 0, 0x1032);
        r1.z = __byte_perm(h.y, 0, 0x1032); r1.w = __byte_perm(h.x, 0, 0x1032);
        rr.x = __byte_perm(h.w, h.z, 0x7610); rr.y = __byte_perm(h.z, h.y, 0x7610);
        rr.z = __byte_perm(h.y, h.x, 0x7610); rr.w = __byte_perm(h.x, hp, 0x7610);
        *reinterpret_cast<uint4*>(tb) = rr;
        *reinterpret_cast<uint4*>(tb + TABW) = r1;
      }
    }
    STAMP(12);
  }
  __syncthreads();

  const int wg = __shfl_sync(0xffffffffu, tid >> 7, 0);
  const int wtid = tid & 127;
  uint4* tile = reinterpret_cast<uint4*>(&sm.tabB[0][0][0]);
  if (wg < 2) {
    asm volatile("setmaxnreg.inc.sync.aligned.u32 224;");
    const int w = (tid >> 5) & 3, g = lane >> 2, tq = lane & 3;
    float* zw = sm.z[wg][w];
    const int sw = 3 * (((tq + w) >> 1) & 1);
    const int off_even = 16 * (tq + w) + 4 * ((0 + (g >> 2)) ^ sw) + (g & 3);
    const int off_odd = 16 * (tq + w) + 4 * ((2 + (g >> 2)) ^ sw) + (g & 3);
    uint32_t a[8][8];
    const uint32_t* tp0 = &sm.tabA[0][g & 1][1019 - 8 * w - (g >> 1) + tq];
    load_a_all(a, tp0 + tab_off(wg));
    float acc[8][16];
#pragma unroll
    for (int b = 0; b < 8; b++)
#pragma unroll
      for (int i = 0; i < 16; i++) acc[b][i] = 0.f;
    gather_kv(sm, c0, tid);
    STAMP(1);
#pragma unroll 1
    for (int c = wg; c < CPC; c += 2) {
      const uint64_t desc = (uint64_t)((smem_u32(&sm.u[c][UPAD - 8]) & 0x3FFFF) >> 4) | ((uint64_t)1 << 16) | ((uint64_t)8 << 32);
      CST(c, 0);
      if (c > 0) bar_sync(1 + wg, 256);
      issue_g<0>(acc, a[0], desc);
      CST(c, 1);
      issue_g<1>(acc, a[1], desc);
      issue_g<2>(acc, a[2], desc);
      issue_g<3>(acc, a[3], desc);
      issue_g<4>(acc, a[4], desc);
      issue_g<5>(acc, a[5], desc);
      if (c + 1 < CPC) bar_arrive(1 + (wg ^ 1), 256);
      issue_g<6>(acc, a[6], desc);
      issue_g<7>(acc, a[7], desc);
      CST(c, 2);
      if (c >= 2) bar_sync(5 + wg, 256);
      wg_wait<4>();
      fence_blk<0>(acc); fence_blk<1>(acc); fence_blk<2>(acc); fence_blk<3>(acc);
      sts_blk<0>(acc, zw, off_even, off_odd);
      sts_blk<1>(acc, zw, off_even, off_odd);
      sts_blk<2>(acc, zw, off_even, off_odd);
      sts_blk<3>(acc, zw, off_even, off_odd);
      bar_arrive(9 + wg, 256);
      CST(c, 3);
      wg_wait<0>();
      fence_blk<4>(acc); fence_blk<5>(acc); fence_blk<6>(acc); fence_blk<7>(acc);
#pragma unroll
      for (int i = 0; i < 8; i++) fence_a(a[i]);
      sts_blk<4>(acc, zw, off_even, off_odd);
      sts_blk<5>(acc, zw, off_even, off_odd);
      sts_blk<6>(acc, zw, off_even, off_odd);
      sts_blk<7>(acc, zw, off_even, off_odd);
      bar_arrive(3 + wg, 256);
      CST(c, 4);
      if (c + 2 < CPC) load_a_all(a, tp0 + tab_off(c + 2));
    }
    STAMP(2 + wg);
    asm volatile("setmaxnreg.dec.sync.aligned.u32 168;");
  } else {
    asm volatile("setmaxnreg.dec.sync.aligned.u32 56;");
    if (((wtid & 15) >> 2) < ((wtid >> 4) & 3))
      *reinterpret_cast<uint4*>(&sm.z[wtid >> 6][(wtid >> 4) & 3][(wtid & 15) * 4]) = make_uint4(0, 0, 0, 0);
    if (wtid == 64) {
      const unsigned target = sm.target2;
      uint32_t v;
      int it = 0;
      do {
        asm volatile("ld.relaxed.gpu.global.u32 %0, [%1];" : "=r"(v) : "l"(&g_ctr2) : "memory");
      } while ((int)(v - target) < 0 && ++it < SPIN_LIMIT);
      asm volatile("mbarrier.arrive.shared.b64 _, [%0];" ::"r"(smem_u32(&sm.mbarc)) : "memory");
    }
    __syncwarp();
    gather_kv(sm, c0, tid);
#pragma unroll
    for (int i = 0; i < 10; i++) g_kv[c0 * 256 + wtid + 128 * i] = make_uint4(0, 0, 0, 0);
    if (wtid == 96) wait_ctr(&g_ctr, sm.target);
    __syncwarp();
    if (wtid == 32) {
      const uint32_t mw = smem_u32(&sm.mbarw);
      mbar_expect(&sm.mbar, 17 * D_ * 2);
#pragma unroll 1
      for (int r = 0; r < 16; r++) bulk_g2s(&sm.q[r][0], gq + (size_t)(cta * 16 + r) * D_, D_ * 2, &sm.mbar);
      bulk_g2s(&sm.wr[0], gwr, D_ * 2, &sm.mbar);
      if (cta < N1) {
        asm volatile("mbarrier.arrive.expect_tx.shared.b64 _, [%0], %1;" ::"r"(mw), "r"(3840 * 16) : "memory");
#pragma unroll 1
        for (int i = 0; i < 4; i++) {
          asm volatile("cp.async.bulk.tensor.2d.shared::cluster.global.mbarrier::complete_tx::bytes [%0], [%1, {%3, %4}], [%2];" ::"r"(smem_u32(&sm.w[i * 480])),
                       "l"(&tmg), "r"(mw), "r"(cta * 24), "r"(i * 160) : "memory");
          asm volatile("cp.async.bulk.tensor.2d.shared::cluster.global.mbarrier::complete_tx::bytes [%0], [%1, {%3, %4}], [%2];" ::"r"(smem_u32(&sm.w[1920 + i * 480])),
                       "l"(&tmu), "r"(mw), "r"(cta * 24), "r"(i * 160) : "memory");
        }
      } else if (cta < N1 + N2) {
        asm volatile("mbarrier.arrive.expect_tx.shared.b64 _, [%0], %1;" ::"r"(mw), "r"(3072 * 16) : "memory");
#pragma unroll 1
        for (int i = 0; i < 6; i++)
          asm volatile("cp.async.bulk.tensor.2d.shared::cluster.global.mbarrier::complete_tx::bytes [%0], [%1, {%3, %4}], [%2];" ::"r"(smem_u32(&sm.w[i * 512])),
                       "l"(&tmd), "r"(mw), "r"((cta - N1) * 16), "r"(i * 256) : "memory");
      }
    }
    const int rpb = wtid >> 1, re2 = wtid & 1;
    const int rsw = 3 * ((rpb >> 1) & 1);
    const int roff0 = 16 * rpb + 4 * ((2 * re2 + 0) ^ rsw);
    const int roff1 = 16 * rpb + 4 * ((2 * re2 + 1) ^ rsw);
    const uint32_t dvl = reinterpret_cast<const unsigned short*>(gD)[c0 + (lane < CPC ? lane : 0)];
#pragma unroll 1
    for (int c = 0; c < CPC; c++) {
      const int zg = c & 1;
      const uint32_t dvc = __shfl_sync(0xffffffffu, dvl, c);
      const bf162 d2 = u2b(dvc | (dvc << 16));
      CST(c, 5);
#pragma unroll
      for (int half = 0; half < 2; half++) {
        bar_sync((half ? 3 : 9) + zg, 256);
        const float* zb = sm.z[zg][0] + half * 1024;
        float4 x[4][2];
#pragma unroll
        for (int ww = 0; ww < 4; ww++) {
          x[ww][0] = *reinterpret_cast<const float4*>(zb + ww * ZPB * 16 + roff0);
          x[ww][1] = *reinterpret_cast<const float4*>(zb + ww * ZPB * 16 + roff1);
        }
        const int sidx = half * 1024 + wtid * 8;
        const uint4 kvv = *reinterpret_cast<const uint4*>(&sm.u[c][UPAD + sidx]);
        if (half == 1 && c + 2 < CPC) bar_arrive(5 + zg, 256);
        uint4 o;
        o.x = pack2((x[0][0].x + x[1][0].x) + (x[2][0].x + x[3][0].x), (x[0][0].y + x[1][0].y) + (x[2][0].y + x[3][0].y));
        o.y = pack2((x[0][0].z + x[1][0].z) + (x[2][0].z + x[3][0].z), (x[0][0].w + x[1][0].w) + (x[2][0].w + x[3][0].w));
        o.z = pack2((x[0][1].x + x[1][1].x) + (x[2][1].x + x[3][1].x), (x[0][1].y + x[1][1].y) + (x[2][1].y + x[3][1].y));
        o.w = pack2((x[0][1].z + x[1][1].z) + (x[2][1].z + x[3][1].z), (x[0][1].w + x[1][1].w) + (x[2][1].w + x[3][1].w));
        o.x = b2u(__hadd2_rn(u2b(o.x), __hmul2_rn(u2b(kvv.x), d2)));
        o.y = b2u(__hadd2_rn(u2b(o.y), __hmul2_rn(u2b(kvv.y), d2)));
        o.z = b2u(__hadd2_rn(u2b(o.z), __hmul2_rn(u2b(kvv.z), d2)));
        o.w = b2u(__hadd2_rn(u2b(o.w), __hmul2_rn(u2b(kvv.w), d2)));
        st_pub4(g_y2 + ((64 * half + rpb) * 640 + c0 + c) * 2 + re2, enc4(o));
        CST(c, 6 + half);
      }
    }
    if (wid == 11) bar_sync(8, 128); else bar_arrive(8, 128);
    STAMP(4);
    asm volatile("setmaxnreg.inc.sync.aligned.u32 168;");
  }

  if (tid == 352) {
    asm volatile("red.relaxed.gpu.global.add.u32 [%0], 1;" ::"l"(&g_ctr3) : "memory");
    wait_ctr(&g_ctr3, sm.target3);
    asm volatile("mbarrier.arrive.shared.b64 _, [%0];" ::"r"(smem_u32(&sm.mbary)) : "memory");
  }
  __syncwarp();
  if (ABL == 4) { mbar_wait(&sm.mbary); for (int i = tid; i < 1280; i += NTHR) g_y2[cta * 1280 + i] = make_uint4(0, 0, 0, 0); if (cta < N1 + N2) mbar_wait(&sm.mbarw); mbar_wait(&sm.mbar); return; }
  RT(0);
  const int g = lane >> 2, tq = lane & 3;
  const int hh = wid & 1, gqi = wid >> 1;
  const int row = hh * 8 + g;
  uint32_t hreg[20], hnreg[20];
  {
    const uint4* src = g_y2 + cta * 1280 + tid;
    uint4 v[4];
    if (wid < 8) {
      mbar_wait(&sm.mbar);
#pragma unroll
      for (int k = 0; k < 5; k++) {
        const uint4 qv4 = *reinterpret_cast<const uint4*>(&sm.q[row][32 * (5 * gqi + k) + 8 * tq]);
        hreg[4 * k] = qv4.x; hreg[4 * k + 1] = qv4.y; hreg[4 * k + 2] = qv4.z; hreg[4 * k + 3] = qv4.w;
      }
      const float2 ps = row_part_stats(hreg);
      if (tq == 0) sm.stq[row][gqi] = ps;
      bar_sync(7, 256);
      row_normalize(reinterpret_cast<const float4*>(sm.stq[row]), hreg, hnreg);
    }
    RT(1);
    mbar_wait(&sm.mbary);
    RT(2);
#pragma unroll
    for (int i = 0; i < 4; i++) if (i < 3 || tid < 128) v[i] = ld_poll4(src + NTHR * i);
    int it = 0;
    bool all;
    do {
      all = true;
#pragma unroll
      for (int i = 0; i < 4; i++)
        if ((i < 3 || tid < 128) && !ready4(v[i])) { v[i] = ld_poll4(src + NTHR * i); all = false; }
    } while (!all && ++it < SPIN_LIMIT);
#pragma unroll
    for (int i = 0; i < 4; i++) {
      if (i < 3 || tid < 128) {
        const int t = tid + NTHR * i;
        tile[(t & 1) * 640 + tile_perm(t >> 1)] = make_uint4(~v[i].x, ~v[i].y, ~v[i].z, ~v[i].w);
      }
    }
  }
  __syncthreads();
  STAMP(5);
  RT(3);
  if (ABL == 3) { for (int i = tid; i < 1280; i += NTHR) g_y2[cta * 1280 + i] = make_uint4(0, 0, 0, 0); if (cta < N1 + N2) mbar_wait(&sm.mbarw); return; }

  if (wid < 8) {
#pragma unroll
    for (int k = 0; k < 5; k++) {
      const int base = 32 * (5 * gqi + k);
      const int lch = base + 8 * ((lane & 7) >> 1) + 2 * (lane >> 3) + (lane & 1);
      uint32_t y[4];
      asm volatile("ldmatrix.sync.aligned.m8n8.x4.trans.shared.b16 {%0,%1,%2,%3}, [%4];"
                   : "=r"(y[0]), "=r"(y[1]), "=r"(y[2]), "=r"(y[3]) : "r"(smem_u32(&tile[hh * 640 + tile_perm(lch)])) : "memory");
#pragma unroll
      for (int i = 0; i < 4; i++)
        hreg[4 * k + i] = b2u(__hadd2_rn(u2b(hreg[4 * k + i]), __hmul2_rn(u2b(hnreg[4 * k + i]), u2b(y[i]))));
    }
    RT(4);
    const float2 ps = row_part_stats(hreg);
    if (tq == 0) sm.st[row][gqi] = ps;
    STAMP(13);
    RT(5);
    bar_sync(7, 256);
    row_normalize(reinterpret_cast<const float4*>(sm.st[row]), hreg, hnreg);
    RT(6);
    float cr[5][4];
#pragma unroll
    for (int k = 0; k < 5; k++) {
      cr[k][0] = cr[k][1] = cr[k][2] = cr[k][3] = 0.f;
      const uint4 w4 = sm.wr[4 * (5 * gqi + k) + tq];
      mma_bf16(cr[k], hnreg[4 * k + 0], hnreg[4 * k + 1], w4.x, w4.y);
      mma_bf16(cr[k], hnreg[4 * k + 2], hnreg[4 * k + 3], w4.z, w4.w);
    }
    if (tq == 0) sm.rp[row][gqi] = ((cr[0][0] + cr[1][0]) + (cr[2][0] + cr[3][0])) + cr[4][0];
  }
  STAMP(14);
  RT(7);
  __syncthreads();
  uint32_t best;
  {
    const int rr = lane & 15;
    const float4 rp4 = *reinterpret_cast<const float4*>(sm.rp[rr]);
    const float r = (rp4.x + rp4.y) + (rp4.z + rp4.w);
    const uint32_t bits = __bfloat16_as_ushort(__float2bfloat16_rn(r));
    const uint32_t ord = (bits & 0x8000u) ? (bits ^ 0xFFFFu) : (bits ^ 0x8000u);
    const uint32_t key = (ord << 16) | 0x8000u | (uint32_t)(2047 - (cta * 16 + rr));
    best = __reduce_max_sync(0xffffffffu, key);
  }
  if (wid >= 8) asm volatile("st.relaxed.gpu.global.u32 [%0], %1;" ::"l"(&g_keys[tid - 256][cta]), "r"(best) : "memory");
  STAMP(15);
  RT(8);
  const int brow = (2047 - (int)(best & 0x7FFu)) - cta * 16;
  if (wid < 8 && row == brow) {
#pragma unroll
    for (int k = 0; k < 5; k++)
      st_pub4(&g_cand[cta][0][4 * (5 * gqi + k) + tq], enc4(make_uint4(hnreg[4 * k], hnreg[4 * k + 1], hnreg[4 * k + 2], hnreg[4 * k + 3])));
#pragma unroll
    for (int k = 0; k < 5; k++)
      st_pub4(&g_cand[cta][1][4 * (5 * gqi + k) + tq], enc4(make_uint4(hreg[4 * k], hreg[4 * k + 1], hreg[4 * k + 2], hreg[4 * k + 3])));
  }
#pragma unroll
  for (int i = 0; i < 20; i++) hreg[i] = b2u(__hadd2_rn(u2b(hreg[i]), u2b(hnreg[i])));
  STAMP(6);
  RT(9);
  if (ABL == 2) { for (int i = tid; i < 1280; i += NTHR) g_y2[cta * 1280 + i] = make_uint4(0, 0, 0, 0); if (cta < N1 + N2) mbar_wait(&sm.mbarw); return; }
  if (wid == 11) {
    const uint4* kp = reinterpret_cast<const uint4*>(&g_keys[cta][0]) + lane;
    uint4 v = ld_poll4(kp);
    int it = 0;
    while (!ready4(v) && ++it < SPIN_LIMIT) v = ld_poll4(kp);
    const uint32_t m = max(max(v.x, v.y), max(v.z, v.w));
    const uint32_t wk = __reduce_max_sync(0xffffffffu, m);
    if (lane == 0) sm.win = wk;
  }
  __syncthreads();
  const uint32_t win = sm.win;
  const int wrow = 2047 - (int)(win & 0x7FFu);
  const int wcta = wrow >> 4;
  const bool st_out = wid < 8 && (cta * 16 + row) != wrow;
  uint4* outp = reinterpret_cast<uint4*>(gout + (size_t)(cta * 16 + row) * D_) + 20 * gqi + tq;
  if (cta >= N1) {
    if (st_out) {
#pragma unroll
      for (int k = 0; k < 5; k++) outp[4 * k] = make_uint4(hreg[4 * k], hreg[4 * k + 1], hreg[4 * k + 2], hreg[4 * k + 3]);
    }
  }
  if (cta >= N1 || ABL == 1) {
#pragma unroll
    for (int i = 0; i < 4; i++) if (i < 3 || tid < 128) g_y2[cta * 1280 + tid + NTHR * i] = make_uint4(0, 0, 0, 0);
  }
  STAMP(7);
  RT(10);
  if (ABL == 1) { if (cta < N1 + N2) mbar_wait(&sm.mbarw); return; }
  if (cta < N1 + N2) mbar_wait(&sm.mbarw);
  float* xs = &sm.z[0][0][0];
  float* part = xs + 2048;
  if (cta < N1) {
    if (tid < 80) {
      const uint4 v = poll4(&g_cand[wcta][0][tid]);
      float4* xp = reinterpret_cast<float4*>(xs + tid * 8);
      xp[0] = make_float4(lo_f(v.x), hi_f(v.x), lo_f(v.y), hi_f(v.y));
      xp[1] = make_float4(lo_f(v.z), hi_f(v.z), lo_f(v.w), hi_f(v.w));
    }
    __syncthreads();
    const int m = wid / 6, hc = (wid % 6) >> 1, rs = (wid & 1) * 32 + lane;
    float a[8];
#pragma unroll
    for (int j = 0; j < 8; j++) a[j] = 0.f;
#pragma unroll
    for (int it = 0; it < 10; it++) {
      const int r = rs + 64 * it;
      const uint4 wv = sm.w[m * 1920 + r * 3 + hc];
      const float x = xs[r];
      a[0] = fmaf(x, lo_f(wv.x), a[0]); a[1] = fmaf(x, hi_f(wv.x), a[1]);
      a[2] = fmaf(x, lo_f(wv.y), a[2]); a[3] = fmaf(x, hi_f(wv.y), a[3]);
      a[4] = fmaf(x, lo_f(wv.z), a[4]); a[5] = fmaf(x, hi_f(wv.z), a[5]);
      a[6] = fmaf(x, lo_f(wv.w), a[6]); a[7] = fmaf(x, hi_f(wv.w), a[7]);
    }
    {
      const bool up = lane & 16;
#pragma unroll
      for (int j = 0; j < 4; j++) {
        const float send = up ? a[j] : a[j + 4], keep = up ? a[j + 4] : a[j];
        a[j] = keep + __shfl_xor_sync(0xffffffffu, send, 16);
      }
      const bool up2 = lane & 8;
#pragma unroll
      for (int j = 0; j < 2; j++) {
        const float send = up2 ? a[j] : a[j + 2], keep = up2 ? a[j + 2] : a[j];
        a[j] = keep + __shfl_xor_sync(0xffffffffu, send, 8);
      }
      const bool up3 = lane & 4;
      const float send = up3 ? a[0] : a[1], keep = up3 ? a[1] : a[0];
      a[0] = keep + __shfl_xor_sync(0xffffffffu, send, 4);
      a[0] += __shfl_xor_sync(0xffffffffu, a[0], 2);
      a[0] += __shfl_xor_sync(0xffffffffu, a[0], 1);
      if ((lane & 3) == 0) part[wid * 8 + (lane >> 2)] = a[0];
    }
    __syncthreads();
    if (wid == 0) {
      uint32_t bits = 0;
      if (lane < 24) {
        const int hc2 = lane >> 3, j = lane & 7;
        const float gt = rbf(part[(2 * hc2) * 8 + j] + part[(2 * hc2 + 1) * 8 + j]);
        const float up = rbf(part[(6 + 2 * hc2) * 8 + j] + part[(6 + 2 * hc2 + 1) * 8 + j]);
        const float sg = rbf(gt / (1.f + __expf(-gt)));
        bits = __bfloat16_as_ushort(__float2bfloat16_rn(sg * up));
      }
      const uint32_t nb = __shfl_down_sync(0xffffffffu, bits, 1);
      const uint32_t pw = bits | (nb << 16);
      const uint32_t w1 = __shfl_down_sync(0xffffffffu, pw, 2), w2 = __shfl_down_sync(0xffffffffu, pw, 4), w3 = __shfl_down_sync(0xffffffffu, pw, 6);
      const uint4 mine = enc4(make_uint4(pw, w1, w2, w3));
#pragma unroll
      for (int i = 0; i < 4; i++) {
        const int t = lane + 32 * i;
        const int cons = t / 3, ck = t - 3 * cons;
        uint4 v;
        v.x = __shfl_sync(0xffffffffu, mine.x, 8 * ck); v.y = __shfl_sync(0xffffffffu, mine.y, 8 * ck);
        v.z = __shfl_sync(0xffffffffu, mine.z, 8 * ck); v.w = __shfl_sync(0xffffffffu, mine.w, 8 * ck);
        if (t < 3 * N2) st_pub4(&g_act[cons][cta * 3 + ck], v);
      }
      __syncwarp();
      bar_arrive(7, 384);
    } else {
      bar_sync(7, 384);
    }
#pragma unroll
    for (int i = 0; i < 4; i++) if (i < 3 || tid < 128) g_y2[cta * 1280 + tid + NTHR * i] = make_uint4(0, 0, 0, 0);
    if (st_out) {
#pragma unroll
      for (int k = 0; k < 5; k++) outp[4 * k] = make_uint4(hreg[4 * k], hreg[4 * k + 1], hreg[4 * k + 2], hreg[4 * k + 3]);
    }
  } else if (cta < N1 + N2 && ABL != 6) {
    const int j2 = cta - N1;
    uint4 rowv = make_uint4(0, 0, 0, 0);
    if (tid < 192) {
      const uint4 v = poll4(&g_act[j2][tid]);
      float4* xp = reinterpret_cast<float4*>(xs + tid * 8);
      xp[0] = make_float4(lo_f(v.x), hi_f(v.x), lo_f(v.y), hi_f(v.y));
      xp[1] = make_float4(lo_f(v.z), hi_f(v.z), lo_f(v.w), hi_f(v.w));
    } else if (tid < 196) {
      const int t = tid - 192;
      rowv = poll4(&g_cand[wcta][t >> 1][j2 * 2 + (t & 1)]);
      reinterpret_cast<uint4*>(part + 256)[t] = rowv;
    }
    __syncthreads();
    const int hc = lane & 1, rs = wid * 16 + (lane >> 1);
    float a[8];
#pragma unroll
    for (int j = 0; j < 8; j++) a[j] = 0.f;
#pragma unroll
    for (int it = 0; it < 8; it++) {
      const int r = rs + 192 * it;
      const uint4 wv = sm.w[r * 2 + hc];
      const float x = xs[r];
      a[0] = fmaf(x, lo_f(wv.x), a[0]); a[1] = fmaf(x, hi_f(wv.x), a[1]);
      a[2] = fmaf(x, lo_f(wv.y), a[2]); a[3] = fmaf(x, hi_f(wv.y), a[3]);
      a[4] = fmaf(x, lo_f(wv.z), a[4]); a[5] = fmaf(x, hi_f(wv.z), a[5]);
      a[6] = fmaf(x, lo_f(wv.w), a[6]); a[7] = fmaf(x, hi_f(wv.w), a[7]);
    }
    {
      const bool up = lane & 16;
#pragma unroll
      for (int j = 0; j < 4; j++) {
        const float send = up ? a[j] : a[j + 4], keep = up ? a[j + 4] : a[j];
        a[j] = keep + __shfl_xor_sync(0xffffffffu, send, 16);
      }
      const bool up2 = lane & 8;
#pragma unroll
      for (int j = 0; j < 2; j++) {
        const float send = up2 ? a[j] : a[j + 2], keep = up2 ? a[j + 2] : a[j];
        a[j] = keep + __shfl_xor_sync(0xffffffffu, send, 8);
      }
      const bool up3 = lane & 4;
      const float send = up3 ? a[0] : a[1], keep = up3 ? a[1] : a[0];
      a[0] = keep + __shfl_xor_sync(0xffffffffu, send, 4);
      a[0] += __shfl_xor_sync(0xffffffffu, a[0], 2);
      if ((lane & 2) == 0) part[wid * 16 + hc * 8 + (lane >> 2)] = a[0];
    }
    __syncthreads();
    if (tid < 16) {
      float y = 0.f;
#pragma unroll
      for (int i = 0; i < 12; i++) y += part[i * 16 + tid];
      const uint32_t ord = win >> 16;
      const uint32_t rb = (ord & 0x8000u) ? (ord ^ 0x8000u) : (ord ^ 0xFFFFu);
      const float r = __uint_as_float(rb << 16);
      const float sg = rbf(1.f / (1.f + __expf(-r)));
      const float yy = rbf(rbf(y) * sg);
      const unsigned short* rv = reinterpret_cast<const unsigned short*>(part + 256);
      const float hn = __uint_as_float((uint32_t)rv[tid] << 16), h = __uint_as_float((uint32_t)rv[16 + tid] << 16);
      gout[(size_t)wrow * D_ + j2 * 16 + tid] = __float2bfloat16_rn(h + rbf(hn + yy));
    }
  }
  STAMP(8);
  RT(11);
}

}

typedef CUresult (*EncodeFn)(CUtensorMap*, CUtensorMapDataType, cuuint32_t, void*, const cuuint64_t*, const cuuint64_t*,
                             const cuuint32_t*, const cuuint32_t*, CUtensorMapInterleave, CUtensorMapSwizzle,
                             CUtensorMapL2promotion, CUtensorMapFloatOOBfill);

extern "C" void kernel_launch(void* const* d_in, const int* in_sizes, int n_in, void* d_out, int out_size) {
  (void)in_sizes; (void)n_in; (void)out_size;
  static EncodeFn encode = nullptr;
  static CUtensorMap tmg, tmu, tmd;
  static void* cached[3] = {nullptr, nullptr, nullptr};
  if (!encode) {
    cudaFuncSetAttribute(fused_kernel, cudaFuncAttributeMaxDynamicSharedMemorySize, (int)sizeof(Smem));
    void* fn = nullptr;
    cudaDriverEntryPointQueryResult qr;
    cudaGetDriverEntryPoint("cuTensorMapEncodeTiled", &fn, cudaEnableDefault, &qr);
    encode = (EncodeFn)fn;
  }
  if (cached[0] != d_in[8] || cached[1] != d_in[9] || cached[2] != d_in[10]) {
    const cuuint32_t es[2] = {1, 1};
    {
      const cuuint64_t dims[2] = {F_, D_}, strides[1] = {F_ * 2};
      const cuuint32_t box[2] = {24, 160};
      encode(&tmg, CU_TENSOR_MAP_DATA_TYPE_BFLOAT16, 2, d_in[8], dims, strides, box, es, CU_TENSOR_MAP_INTERLEAVE_NONE,
             CU_TENSOR_MAP_SWIZZLE_NONE, CU_TENSOR_MAP_L2_PROMOTION_NONE, CU_TENSOR_MAP_FLOAT_OOB_FILL_NONE);
      encode(&tmu, CU_TENSOR_MAP_DATA_TYPE_BFLOAT16, 2, d_in[9], dims, strides, box, es, CU_TENSOR_MAP_INTERLEAVE_NONE,
             CU_TENSOR_MAP_SWIZZLE_NONE, CU_TENSOR_MAP_L2_PROMOTION_NONE, CU_TENSOR_MAP_FLOAT_OOB_FILL_NONE);
    }
    {
      const cuuint64_t dims[2] = {D_, F_}, strides[1] = {D_ * 2};
      const cuuint32_t box[2] = {16, 256};
      encode(&tmd, CU_TENSOR_MAP_DATA_TYPE_BFLOAT16, 2, d_in[10], dims, strides, box, es, CU_TENSOR_MAP_INTERLEAVE_NONE,
             CU_TENSOR_MAP_SWIZZLE_NONE, CU_TENSOR_MAP_L2_PROMOTION_NONE, CU_TENSOR_MAP_FLOAT_OOB_FILL_NONE);
    }
    cached[0] = d_in[8]; cached[1] = d_in[9]; cached[2] = d_in[10];
  }
  fused_kernel<<<NCTA, NTHR, sizeof(Smem), cudaStreamPerThread>>>(
      tmg, tmu, tmd, (const bf16*)d_in[0], (const bf16*)d_in[1], (const bf16*)d_in[2], (const bf16*)d_in[3],
      (const bf16*)d_in[4], (const bf16*)d_in[5], (const bf16*)d_in[7], (bf16*)d_out);
}
```

```cpp
#include <cuda_runtime.h>
#include <cuda_bf16.h>
#include <cuda.h>
#include <stdint.h>

namespace {

typedef __nv_bfloat16 bf16;
typedef __nv_bfloat162 bf162;

constexpr int S_ = 2048, D_ = 640, F_ = 1536;
constexpr int NCTA = 128, CPC = 5, NTHR = 384;
constexpr int UPAD = 136, USTR = 2192;
constexpr int TABW = 1040;
constexpr int ZPB = 132;
constexpr int QSTR = 648;
constexpr int N1 = 64;
constexpr int N2 = 40;
constexpr int SPIN_LIMIT = 1 << 19;
#define LN2_EXACT 1
#define ABL 0
#define CTR_NS 0
#define C_DELAY 0
#define TESTV 0
#define TESTC 0
#define HINT1 1
#define HINT2 1
#define SIGPOS 5
#define POLL_NS 100
#define H_DELAY 0
#define Q_DELAY 4500

struct __align__(128) Smem {
  uint32_t tabA[3][2][TABW];
  uint32_t extra[1024];
  uint32_t tabB[2][2][TABW];
  bf16 u[CPC][USTR];
  float z[2][4][ZPB * 16];
  bf16 q[16][QSTR];
  alignas(128) uint4 w[3840];
  uint4 wr[80];
  alignas(16) float2 st[16][4];
  alignas(16) float2 stq[16][4];
  alignas(16) float rp[16][4];
  unsigned long long mbar;
  unsigned long long mbarw;
  unsigned long long mbarc;
  unsigned long long mbary;
  unsigned long long mbarh;
  uint32_t target;
  uint32_t target2;
  uint32_t target3;
  uint32_t best;
  uint32_t win;
};

__device__ uint4 g_kv[D_ * S_ / 8];
__device__ uint4 g_y2[D_ * S_ / 8];
__device__ uint32_t g_keys[NCTA][NCTA];
__device__ uint4 g_cand[NCTA][2][80];
__device__ uint4 g_act[N2][F_ / 8];
__device__ unsigned int g_ctr;
__device__ unsigned int g_ctr2;
__device__ unsigned int g_ctr3;
#define STAMP(i)
#define RT(i)
#define CST(c, i)

__device__ __forceinline__ uint32_t smem_u32(const void* p) { return (uint32_t)__cvta_generic_to_shared(p); }
__device__ __forceinline__ void wg_fence() { asm volatile("wgmma.fence.sync.aligned;" ::: "memory"); }
__device__ __forceinline__ void wg_commit() { asm volatile("wgmma.commit_group.sync.aligned;" ::: "memory"); }
template <int N> __device__ __forceinline__ void wg_wait() { asm volatile("wgmma.wait_group.sync.aligned %0;" ::"n"(N) : "memory"); }
__device__ __forceinline__ void bar_sync(int id, int n) { asm volatile("bar.sync %0, %1;" ::"r"(id), "r"(n) : "memory"); }
__device__ __forceinline__ void bar_arrive(int id, int n) { asm volatile("bar.arrive %0, %1;" ::"r"(id), "r"(n) : "memory"); }
__device__ __forceinline__ bf162 u2b(uint32_t u) { return *reinterpret_cast<bf162*>(&u); }
__device__ __forceinline__ uint32_t b2u(bf162 b) { return *reinterpret_cast<uint32_t*>(&b); }
__device__ __forceinline__ float lo_f(uint32_t u) { return __uint_as_float(u << 16); }
__device__ __forceinline__ float hi_f(uint32_t u) { return __uint_as_float(u & 0xFFFF0000u); }
__device__ __forceinline__ float rbf(float x) { return __bfloat162float(__float2bfloat16_rn(x)); }
__device__ __forceinline__ uint32_t pack2(float a, float b) { return b2u(__floats2bfloat162_rn(a, b)); }
__device__ __forceinline__ uint32_t enc(uint32_t w) { return max(~w, 1u); }
__device__ __forceinline__ uint4 enc4(uint4 v) { return make_uint4(enc(v.x), enc(v.y), enc(v.z), enc(v.w)); }
__device__ __forceinline__ uint4 ld_poll4(const uint4* p) {
  uint4 v;
  asm volatile("ld.relaxed.gpu.global.v4.u32 {%0,%1,%2,%3}, [%4];" : "=r"(v.x), "=r"(v.y), "=r"(v.z), "=r"(v.w) : "l"(p) : "memory");
  return v;
}
__device__ __forceinline__ bool ready4(uint4 v) { return v.x != 0u && v.y != 0u && v.z != 0u && v.w != 0u; }
__device__ __forceinline__ uint4 poll4(const uint4* p) {
  uint4 v = ld_poll4(p);
  int it = 0;
  while (!ready4(v) && ++it < SPIN_LIMIT) v = ld_poll4(p);
  return make_uint4(~v.x, ~v.y, ~v.z, ~v.w);
}
__device__ __forceinline__ void st_pub4(uint4* p, uint4 v) {
  asm volatile("st.relaxed.gpu.global.v4.u32 [%0], {%1,%2,%3,%4};" ::"l"(p), "r"(v.x), "r"(v.y), "r"(v.z), "r"(v.w) : "memory");
}
__device__ __forceinline__ void st_pub2(uint2* p, uint32_t a, uint32_t b) {
  asm volatile("st.relaxed.gpu.global.v2.u32 [%0], {%1,%2};" ::"l"(p), "r"(a), "r"(b) : "memory");
}
__device__ __forceinline__ void mma_bf16(float (&c)[4], uint32_t a0, uint32_t a2, uint32_t b0, uint32_t b1) {
  asm volatile("mma.sync.aligned.m16n8k16.row.col.f32.bf16.bf16.f32 {%0,%1,%2,%3}, {%4,%5,%6,%5}, {%7,%8}, {%0,%1,%2,%3};"
               : "+f"(c[0]), "+f"(c[1]), "+f"(c[2]), "+f"(c[3]) : "r"(a0), "r"(0u), "r"(a2), "r"(b0), "r"(b1));
}
__device__ __forceinline__ void mbar_wait(const unsigned long long* bar) {
  const uint32_t mb = smem_u32(bar);
  uint32_t ok = 0;
  int it = 0;
  while (!ok && ++it < SPIN_LIMIT)
    asm volatile("{ .reg .pred p; mbarrier.try_wait.parity.shared.b64 p, [%1], 0; selp.u32 %0, 1, 0, p; }" : "=r"(ok) : "r"(mb) : "memory");
}
__device__ __forceinline__ void bulk_g2s(void* dst, const void* src, uint32_t bytes, const unsigned long long* bar) {
  asm volatile("cp.async.bulk.shared::cluster.global.mbarrier::complete_tx::bytes [%0], [%1], %2, [%3];" ::"r"(smem_u32(dst)),
               "l"(src), "r"(bytes), "r"(smem_u32(bar)) : "memory");
}
__device__ __forceinline__ void mbar_expect(const unsigned long long* bar, uint32_t bytes) {
  asm volatile("mbarrier.arrive.expect_tx.shared.b64 _, [%0], %1;" ::"r"(smem_u32(bar)), "r"(bytes) : "memory");
}
__device__ __forceinline__ void mma_bf16x(float (&c)[4], uint32_t a0, uint32_t a1, uint32_t a2, uint32_t a3, uint32_t b0, uint32_t b1) {
  asm volatile("mma.sync.aligned.m16n8k16.row.col.f32.bf16.bf16.f32 {%0,%1,%2,%3}, {%4,%5,%6,%7}, {%8,%9}, {%0,%1,%2,%3};"
               : "+f"(c[0]), "+f"(c[1]), "+f"(c[2]), "+f"(c[3]) : "r"(a0), "r"(a1), "r"(a2), "r"(a3), "r"(b0), "r"(b1));
}
__device__ __forceinline__ float fdivr(float a, float d, float r) {
  float q = a * r;
  float e = fmaf(-q, d, a);
  return fmaf(e, r, q);
}

template <bool FIRST> __device__ __forceinline__ void wgmma32(float (&d)[16], const uint32_t* a, uint64_t desc) {
  if (FIRST) {
    asm volatile("wgmma.mma_async.sync.aligned.m64n32k16.f32.bf16.bf16 {%0,%1,%2,%3,%4,%5,%6,%7,%8,%9,%10,%11,%12,%13,%14,%15}, {%16,%17,%18,%19}, %20, 0, 1, 1, 0;"
                 : "+f"(d[0]), "+f"(d[1]), "+f"(d[2]), "+f"(d[3]), "+f"(d[4]), "+f"(d[5]), "+f"(d[6]), "+f"(d[7]),
                   "+f"(d[8]), "+f"(d[9]), "+f"(d[10]), "+f"(d[11]), "+f"(d[12]), "+f"(d[13]), "+f"(d[14]), "+f"(d[15])
                 : "r"(a[0]), "r"(a[1]), "r"(a[2]), "r"(a[3]), "l"(desc));
  } else {
    asm volatile("wgmma.mma_async.sync.aligned.m64n32k16.f32.bf16.bf16 {%0,%1,%2,%3,%4,%5,%6,%7,%8,%9,%10,%11,%12,%13,%14,%15}, {%16,%17,%18,%19}, %20, 1, 1, 1, 0;"
                 : "+f"(d[0]), "+f"(d[1]), "+f"(d[2]), "+f"(d[3]), "+f"(d[4]), "+f"(d[5]), "+f"(d[6]), "+f"(d[7]),
                   "+f"(d[8]), "+f"(d[9]), "+f"(d[10]), "+f"(d[11]), "+f"(d[12]), "+f"(d[13]), "+f"(d[14]), "+f"(d[15])
                 : "r"(a[0]), "r"(a[1]), "r"(a[2]), "r"(a[3]), "l"(desc));
  }
}

template <int G> __device__ __forceinline__ void load_a(uint32_t (&a)[8], const uint32_t* tp) {
#pragma unroll
  for (int q = 0; q < 2; q++) {
    const int e = 2 * G + q;
    a[4 * q + 0] = tp[-64 * e];
    a[4 * q + 1] = tp[-64 * e - 32];
    a[4 * q + 2] = tp[-64 * e + 4];
    a[4 * q + 3] = tp[-64 * e - 28];
  }
}
__device__ __forceinline__ void load_a_all(uint32_t (&a)[8][8], const uint32_t* tp) {
  load_a<0>(a[0], tp); load_a<1>(a[1], tp); load_a<2>(a[2], tp); load_a<3>(a[3], tp);
  load_a<4>(a[4], tp); load_a<5>(a[5], tp); load_a<6>(a[6], tp); load_a<7>(a[7], tp);
}
template <int G> __device__ __forceinline__ void issue_g(float (&acc)[8][16], uint32_t (&a)[8], uint64_t desc0) {
  wg_fence();
#pragma unroll
  for (int q = 0; q < 2; q++) {
#pragma unroll
    for (int b = G; b < 8; b++) {
      const int delta = 2 * b - (2 * G + q);
      if (G == 0 && q == 0) wgmma32<true>(acc[b], &a[4 * q], desc0 + (uint64_t)(int64_t)(16 * delta));
      else wgmma32<false>(acc[b], &a[4 * q], desc0 + (uint64_t)(int64_t)(16 * delta));
    }
  }
  wg_commit();
}
template <int B> __device__ __forceinline__ void fence_blk(float (&acc)[8][16]) {
#pragma unroll
  for (int i = 0; i < 16; i++) asm volatile("" : "+f"(acc[B][i])::"memory");
}
__device__ __forceinline__ void fence_a(uint32_t (&a)[8]) {
#pragma unroll
  for (int i = 0; i < 8; i++) asm volatile("" : "+r"(a[i])::"memory");
}
template <int B> __device__ __forceinline__ void sts_blk(float (&acc)[8][16], float* zw, int off_even, int off_odd) {
#pragma unroll
  for (int jj = 0; jj < 4; jj++) {
    const int j = 4 * B + jj;
    float p0 = acc[B][4 * jj + 0], p1 = acc[B][4 * jj + 1];
    if (jj > 0) { p0 += acc[B][4 * (jj - 1) + 2]; p1 += acc[B][4 * (jj - 1) + 3]; }
    else if (B > 0) { p0 += acc[B > 0 ? B - 1 : 0][14]; p1 += acc[B > 0 ? B - 1 : 0][15]; }
    zw[64 * j + off_even] = p0;
    zw[64 * j + off_odd] = p1;
  }
}
__device__ __forceinline__ int tab_off(int c) { return c == 4 ? 0 : (c + 1) * 2 * TABW + (c >= 2 ? 1024 : 0); }
__device__ __forceinline__ int tile_perm(int ch) { return ch ^ (((ch >> 3) & 3) << 1); }

__device__ __forceinline__ void wait_ctr(const unsigned int* ctr, uint32_t target) {
  uint32_t v;
  int it = 0;
  do {
    asm volatile("ld.acquire.gpu.global.u32 %0, [%1];" : "=r"(v) : "l"(ctr) : "memory");
  } while ((int)(v - target) < 0 && ++it < SPIN_LIMIT);
}

__device__ __forceinline__ float2 row_part_stats(const uint32_t (&x)[20]) {
  float cs[5][4];
#pragma unroll
  for (int k = 0; k < 5; k++) {
    cs[k][0] = cs[k][1] = cs[k][2] = cs[k][3] = 0.f;
    mma_bf16x(cs[k], x[4 * k + 0], x[4 * k + 2], x[4 * k + 1], x[4 * k + 3], 0x3F803F80u, 0x3F803F80u);
  }
  const float mean = ((((cs[0][0] + cs[0][2]) + (cs[1][0] + cs[1][2])) + ((cs[2][0] + cs[2][2]) + (cs[3][0] + cs[3][2]))) + (cs[4][0] + cs[4][2])) * (1.f / 160.f);
  float m2a = 0.f, m2b = 0.f, m2c = 0.f, m2d = 0.f;
#pragma unroll
  for (int i = 0; i < 20; i += 2) {
    const float a = lo_f(x[i]) - mean, b = hi_f(x[i]) - mean, c = lo_f(x[i + 1]) - mean, d = hi_f(x[i + 1]) - mean;
    m2a = fmaf(a, a, m2a); m2b = fmaf(b, b, m2b); m2c = fmaf(c, c, m2c); m2d = fmaf(d, d, m2d);
  }
  float m2 = (m2a + m2b) + (m2c + m2d);
  m2 += __shfl_xor_sync(0xffffffffu, m2, 1);
  m2 += __shfl_xor_sync(0xffffffffu, m2, 2);
  return make_float2(mean, m2);
}
template <bool EXACT> __device__ __forceinline__ void row_normalize(const float4* st, const uint32_t (&x)[20], uint32_t (&y)[20]) {
  const float4 p = st[0], q = st[1];
  const float mean = ((p.x + p.z) + (q.x + q.z)) * 0.25f;
  const float d0 = p.x - mean, d1 = p.z - mean, d2 = q.x - mean, d3 = q.z - mean;
  const float m2 = ((p.y + p.w) + (q.y + q.w)) + 160.f * ((d0 * d0 + d1 * d1) + (d2 * d2 + d3 * d3));
  const float hd = rbf(sqrtf(rbf(rbf(m2 * (1.f / D_)) + 1e-5f)));
  const float hr = __frcp_rn(hd);
  const bf162 hm2 = __float2bfloat162_rn(mean);
#pragma unroll
  for (int i = 0; i < 20; i++) {
    const uint32_t d = b2u(__hsub2_rn(u2b(x[i]), hm2));
    y[i] = EXACT ? pack2(fdivr(lo_f(d), hd, hr), fdivr(hi_f(d), hd, hr)) : pack2(lo_f(d) * hr, hi_f(d) * hr);
  }
}

__device__ __forceinline__ void gather_kv(Smem& sm, int c0, int tid) {
  if (HINT1) mbar_wait(&sm.mbarc);
  uint4 v[4];
  uint4* src = g_kv + c0 * 256 + tid;
#pragma unroll
  for (int i = 0; i < 4; i++) if (i < 3 || tid >= 256) v[i] = ld_poll4(src + NTHR * i - (i == 3 ? 256 : 0));
#pragma unroll
  for (int i = 0; i < 4; i++) {
    if (i < 3 || tid >= 256) {
      const int t = tid + NTHR * i - (i == 3 ? 256 : 0);
      int it = 0;
      while (!ready4(v[i]) && ++it < SPIN_LIMIT) { __nanosleep(POLL_NS); v[i] = ld_poll4(g_kv + c0 * 256 + t); }
      *reinterpret_cast<uint4*>(&sm.u[t >> 8][UPAD + (t & 255) * 8]) = make_uint4(~v[i].x, ~v[i].y, ~v[i].z, ~v[i].w);
    }
  }
  asm volatile("fence.proxy.async.shared::cta;" ::: "memory");
  __syncthreads();
}

__global__ void __launch_bounds__(NTHR, 1)
fused_kernel(const __grid_constant__ CUtensorMap tmg, const __grid_constant__ CUtensorMap tmu,
             const __grid_constant__ CUtensorMap tmd, const bf16* __restrict__ gq, const bf16* __restrict__ gk, const bf16* __restrict__ gv,
             const bf16* __restrict__ gsk, const bf16* __restrict__ gh, const bf16* __restrict__ gD,
             const bf16* __restrict__ gwr, bf16* __restrict__ gout) {
  extern __shared__ __align__(128) unsigned char smraw[];
  Smem& sm = *reinterpret_cast<Smem*>(smraw);
  const int tid = threadIdx.x;
  const int cta = blockIdx.x;
  const int c0 = cta * CPC;
  const int lane = tid & 31;
  const int wid = tid >> 5;
  STAMP(0);
  const long long tstart = clock64();

  {
    uint4* hs = reinterpret_cast<uint4*>(&sm.z[0][0][0]);
    const int oc = tid >> 2;
    const int r0 = cta * 16 + (tid & 3) * 4;
    uint4 kk[7], vv[4], sk[4];
    if (tid < 320) {
      const uint4* kp = reinterpret_cast<const uint4*>(gk) + (size_t)r0 * 80 + oc;
      const uint4* vp = reinterpret_cast<const uint4*>(gv) + (size_t)r0 * 80 + oc;
#pragma unroll
      for (int i = 0; i < 7; i++) kk[i] = (i >= 3 || r0 > 0) ? __ldg(kp + (i - 3) * 80) : make_uint4(0, 0, 0, 0);
#pragma unroll
      for (int i = 0; i < 4; i++) vv[i] = __ldg(vp + i * 80);
#pragma unroll
      for (int i = 0; i < 4; i++) sk[i] = __ldg(reinterpret_cast<const uint4*>(gsk) + oc * 4 + i);
    } else if (tid == 320) {
      asm volatile("mbarrier.init.shared.b64 [%0], 1;" ::"r"(smem_u32(&sm.mbarh)) : "memory");
      asm volatile("mbarrier.init.shared.b64 [%0], 1;" ::"r"(smem_u32(&sm.mbar)) : "memory");
      asm volatile("mbarrier.init.shared.b64 [%0], 1;" ::"r"(smem_u32(&sm.mbarw)) : "memory");
      asm volatile("mbarrier.init.shared.b64 [%0], 1;" ::"r"(smem_u32(&sm.mbarc)) : "memory");
      asm volatile("mbarrier.init.shared.b64 [%0], 1;" ::"r"(smem_u32(&sm.mbary)) : "memory");
      asm volatile("fence.proxy.async.shared::cta;" ::: "memory");
    } else if (tid == 352) {
      uint32_t v1, v2, v3;
      asm volatile("ld.relaxed.gpu.global.u32 %0, [%1];" : "=r"(v1) : "l"(&g_ctr) : "memory");
      asm volatile("ld.relaxed.gpu.global.u32 %0, [%1];" : "=r"(v2) : "l"(&g_ctr2) : "memory");
      asm volatile("ld.relaxed.gpu.global.u32 %0, [%1];" : "=r"(v3) : "l"(&g_ctr3) : "memory");
      sm.target = (v1 / NCTA + 1u) * NCTA;
      sm.target2 = (v2 / NCTA + 1u) * NCTA;
      sm.target3 = (v3 / NCTA + 1u) * NCTA;
    }
    if (tid < 320) bar_sync(6, 384); else { bar_arrive(6, 384); bar_sync(5, 64); }
    STAMP(9);
    if (tid < 320) {
      uint32_t o[4][4];
#pragma unroll
      for (int p = 0; p < 4; p++) {
        const bf162 w0 = u2b(__byte_perm(sk[p].x, sk[p].z, 0x5410)), w1 = u2b(__byte_perm(sk[p].x, sk[p].z, 0x7632));
        const bf162 w2 = u2b(__byte_perm(sk[p].y, sk[p].w, 0x5410)), w3 = u2b(__byte_perm(sk[p].y, sk[p].w, 0x7632));
        uint32_t kv[4];
#pragma unroll
        for (int i = 0; i < 4; i++) {
          const uint32_t k0 = p == 0 ? kk[i].x : p == 1 ? kk[i].y : p == 2 ? kk[i].z : kk[i].w;
          const uint32_t k1 = p == 0 ? kk[i + 1].x : p == 1 ? kk[i + 1].y : p == 2 ? kk[i + 1].z : kk[i + 1].w;
          const uint32_t k2 = p == 0 ? kk[i + 2].x : p == 1 ? kk[i + 2].y : p == 2 ? kk[i + 2].z : kk[i + 2].w;
          const uint32_t k3 = p == 0 ? kk[i + 3].x : p == 1 ? kk[i + 3].y : p == 2 ? kk[i + 3].z : kk[i + 3].w;
          const uint32_t vx = p == 0 ? vv[i].x : p == 1 ? vv[i].y : p == 2 ? vv[i].z : vv[i].w;
          bf162 a = __hmul2_rn(u2b(k0), w3);
          a = __hadd2_rn(a, __hmul2_rn(u2b(k1), w2));
          a = __hadd2_rn(a, __hmul2_rn(u2b(k2), w1));
          a = __hadd2_rn(a, __hmul2_rn(u2b(k3), w0));
          kv[i] = b2u(__hmul2_rn(a, u2b(vx)));
        }
        o[p][0] = enc(__byte_perm(kv[0], kv[1], 0x5410)); o[p][1] = enc(__byte_perm(kv[2], kv[3], 0x5410));
        o[p][2] = enc(__byte_perm(kv[0], kv[1], 0x7632)); o[p][3] = enc(__byte_perm(kv[2], kv[3], 0x7632));
      }
      uint2* dst = reinterpret_cast<uint2*>(g_kv) + (size_t)(oc * 8) * 512 + (r0 >> 2);
#pragma unroll
      for (int p = 0; p < 4; p++) {
        st_pub2(dst + (2 * p) * 512, o[p][0], o[p][1]);
        st_pub2(dst + (2 * p + 1) * 512, o[p][2], o[p][3]);
      }
      STAMP(10);
      if (wid == 0) bar_sync(4, 320); else bar_arrive(4, 320);
      if (tid == 0) {
        asm volatile("red.relaxed.gpu.global.add.u32 [%0], 1;" ::"l"(&g_ctr2) : "memory");
      }
      __syncwarp();
    } else {
      const int t0 = tid - 320;
      const uint4 zz = make_uint4(0, 0, 0, 0);
      if (tid == 320) {
        while (clock64() - tstart < H_DELAY) {}
        mbar_expect(&sm.mbarh, CPC * S_ * 2);
        bulk_g2s(hs, gh + (size_t)c0 * S_, CPC * S_ * 2, &sm.mbarh);
      }
      __syncwarp();
      for (int t = t0; t < CPC * 17; t += 64) *reinterpret_cast<uint4*>(&sm.u[t / 17][(t % 17) * 8]) = zz;
      if (t0 < 40) *reinterpret_cast<uint4*>(&sm.tabA[0][0][0] + tab_off(t0 >> 3) + ((t0 >> 2) & 1) * TABW + 1024 + 4 * (t0 & 3)) = zz;
      while (clock64() - tstart < C_DELAY) {}
      (&g_cand[cta][0][0])[t0] = zz;
      (&g_cand[cta][0][0])[64 + t0] = zz;
      if (t0 < 32) (&g_cand[cta][0][0])[128 + t0] = zz;
      else reinterpret_cast<uint4*>(&g_keys[cta][0])[t0 - 32] = zz;
      if (cta >= N1 && cta < N1 + N2) {
#pragma unroll
        for (int i = 0; i < 3; i++) g_act[cta - N1][t0 + 64 * i] = zz;
      }
    }
    mbar_wait(&sm.mbarh);
#pragma unroll
    for (int i = 0; i < 4; i++) {
      const int t = (NTHR - 1 - tid) + NTHR * i;
      if (t < CPC * 256) {
        uint32_t* tb = &sm.tabA[0][0][0] + tab_off(t >> 8) + (255 - (t & 255)) * 4;
        const uint4 h = hs[t];
        const uint32_t hp = (t & 255) ? reinterpret_cast<const uint32_t*>(hs)[4 * t - 1] : 0u;
        uint4 r1, rr;
        r1.x = __byte_perm(h.w, 0, 0x1032); r1.y = __byte_perm(h.z, 0, 0x1032);
        r1.z = __byte_perm(h.y, 0, 0x1032); r1.w = __byte_perm(h.x, 0, 0x1032);
        rr.x = __byte_perm(h.w, h.z, 0x7610); rr.y = __byte_perm(h.z, h.y, 0x7610);
        rr.z = __byte_perm(h.y, h.x, 0x7610); rr.w = __byte_perm(h.x, hp, 0x7610);
        *reinterpret_cast<uint4*>(tb) = rr;
        *reinterpret_cast<uint4*>(tb + TABW) = r1;
      }
    }
    STAMP(12);
  }
  __syncthreads();

  const int wg = __shfl_sync(0xffffffffu, tid >> 7, 0);
  const int wtid = tid & 127;
  uint4* tile = reinterpret_cast<uint4*>(&sm.tabB[0][0][0]);
  if (wg < 2) {
    asm volatile("setmaxnreg.inc.sync.aligned.u32 224;");
    const int w = (tid >> 5) & 3, g = lane >> 2, tq = lane & 3;
    float* zw = sm.z[wg][w];
    const int sw = 3 * (((tq + w) >> 1) & 1);
    const int off_even = 16 * (tq + w) + 4 * ((0 + (g >> 2)) ^ sw) + (g & 3);
    const int off_odd = 16 * (tq + w) + 4 * ((2 + (g >> 2)) ^ sw) + (g & 3);
    uint32_t a[8][8];
    const uint32_t* tp0 = &sm.tabA[0][g & 1][1019 - 8 * w - (g >> 1) + tq];
    load_a_all(a, tp0 + tab_off(wg));
    float acc[8][16];
#pragma unroll
    for (int b = 0; b < 8; b++)
#pragma unroll
      for (int i = 0; i < 16; i++) acc[b][i] = 0.f;
    gather_kv(sm, c0, tid);
    STAMP(1);
#pragma unroll 1
    for (int c = wg; c < CPC; c += 2) {
      const uint64_t desc = (uint64_t)((smem_u32(&sm.u[c][UPAD - 8]) & 0x3FFFF) >> 4) | ((uint64_t)1 << 16) | ((uint64_t)8 << 32);
      CST(c, 0);
      if (c > 0) bar_sync(1 + wg, 256);
      issue_g<0>(acc, a[0], desc);
      CST(c, 1);
      issue_g<1>(acc, a[1], desc);
      if (SIGPOS == 1 && c + 1 < CPC) bar_arrive(1 + (wg ^ 1), 256);
      issue_g<2>(acc, a[2], desc);
      if (SIGPOS == 2 && c + 1 < CPC) bar_arrive(1 + (wg ^ 1), 256);
      issue_g<3>(acc, a[3], desc);
      if (SIGPOS == 3 && c + 1 < CPC) bar_arrive(1 + (wg ^ 1), 256);
      issue_g<4>(acc, a[4], desc);
      if (SIGPOS == 4 && c + 1 < CPC) bar_arrive(1 + (wg ^ 1), 256);
      issue_g<5>(acc, a[5], desc);
      if (SIGPOS == 5 && c + 1 < CPC) bar_arrive(1 + (wg ^ 1), 256);
      issue_g<6>(acc, a[6], desc);
      if (SIGPOS == 6 && c + 1 < CPC) bar_arrive(1 + (wg ^ 1), 256);
      issue_g<7>(acc, a[7], desc);
      CST(c, 2);
      if (c >= 2) bar_sync(5 + wg, 256);
      wg_wait<4>();
      fence_blk<0>(acc); fence_blk<1>(acc); fence_blk<2>(acc); fence_blk<3>(acc);
      sts_blk<0>(acc, zw, off_even, off_odd);
      sts_blk<1>(acc, zw, off_even, off_odd);
      sts_blk<2>(acc, zw, off_even, off_odd);
      sts_blk<3>(acc, zw, off_even, off_odd);
      bar_arrive(9 + wg, 256);
      CST(c, 3);
      wg_wait<0>();
      fence_blk<4>(acc); fence_blk<5>(acc); fence_blk<6>(acc); fence_blk<7>(acc);
#pragma unroll
      for (int i = 0; i < 8; i++) fence_a(a[i]);
      sts_blk<4>(acc, zw, off_even, off_odd);
      sts_blk<5>(acc, zw, off_even, off_odd);
      sts_blk<6>(acc, zw, off_even, off_odd);
      sts_blk<7>(acc, zw, off_even, off_odd);
      bar_arrive(3 + wg, 256);
      CST(c, 4);
      if (c + 2 < CPC) load_a_all(a, tp0 + tab_off(c + 2));
    }
    STAMP(2 + wg);
    asm volatile("setmaxnreg.dec.sync.aligned.u32 168;");
  } else {
    asm volatile("setmaxnreg.dec.sync.aligned.u32 56;");
    if (((wtid & 15) >> 2) < ((wtid >> 4) & 3))
      *reinterpret_cast<uint4*>(&sm.z[wtid >> 6][(wtid >> 4) & 3][(wtid & 15) * 4]) = make_uint4(0, 0, 0, 0);
    if (wtid == 96) {
      __threadfence();
      asm volatile("red.relaxed.gpu.global.add.u32 [%0], 1;" ::"l"(&g_ctr) : "memory");
    }
    if (wtid == 64) {
      const unsigned target = sm.target2;
      uint32_t v;
      int it = 0;
      do {
        asm volatile("ld.relaxed.gpu.global.u32 %0, [%1];" : "=r"(v) : "l"(&g_ctr2) : "memory");
      } while ((int)(v - target) < 0 && ++it < SPIN_LIMIT);
      asm volatile("mbarrier.arrive.shared.b64 _, [%0];" ::"r"(smem_u32(&sm.mbarc)) : "memory");
    }
    __syncwarp();
    gather_kv(sm, c0, tid);
#pragma unroll
    for (int i = 0; i < 10; i++) g_kv[c0 * 256 + wtid + 128 * i] = make_uint4(0, 0, 0, 0);
    if (wtid == 96) wait_ctr(&g_ctr, sm.target);
    __syncwarp();
    if (wtid == 32) {
      const uint32_t mw = smem_u32(&sm.mbarw);
      mbar_expect(&sm.mbar, 17 * D_ * 2);
#pragma unroll 1
      for (int r = 0; r < 16; r++) bulk_g2s(&sm.q[r][0], gq + (size_t)(cta * 16 + r) * D_, D_ * 2, &sm.mbar);
      bulk_g2s(&sm.wr[0], gwr, D_ * 2, &sm.mbar);
      if (cta < N1) {
        asm volatile("mbarrier.arrive.expect_tx.shared.b64 _, [%0], %1;" ::"r"(mw), "r"(3840 * 16) : "memory");
#pragma unroll 1
        for (int i = 0; i < 4; i++) {
          asm volatile("cp.async.bulk.tensor.2d.shared::cluster.global.mbarrier::complete_tx::bytes [%0], [%1, {%3, %4}], [%2];" ::"r"(smem_u32(&sm.w[i * 480])),
                       "l"(&tmg), "r"(mw), "r"(cta * 24), "r"(i * 160) : "memory");
          asm volatile("cp.async.bulk.tensor.2d.shared::cluster.global.mbarrier::complete_tx::bytes [%0], [%1, {%3, %4}], [%2];" ::"r"(smem_u32(&sm.w[1920 + i * 480])),
                       "l"(&tmu), "r"(mw), "r"(cta * 24), "r"(i * 160) : "memory");
        }
      } else if (cta < N1 + N2) {
        asm volatile("mbarrier.arrive.expect_tx.shared.b64 _, [%0], %1;" ::"r"(mw), "r"(3072 * 16) : "memory");
#pragma unroll 1
        for (int i = 0; i < 6; i++)
          asm volatile("cp.async.bulk.tensor.2d.shared::cluster.global.mbarrier::complete_tx::bytes [%0], [%1, {%3, %4}], [%2];" ::"r"(smem_u32(&sm.w[i * 512])),
                       "l"(&tmd), "r"(mw), "r"((cta - N1) * 16), "r"(i * 256) : "memory");
      }
    }
    const int rpb = wtid >> 1, re2 = wtid & 1;
    const int rsw = 3 * ((rpb >> 1) & 1);
    const int roff0 = 16 * rpb + 4 * ((2 * re2 + 0) ^ rsw);
    const int roff1 = 16 * rpb + 4 * ((2 * re2 + 1) ^ rsw);
    const uint32_t dvl = reinterpret_cast<const unsigned short*>(gD)[c0 + (lane < CPC ? lane : 0)];
#pragma unroll 1
    for (int c = 0; c < CPC; c++) {
      const int zg = c & 1;
      const uint32_t dvc = __shfl_sync(0xffffffffu, dvl, c);
      const bf162 d2 = u2b(dvc | (dvc << 16));
      CST(c, 5);
#pragma unroll
      for (int half = 0; half < 2; half++) {
        bar_sync((half ? 3 : 9) + zg, 256);
        const float* zb = sm.z[zg][0] + half * 1024;
        float4 x[4][2];
#pragma unroll
        for (int ww = 0; ww < 4; ww++) {
          x[ww][0] = *reinterpret_cast<const float4*>(zb + ww * ZPB * 16 + roff0);
          x[ww][1] = *reinterpret_cast<const float4*>(zb + ww * ZPB * 16 + roff1);
        }
        const int sidx = half * 1024 + wtid * 8;
        const uint4 kvv = *reinterpret_cast<const uint4*>(&sm.u[c][UPAD + sidx]);
        if (half == 1 && c + 2 < CPC) bar_arrive(5 + zg, 256);
        uint4 o;
        o.x = pack2((x[0][0].x + x[1][0].x) + (x[2][0].x + x[3][0].x), (x[0][0].y + x[1][0].y) + (x[2][0].y + x[3][0].y));
        o.y = pack2((x[0][0].z + x[1][0].z) + (x[2][0].z + x[3][0].z), (x[0][0].w + x[1][0].w) + (x[2][0].w + x[3][0].w));
        o.z = pack2((x[0][1].x + x[1][1].x) + (x[2][1].x + x[3][1].x), (x[0][1].y + x[1][1].y) + (x[2][1].y + x[3][1].y));
        o.w = pack2((x[0][1].z + x[1][1].z) + (x[2][1].z + x[3][1].z), (x[0][1].w + x[1][1].w) + (x[2][1].w + x[3][1].w));
        o.x = b2u(__hadd2_rn(u2b(o.x), __hmul2_rn(u2b(kvv.x), d2)));
        o.y = b2u(__hadd2_rn(u2b(o.y), __hmul2_rn(u2b(kvv.y), d2)));
        o.z = b2u(__hadd2_rn(u2b(o.z), __hmul2_rn(u2b(kvv.z), d2)));
        o.w = b2u(__hadd2_rn(u2b(o.w), __hmul2_rn(u2b(kvv.w), d2)));
        st_pub4(g_y2 + ((64 * half + rpb) * 640 + c0 + c) * 2 + re2, enc4(o));
        CST(c, 6 + half);
      }
    }
    if (wid == 11) bar_sync(8, 128); else bar_arrive(8, 128);
    STAMP(4);
    asm volatile("setmaxnreg.inc.sync.aligned.u32 168;");
  }

  if (tid == 352) {
    asm volatile("red.relaxed.gpu.global.add.u32 [%0], 1;" ::"l"(&g_ctr3) : "memory");
    wait_ctr(&g_ctr3, sm.target3);
    asm volatile("mbarrier.arrive.shared.b64 _, [%0];" ::"r"(smem_u32(&sm.mbary)) : "memory");
  }
  __syncwarp();
  if (ABL == 4) { mbar_wait(&sm.mbary); for (int i = tid; i < 1280; i += NTHR) g_y2[cta * 1280 + i] = make_uint4(0, 0, 0, 0); if (cta < N1 + N2) mbar_wait(&sm.mbarw); mbar_wait(&sm.mbar); return; }
  RT(0);
  const int g = lane >> 2, tq = lane & 3;
  const int hh = wid & 1, gqi = wid >> 1;
  const int row = hh * 8 + g;
  uint32_t hreg[20], hnreg[20];
  {
    const uint4* src = g_y2 + cta * 1280 + tid;
    uint4 v[4];
    if (wid < 8) {
      mbar_wait(&sm.mbar);
#pragma unroll
      for (int k = 0; k < 5; k++) {
        const uint4 qv4 = *reinterpret_cast<const uint4*>(&sm.q[row][32 * (5 * gqi + k) + 8 * tq]);
        hreg[4 * k] = qv4.x; hreg[4 * k + 1] = qv4.y; hreg[4 * k + 2] = qv4.z; hreg[4 * k + 3] = qv4.w;
      }
      const float2 ps = row_part_stats(hreg);
      if (tq == 0) sm.stq[row][gqi] = ps;
      bar_sync(7, 256);
      row_normalize<false>(reinterpret_cast<const float4*>(sm.stq[row]), hreg, hnreg);
    }
    RT(1);
    if (HINT2) mbar_wait(&sm.mbary);
    RT(2);
#pragma unroll
    for (int i = 0; i < 4; i++) if (i < 3 || tid < 128) v[i] = ld_poll4(src + NTHR * i);
    int it = 0;
    bool all;
    do {
      all = true;
#pragma unroll
      for (int i = 0; i < 4; i++)
        if ((i < 3 || tid < 128) && !ready4(v[i])) { v[i] = ld_poll4(src + NTHR * i); all = false; }
    } while (!all && ++it < SPIN_LIMIT);
#pragma unroll
    for (int i = 0; i < 4; i++) {
      if (i < 3 || tid < 128) {
        const int t = tid + NTHR * i;
        tile[(t & 1) * 640 + tile_perm(t >> 1)] = make_uint4(~v[i].x, ~v[i].y, ~v[i].z, ~v[i].w);
      }
    }
  }
  __syncthreads();
  STAMP(5);
  RT(3);
  if (ABL == 3) { for (int i = tid; i < 1280; i += NTHR) g_y2[cta * 1280 + i] = make_uint4(0, 0, 0, 0); if (cta < N1 + N2) mbar_wait(&sm.mbarw); return; }

  if (wid < 8) {
#pragma unroll
    for (int k = 0; k < 5; k++) {
      const int base = 32 * (5 * gqi + k);
      const int lch = base + 8 * ((lane & 7) >> 1) + 2 * (lane >> 3) + (lane & 1);
      uint32_t y[4];
      asm volatile("ldmatrix.sync.aligned.m8n8.x4.trans.shared.b16 {%0,%1,%2,%3}, [%4];"
                   : "=r"(y[0]), "=r"(y[1]), "=r"(y[2]), "=r"(y[3]) : "r"(smem_u32(&tile[hh * 640 + tile_perm(lch)])) : "memory");
#pragma unroll
      for (int i = 0; i < 4; i++)
        hreg[4 * k + i] = b2u(__hadd2_rn(u2b(hreg[4 * k + i]), __hmul2_rn(u2b(hnreg[4 * k + i]), u2b(y[i]))));
    }
    RT(4);
    const float2 ps = row_part_stats(hreg);
    if (tq == 0) sm.st[row][gqi] = ps;
    STAMP(13);
    RT(5);
    bar_sync(7, 256);
    row_normalize<false>(reinterpret_cast<const float4*>(sm.st[row]), hreg, hnreg);
    RT(6);
    float cr[5][4];
#pragma unroll
    for (int k = 0; k < 5; k++) {
      cr[k][0] = cr[k][1] = cr[k][2] = cr[k][3] = 0.f;
      const uint4 w4 = sm.wr[4 * (5 * gqi + k) + tq];
      mma_bf16(cr[k], hnreg[4 * k + 0], hnreg[4 * k + 1], w4.x, w4.y);
      mma_bf16(cr[k], hnreg[4 * k + 2], hnreg[4 * k + 3], w4.z, w4.w);
    }
    if (tq == 0) sm.rp[row][gqi] = ((cr[0][0] + cr[1][0]) + (cr[2][0] + cr[3][0])) + cr[4][0];
  }
  STAMP(14);
  RT(7);
  __syncthreads();
  uint32_t best;
  {
    const int rr = lane & 15;
    const float4 rp4 = *reinterpret_cast<const float4*>(sm.rp[rr]);
    const float r = (rp4.x + rp4.y) + (rp4.z + rp4.w);
    const uint32_t bits = __bfloat16_as_ushort(__float2bfloat16_rn(r));
    const uint32_t ord = (bits & 0x8000u) ? (bits ^ 0xFFFFu) : (bits ^ 0x8000u);
    const uint32_t key = (ord << 16) | 0x8000u | (uint32_t)(2047 - (cta * 16 + rr));
    best = __reduce_max_sync(0xffffffffu, key);
  }
  if (wid >= 8) asm volatile("st.relaxed.gpu.global.u32 [%0], %1;" ::"l"(&g_keys[tid - 256][cta]), "r"(best) : "memory");
  STAMP(15);
  RT(8);
  const int brow = (2047 - (int)(best & 0x7FFu)) - cta * 16;
  if (wid < 8 && row == brow) {
#pragma unroll
    for (int k = 0; k < 5; k++)
      st_pub4(&g_cand[cta][0][4 * (5 * gqi + k) + tq], enc4(make_uint4(hnreg[4 * k], hnreg[4 * k + 1], hnreg[4 * k + 2], hnreg[4 * k + 3])));
#pragma unroll
    for (int k = 0; k < 5; k++)
      st_pub4(&g_cand[cta][1][4 * (5 * gqi + k) + tq], enc4(make_uint4(hreg[4 * k], hreg[4 * k + 1], hreg[4 * k + 2], hreg[4 * k + 3])));
  }
#pragma unroll
  for (int i = 0; i < 20; i++) hreg[i] = b2u(__hadd2_rn(u2b(hreg[i]), u2b(hnreg[i])));
  STAMP(6);
  RT(9);
  if (ABL == 2) { for (int i = tid; i < 1280; i += NTHR) g_y2[cta * 1280 + i] = make_uint4(0, 0, 0, 0); if (cta < N1 + N2) mbar_wait(&sm.mbarw); return; }
  if (wid == 11) {
    const uint4* kp = reinterpret_cast<const uint4*>(&g_keys[cta][0]) + lane;
    uint4 v = ld_poll4(kp);
    int it = 0;
    while (!ready4(v) && ++it < SPIN_LIMIT) v = ld_poll4(kp);
    const uint32_t m = max(max(v.x, v.y), max(v.z, v.w));
    const uint32_t wk = __reduce_max_sync(0xffffffffu, m);
    if (lane == 0) sm.win = wk;
  }
  __syncthreads();
  const uint32_t win = sm.win;
  const int wrow = 2047 - (int)(win & 0x7FFu);
  const int wcta = wrow >> 4;
  const bool st_out = wid < 8 && (cta * 16 + row) != wrow;
  uint4* outp = reinterpret_cast<uint4*>(gout + (size_t)(cta * 16 + row) * D_) + 20 * gqi + tq;
  if (cta >= N1) {
    if (st_out) {
#pragma unroll
      for (int k = 0; k < 5; k++) outp[4 * k] = make_uint4(hreg[4 * k], hreg[4 * k + 1], hreg[4 * k + 2], hreg[4 * k + 3]);
    }
  }
  if (cta >= N1 || ABL == 1) {
#pragma unroll
    for (int i = 0; i < 4; i++) if (i < 3 || tid < 128) g_y2[cta * 1280 + tid + NTHR * i] = make_uint4(0, 0, 0, 0);
  }
  STAMP(7);
  RT(10);
  if (ABL == 1) { if (cta < N1 + N2) mbar_wait(&sm.mbarw); return; }
  if (cta < N1 + N2) mbar_wait(&sm.mbarw);
  float* xs = &sm.z[0][0][0];
  float* part = xs + 2048;
  if (cta < N1) {
    if (tid < 80) {
      const uint4 v = poll4(&g_cand[wcta][0][tid]);
      float4* xp = reinterpret_cast<float4*>(xs + tid * 8);
      xp[0] = make_float4(lo_f(v.x), hi_f(v.x), lo_f(v.y), hi_f(v.y));
      xp[1] = make_float4(lo_f(v.z), hi_f(v.z), lo_f(v.w), hi_f(v.w));
    }
    __syncthreads();
    const int m = wid / 6, hc = (wid % 6) >> 1, rs = (wid & 1) * 32 + lane;
    float a[8];
#pragma unroll
    for (int j = 0; j < 8; j++) a[j] = 0.f;
#pragma unroll
    for (int it = 0; it < 10; it++) {
      const int r = rs + 64 * it;
      const uint4 wv = sm.w[m * 1920 + r * 3 + hc];
      const float x = xs[r];
      a[0] = fmaf(x, lo_f(wv.x), a[0]); a[1] = fmaf(x, hi_f(wv.x), a[1]);
      a[2] = fmaf(x, lo_f(wv.y), a[2]); a[3] = fmaf(x, hi_f(wv.y), a[3]);
      a[4] = fmaf(x, lo_f(wv.z), a[4]); a[5] = fmaf(x, hi_f(wv.z), a[5]);
      a[6] = fmaf(x, lo_f(wv.w), a[6]); a[7] = fmaf(x, hi_f(wv.w), a[7]);
    }
    {
      const bool up = lane & 16;
#pragma unroll
      for (int j = 0; j < 4; j++) {
        const float send = up ? a[j] : a[j + 4], keep = up ? a[j + 4] : a[j];
        a[j] = keep + __shfl_xor_sync(0xffffffffu, send, 16);
      }
      const bool up2 = lane & 8;
#pragma unroll
      for (int j = 0; j < 2; j++) {
        const float send = up2 ? a[j] : a[j + 2], keep = up2 ? a[j + 2] : a[j];
        a[j] = keep + __shfl_xor_sync(0xffffffffu, send, 8);
      }
      const bool up3 = lane & 4;
      const float send = up3 ? a[0] : a[1], keep = up3 ? a[1] : a[0];
      a[0] = keep + __shfl_xor_sync(0xffffffffu, send, 4);
      a[0] += __shfl_xor_sync(0xffffffffu, a[0], 2);
      a[0] += __shfl_xor_sync(0xffffffffu, a[0], 1);
      if ((lane & 3) == 0) part[wid * 8 + (lane >> 2)] = a[0];
    }
    __syncthreads();
    if (wid == 0) {
      uint32_t bits = 0;
      if (lane < 24) {
        const int hc2 = lane >> 3, j = lane & 7;
        const float gt = rbf(part[(2 * hc2) * 8 + j] + part[(2 * hc2 + 1) * 8 + j]);
        const float up = rbf(part[(6 + 2 * hc2) * 8 + j] + part[(6 + 2 * hc2 + 1) * 8 + j]);
        const float sg = rbf(gt / (1.f + __expf(-gt)));
        bits = __bfloat16_as_ushort(__float2bfloat16_rn(sg * up));
      }
      const uint32_t nb = __shfl_down_sync(0xffffffffu, bits, 1);
      const uint32_t pw = bits | (nb << 16);
      const uint32_t w1 = __shfl_down_sync(0xffffffffu, pw, 2), w2 = __shfl_down_sync(0xffffffffu, pw, 4), w3 = __shfl_down_sync(0xffffffffu, pw, 6);
      const uint4 mine = enc4(make_uint4(pw, w1, w2, w3));
#pragma unroll
      for (int i = 0; i < 4; i++) {
        const int t = lane + 32 * i;
        const int cons = t / 3, ck = t - 3 * cons;
        uint4 v;
        v.x = __shfl_sync(0xffffffffu, mine.x, 8 * ck); v.y = __shfl_sync(0xffffffffu, mine.y, 8 * ck);
        v.z = __shfl_sync(0xffffffffu, mine.z, 8 * ck); v.w = __shfl_sync(0xffffffffu, mine.w, 8 * ck);
        if (t < 3 * N2) st_pub4(&g_act[cons][cta * 3 + ck], v);
      }
      __syncwarp();
      bar_arrive(7, 384);
    } else {
      bar_sync(7, 384);
    }
#pragma unroll
    for (int i = 0; i < 4; i++) if (i < 3 || tid < 128) g_y2[cta * 1280 + tid + NTHR * i] = make_uint4(0, 0, 0, 0);
    if (st_out) {
#pragma unroll
      for (int k = 0; k < 5; k++) outp[4 * k] = make_uint4(hreg[4 * k], hreg[4 * k + 1], hreg[4 * k + 2], hreg[4 * k + 3]);
    }
  } else if (cta < N1 + N2 && ABL != 6) {
    const int j2 = cta - N1;
    uint4 rowv = make_uint4(0, 0, 0, 0);
    if (tid < 192) {
      const uint4 v = poll4(&g_act[j2][tid]);
      float4* xp = reinterpret_cast<float4*>(xs + tid * 8);
      xp[0] = make_float4(lo_f(v.x), hi_f(v.x), lo_f(v.y), hi_f(v.y));
      xp[1] = make_float4(lo_f(v.z), hi_f(v.z), lo_f(v.w), hi_f(v.w));
    } else if (tid < 196) {
      const int t = tid - 192;
      rowv = poll4(&g_cand[wcta][t >> 1][j2 * 2 + (t & 1)]);
      reinterpret_cast<uint4*>(part + 256)[t] = rowv;
    }
    __syncthreads();
    const int hc = lane & 1, rs = wid * 16 + (lane >> 1);
    float a[8];
#pragma unroll
    for (int j = 0; j < 8; j++) a[j] = 0.f;
#pragma unroll
    for (int it = 0; it < 8; it++) {
      const int r = rs + 192 * it;
      const uint4 wv = sm.w[r * 2 + hc];
      const float x = xs[r];
      a[0] = fmaf(x, lo_f(wv.x), a[0]); a[1] = fmaf(x, hi_f(wv.x), a[1]);
      a[2] = fmaf(x, lo_f(wv.y), a[2]); a[3] = fmaf(x, hi_f(wv.y), a[3]);
      a[4] = fmaf(x, lo_f(wv.z), a[4]); a[5] = fmaf(x, hi_f(wv.z), a[5]);
      a[6] = fmaf(x, lo_f(wv.w), a[6]); a[7] = fmaf(x, hi_f(wv.w), a[7]);
    }
    {
      const bool up = lane & 16;
#pragma unroll
      for (int j = 0; j < 4; j++) {
        const float send = up ? a[j] : a[j + 4], keep = up ? a[j + 4] : a[j];
        a[j] = keep + __shfl_xor_sync(0xffffffffu, send, 16);
      }
      const bool up2 = lane & 8;
#pragma unroll
      for (int j = 0; j < 2; j++) {
        const float send = up2 ? a[j] : a[j + 2], keep = up2 ? a[j + 2] : a[j];
        a[j] = keep + __shfl_xor_sync(0xffffffffu, send, 8);
      }
      const bool up3 = lane & 4;
      const float send = up3 ? a[0] : a[1], keep = up3 ? a[1] : a[0];
      a[0] = keep + __shfl_xor_sync(0xffffffffu, send, 4);
      a[0] += __shfl_xor_sync(0xffffffffu, a[0], 2);
      if ((lane & 2) == 0) part[wid * 16 + hc * 8 + (lane >> 2)] = a[0];
    }
    __syncthreads();
    if (tid < 16) {
      float y = 0.f;
#pragma unroll
      for (int i = 0; i < 12; i++) y += part[i * 16 + tid];
      const uint32_t ord = win >> 16;
      const uint32_t rb = (ord & 0x8000u) ? (ord ^ 0x8000u) : (ord ^ 0xFFFFu);
      const float r = __uint_as_float(rb << 16);
      const float sg = rbf(1.f / (1.f + __expf(-r)));
      const float yy = rbf(rbf(y) * sg);
      const unsigned short* rv = reinterpret_cast<const unsigned short*>(part + 256);
      const float hn = __uint_as_float((uint32_t)rv[tid] << 16), h = __uint_as_float((uint32_t)rv[16 + tid] << 16);
      gout[(size_t)wrow * D_ + j2 * 16 + tid] = __float2bfloat16_rn(h + rbf(hn + yy));
    }
  }
  STAMP(8);
  RT(11);
}

}

typedef CUresult (*EncodeFn)(CUtensorMap*, CUtensorMapDataType, cuuint32_t, void*, const cuuint64_t*, const cuuint64_t*,
                             const cuuint32_t*, const cuuint32_t*, CUtensorMapInterleave, CUtensorMapSwizzle,
                             CUtensorMapL2promotion, CUtensorMapFloatOOBfill);

extern "C" void kernel_launch(void* const* d_in, const int* in_sizes, int n_in, void* d_out, int out_size) {
  (void)in_sizes; (void)n_in; (void)out_size;
  static EncodeFn encode = nullptr;
  static CUtensorMap tmg, tmu, tmd;
  static void* cached[3] = {nullptr, nullptr, nullptr};
  if (!encode) {
    cudaFuncSetAttribute(fused_kernel, cudaFuncAttributeMaxDynamicSharedMemorySize, (int)sizeof(Smem));
    void* fn = nullptr;
    cudaDriverEntryPointQueryResult qr;
    cudaGetDriverEntryPoint("cuTensorMapEncodeTiled", &fn, cudaEnableDefault, &qr);
    encode = (EncodeFn)fn;
  }
  if (cached[0] != d_in[8] || cached[1] != d_in[9] || cached[2] != d_in[10]) {
    const cuuint32_t es[2] = {1, 1};
    {
      const cuuint64_t dims[2] = {F_, D_}, strides[1] = {F_ * 2};
      const cuuint32_t box[2] = {24, 160};
      encode(&tmg, CU_TENSOR_MAP_DATA_TYPE_BFLOAT16, 2, d_in[8], dims, strides, box, es, CU_TENSOR_MAP_INTERLEAVE_NONE,
             CU_TENSOR_MAP_SWIZZLE_NONE, CU_TENSOR_MAP_L2_PROMOTION_NONE, CU_TENSOR_MAP_FLOAT_OOB_FILL_NONE);
      encode(&tmu, CU_TENSOR_MAP_DATA_TYPE_BFLOAT16, 2, d_in[9], dims, strides, box, es, CU_TENSOR_MAP_INTERLEAVE_NONE,
             CU_TENSOR_MAP_SWIZZLE_NONE, CU_TENSOR_MAP_L2_PROMOTION_NONE, CU_TENSOR_MAP_FLOAT_OOB_FILL_NONE);
    }
    {
      const cuuint64_t dims[2] = {D_, F_}, strides[1] = {D_ * 2};
      const cuuint32_t box[2] = {16, 256};
      encode(&tmd, CU_TENSOR_MAP_DATA_TYPE_BFLOAT16, 2, d_in[10], dims, strides, box, es, CU_TENSOR_MAP_INTERLEAVE_NONE,
             CU_TENSOR_MAP_SWIZZLE_NONE, CU_TENSOR_MAP_L2_PROMOTION_NONE, CU_TENSOR_MAP_FLOAT_OOB_FILL_NONE);
    }
    cached[0] = d_in[8]; cached[1] = d_in[9]; cached[2] = d_in[10];
  }
  fused_kernel<<<NCTA, NTHR, sizeof(Smem), cudaStreamPerThread>>>(
      tmg, tmu, tmd, (const bf16*)d_in[0], (const bf16*)d_in[1], (const bf16*)d_in[2], (const bf16*)d_in[3],
      (const bf16*)d_in[4], (const bf16*)d_in[5], (const bf16*)d_in[7], (bf16*)d_out);
}
```

```cpp
#include <cuda_runtime.h>
#include <cuda_bf16.h>
#include <cuda.h>
#include <stdint.h>

namespace {

typedef __nv_bfloat16 bf16;
typedef __nv_bfloat162 bf162;

constexpr int S_ = 2048, D_ = 640, F_ = 1536;
constexpr int NCTA = 128, CPC = 5, NTHR = 384;
constexpr int UPAD = 136, USTR = 2192;
constexpr int TABW = 1040;
constexpr int ZPB = 132;
constexpr int QSTR = 648;
constexpr int N1 = 64;
constexpr int N2 = 40;
constexpr int SPIN_LIMIT = 1 << 19;
constexpr int POLL_NS = 100;

struct __align__(128) Smem {
  uint32_t tabA[3][2][TABW];
  uint32_t extra[1024];
  uint32_t tabB[2][2][TABW];
  bf16 u[CPC][USTR];
  float z[2][4][ZPB * 16];
  bf16 q[16][QSTR];
  alignas(128) uint4 w[3840];
  uint4 wr[80];
  alignas(16) float2 st[16][4];
  alignas(16) float2 stq[16][4];
  alignas(16) float rp[16][4];
  unsigned long long mbar;
  unsigned long long mbarw;
  unsigned long long mbarc;
  unsigned long long mbary;
  unsigned long long mbarh;
  uint32_t target;
  uint32_t target2;
  uint32_t target3;
  uint32_t best;
  uint32_t win;
};

__device__ uint4 g_kv[D_ * S_ / 8];
__device__ uint4 g_y2[D_ * S_ / 8];
__device__ uint32_t g_keys[NCTA][NCTA];
__device__ uint4 g_cand[NCTA][2][80];
__device__ uint4 g_act[N2][F_ / 8];
__device__ unsigned int g_ctr;
__device__ unsigned int g_ctr2;
__device__ unsigned int g_ctr3;

__device__ __forceinline__ uint32_t smem_u32(const void* p) { return (uint32_t)__cvta_generic_to_shared(p); }
__device__ __forceinline__ void wg_fence() { asm volatile("wgmma.fence.sync.aligned;" ::: "memory"); }
__device__ __forceinline__ void wg_commit() { asm volatile("wgmma.commit_group.sync.aligned;" ::: "memory"); }
template <int N> __device__ __forceinline__ void wg_wait() { asm volatile("wgmma.wait_group.sync.aligned %0;" ::"n"(N) : "memory"); }
__device__ __forceinline__ void bar_sync(int id, int n) { asm volatile("bar.sync %0, %1;" ::"r"(id), "r"(n) : "memory"); }
__device__ __forceinline__ void bar_arrive(int id, int n) { asm volatile("bar.arrive %0, %1;" ::"r"(id), "r"(n) : "memory"); }
__device__ __forceinline__ bf162 u2b(uint32_t u) { return *reinterpret_cast<bf162*>(&u); }
__device__ __forceinline__ uint32_t b2u(bf162 b) { return *reinterpret_cast<uint32_t*>(&b); }
__device__ __forceinline__ float lo_f(uint32_t u) { return __uint_as_float(u << 16); }
__device__ __forceinline__ float hi_f(uint32_t u) { return __uint_as_float(u & 0xFFFF0000u); }
__device__ __forceinline__ float rbf(float x) { return __bfloat162float(__float2bfloat16_rn(x)); }
__device__ __forceinline__ uint32_t pack2(float a, float b) { return b2u(__floats2bfloat162_rn(a, b)); }
__device__ __forceinline__ uint32_t enc(uint32_t w) { return max(~w, 1u); }
__device__ __forceinline__ uint4 enc4(uint4 v) { return make_uint4(enc(v.x), enc(v.y), enc(v.z), enc(v.w)); }
__device__ __forceinline__ uint4 ld_poll4(const uint4* p) {
  uint4 v;
  asm volatile("ld.relaxed.gpu.global.v4.u32 {%0,%1,%2,%3}, [%4];" : "=r"(v.x), "=r"(v.y), "=r"(v.z), "=r"(v.w) : "l"(p) : "memory");
  return v;
}
__device__ __forceinline__ bool ready4(uint4 v) { return v.x != 0u && v.y != 0u && v.z != 0u && v.w != 0u; }
__device__ __forceinline__ uint4 poll4(const uint4* p) {
  uint4 v = ld_poll4(p);
  int it = 0;
  while (!ready4(v) && ++it < SPIN_LIMIT) v = ld_poll4(p);
  return make_uint4(~v.x, ~v.y, ~v.z, ~v.w);
}
__device__ __forceinline__ void st_pub4(uint4* p, uint4 v) {
  asm volatile("st.relaxed.gpu.global.v4.u32 [%0], {%1,%2,%3,%4};" ::"l"(p), "r"(v.x), "r"(v.y), "r"(v.z), "r"(v.w) : "memory");
}
__device__ __forceinline__ void st_pub2(uint2* p, uint32_t a, uint32_t b) {
  asm volatile("st.relaxed.gpu.global.v2.u32 [%0], {%1,%2};" ::"l"(p), "r"(a), "r"(b) : "memory");
}
__device__ __forceinline__ void mma_bf16(float (&c)[4], uint32_t a0, uint32_t a2, uint32_t b0, uint32_t b1) {
  asm volatile("mma.sync.aligned.m16n8k16.row.col.f32.bf16.bf16.f32 {%0,%1,%2,%3}, {%4,%5,%6,%5}, {%7,%8}, {%0,%1,%2,%3};"
               : "+f"(c[0]), "+f"(c[1]), "+f"(c[2]), "+f"(c[3]) : "r"(a0), "r"(0u), "r"(a2), "r"(b0), "r"(b1));
}
__device__ __forceinline__ void mbar_wait(const unsigned long long* bar) {
  const uint32_t mb = smem_u32(bar);
  uint32_t ok = 0;
  int it = 0;
  while (!ok && ++it < SPIN_LIMIT)
    asm volatile("{ .reg .pred p; mbarrier.try_wait.parity.shared.b64 p, [%1], 0; selp.u32 %0, 1, 0, p; }" : "=r"(ok) : "r"(mb) : "memory");
}
__device__ __forceinline__ void bulk_g2s(void* dst, const void* src, uint32_t bytes, const unsigned long long* bar) {
  asm volatile("cp.async.bulk.shared::cluster.global.mbarrier::complete_tx::bytes [%0], [%1], %2, [%3];" ::"r"(smem_u32(dst)),
               "l"(src), "r"(bytes), "r"(smem_u32(bar)) : "memory");
}
__device__ __forceinline__ void mbar_expect(const unsigned long long* bar, uint32_t bytes) {
  asm volatile("mbarrier.arrive.expect_tx.shared.b64 _, [%0], %1;" ::"r"(smem_u32(bar)), "r"(bytes) : "memory");
}
__device__ __forceinline__ void mma_bf16x(float (&c)[4], uint32_t a0, uint32_t a1, uint32_t a2, uint32_t a3, uint32_t b0, uint32_t b1) {
  asm volatile("mma.sync.aligned.m16n8k16.row.col.f32.bf16.bf16.f32 {%0,%1,%2,%3}, {%4,%5,%6,%7}, {%8,%9}, {%0,%1,%2,%3};"
               : "+f"(c[0]), "+f"(c[1]), "+f"(c[2]), "+f"(c[3]) : "r"(a0), "r"(a1), "r"(a2), "r"(a3), "r"(b0), "r"(b1));
}
__device__ __forceinline__ float fdivr(float a, float d, float r) {
  float q = a * r;
  float e = fmaf(-q, d, a);
  return fmaf(e, r, q);
}

template <bool FIRST> __device__ __forceinline__ void wgmma32(float (&d)[16], const uint32_t* a, uint64_t desc) {
  if (FIRST) {
    asm volatile("wgmma.mma_async.sync.aligned.m64n32k16.f32.bf16.bf16 {%0,%1,%2,%3,%4,%5,%6,%7,%8,%9,%10,%11,%12,%13,%14,%15}, {%16,%17,%18,%19}, %20, 0, 1, 1, 0;"
                 : "+f"(d[0]), "+f"(d[1]), "+f"(d[2]), "+f"(d[3]), "+f"(d[4]), "+f"(d[5]), "+f"(d[6]), "+f"(d[7]),
                   "+f"(d[8]), "+f"(d[9]), "+f"(d[10]), "+f"(d[11]), "+f"(d[12]), "+f"(d[13]), "+f"(d[14]), "+f"(d[15])
                 : "r"(a[0]), "r"(a[1]), "r"(a[2]), "r"(a[3]), "l"(desc));
  } else {
    asm volatile("wgmma.mma_async.sync.aligned.m64n32k16.f32.bf16.bf16 {%0,%1,%2,%3,%4,%5,%6,%7,%8,%9,%10,%11,%12,%13,%14,%15}, {%16,%17,%18,%19}, %20, 1, 1, 1, 0;"
                 : "+f"(d[0]), "+f"(d[1]), "+f"(d[2]), "+f"(d[3]), "+f"(d[4]), "+f"(d[5]), "+f"(d[6]), "+f"(d[7]),
                   "+f"(d[8]), "+f"(d[9]), "+f"(d[10]), "+f"(d[11]), "+f"(d[12]), "+f"(d[13]), "+f"(d[14]), "+f"(d[15])
                 : "r"(a[0]), "r"(a[1]), "r"(a[2]), "r"(a[3]), "l"(desc));
  }
}

template <int G> __device__ __forceinline__ void load_a(uint32_t (&a)[8], const uint32_t* tp) {
#pragma unroll
  for (int q = 0; q < 2; q++) {
    const int e = 2 * G + q;
    a[4 * q + 0] = tp[-64 * e];
    a[4 * q + 1] = tp[-64 * e - 32];
    a[4 * q + 2] = tp[-64 * e + 4];
    a[4 * q + 3] = tp[-64 * e - 28];
  }
}
__device__ __forceinline__ void load_a_all(uint32_t (&a)[8][8], const uint32_t* tp) {
  load_a<0>(a[0], tp); load_a<1>(a[1], tp); load_a<2>(a[2], tp); load_a<3>(a[3], tp);
  load_a<4>(a[4], tp); load_a<5>(a[5], tp); load_a<6>(a[6], tp); load_a<7>(a[7], tp);
}
template <int G> __device__ __forceinline__ void issue_g(float (&acc)[8][16], uint32_t (&a)[8], uint64_t desc0) {
  wg_fence();
#pragma unroll
  for (int q = 0; q < 2; q++) {
#pragma unroll
    for (int b = G; b < 8; b++) {
      const int delta = 2 * b - (2 * G + q);
      if (G == 0 && q == 0) wgmma32<true>(acc[b], &a[4 * q], desc0 + (uint64_t)(int64_t)(16 * delta));
      else wgmma32<false>(acc[b], &a[4 * q], desc0 + (uint64_t)(int64_t)(16 * delta));
    }
  }
  wg_commit();
}
template <int B> __device__ __forceinline__ void fence_blk(float (&acc)[8][16]) {
#pragma unroll
  for (int i = 0; i < 16; i++) asm volatile("" : "+f"(acc[B][i])::"memory");
}
__device__ __forceinline__ void fence_a(uint32_t (&a)[8]) {
#pragma unroll
  for (int i = 0; i < 8; i++) asm volatile("" : "+r"(a[i])::"memory");
}
template <int B> __device__ __forceinline__ void sts_blk(float (&acc)[8][16], float* zw, int off_even, int off_odd) {
#pragma unroll
  for (int jj = 0; jj < 4; jj++) {
    const int j = 4 * B + jj;
    float p0 = acc[B][4 * jj + 0], p1 = acc[B][4 * jj + 1];
    if (jj > 0) { p0 += acc[B][4 * (jj - 1) + 2]; p1 += acc[B][4 * (jj - 1) + 3]; }
    else if (B > 0) { p0 += acc[B > 0 ? B - 1 : 0][14]; p1 += acc[B > 0 ? B - 1 : 0][15]; }
    zw[64 * j + off_even] = p0;
    zw[64 * j + off_odd] = p1;
  }
}
__device__ __forceinline__ int tab_off(int c) { return c == 4 ? 0 : (c + 1) * 2 * TABW + (c >= 2 ? 1024 : 0); }
__device__ __forceinline__ int tile_perm(int ch) { return ch ^ (((ch >> 3) & 3) << 1); }

__device__ __forceinline__ void wait_ctr(const unsigned int* ctr, uint32_t target) {
  uint32_t v;
  int it = 0;
  do {
    asm volatile("ld.acquire.gpu.global.u32 %0, [%1];" : "=r"(v) : "l"(ctr) : "memory");
  } while ((int)(v - target) < 0 && ++it < SPIN_LIMIT);
}

__device__ __forceinline__ float2 row_part_stats(const uint32_t (&x)[20]) {
  float cs[5][4];
#pragma unroll
  for (int k = 0; k < 5; k++) {
    cs[k][0] = cs[k][1] = cs[k][2] = cs[k][3] = 0.f;
    mma_bf16x(cs[k], x[4 * k + 0], x[4 * k + 2], x[4 * k + 1], x[4 * k + 3], 0x3F803F80u, 0x3F803F80u);
  }
  const float mean = ((((cs[0][0] + cs[0][2]) + (cs[1][0] + cs[1][2])) + ((cs[2][0] + cs[2][2]) + (cs[3][0] + cs[3][2]))) + (cs[4][0] + cs[4][2])) * (1.f / 160.f);
  float m2a = 0.f, m2b = 0.f, m2c = 0.f, m2d = 0.f;
#pragma unroll
  for (int i = 0; i < 20; i += 2) {
    const float a = lo_f(x[i]) - mean, b = hi_f(x[i]) - mean, c = lo_f(x[i + 1]) - mean, d = hi_f(x[i + 1]) - mean;
    m2a = fmaf(a, a, m2a); m2b = fmaf(b, b, m2b); m2c = fmaf(c, c, m2c); m2d = fmaf(d, d, m2d);
  }
  float m2 = (m2a + m2b) + (m2c + m2d);
  m2 += __shfl_xor_sync(0xffffffffu, m2, 1);
  m2 += __shfl_xor_sync(0xffffffffu, m2, 2);
  return make_float2(mean, m2);
}
template <bool EXACT> __device__ __forceinline__ void row_normalize(const float4* st, const uint32_t (&x)[20], uint32_t (&y)[20]) {
  const float4 p = st[0], q = st[1];
  const float mean = ((p.x + p.z) + (q.x + q.z)) * 0.25f;
  const float d0 = p.x - mean, d1 = p.z - mean, d2 = q.x - mean, d3 = q.z - mean;
  const float m2 = ((p.y + p.w) + (q.y + q.w)) + 160.f * ((d0 * d0 + d1 * d1) + (d2 * d2 + d3 * d3));
  const float hd = rbf(sqrtf(rbf(rbf(m2 * (1.f / D_)) + 1e-5f)));
  const float hr = __frcp_rn(hd);
  const bf162 hm2 = __float2bfloat162_rn(mean);
#pragma unroll
  for (int i = 0; i < 20; i++) {
    const uint32_t d = b2u(__hsub2_rn(u2b(x[i]), hm2));
    y[i] = EXACT ? pack2(fdivr(lo_f(d), hd, hr), fdivr(hi_f(d), hd, hr)) : pack2(lo_f(d) * hr, hi_f(d) * hr);
  }
}

__device__ __forceinline__ void gather_kv(Smem& sm, int c0, int tid) {
  mbar_wait(&sm.mbarc);
  uint4 v[4];
  uint4* src = g_kv + c0 * 256 + tid;
#pragma unroll
  for (int i = 0; i < 4; i++) if (i < 3 || tid >= 256) v[i] = ld_poll4(src + NTHR * i - (i == 3 ? 256 : 0));
#pragma unroll
  for (int i = 0; i < 4; i++) {
    if (i < 3 || tid >= 256) {
      const int t = tid + NTHR * i - (i == 3 ? 256 : 0);
      int it = 0;
      while (!ready4(v[i]) && ++it < SPIN_LIMIT) { __nanosleep(POLL_NS); v[i] = ld_poll4(g_kv + c0 * 256 + t); }
      *reinterpret_cast<uint4*>(&sm.u[t >> 8][UPAD + (t & 255) * 8]) = make_uint4(~v[i].x, ~v[i].y, ~v[i].z, ~v[i].w);
    }
  }
  asm volatile("fence.proxy.async.shared::cta;" ::: "memory");
  __syncthreads();
}

__global__ void __launch_bounds__(NTHR, 1)
fused_kernel(const __grid_constant__ CUtensorMap tmg, const __grid_constant__ CUtensorMap tmu,
             const __grid_constant__ CUtensorMap tmd, const bf16* __restrict__ gq, const bf16* __restrict__ gk, const bf16* __restrict__ gv,
             const bf16* __restrict__ gsk, const bf16* __restrict__ gh, const bf16* __restrict__ gD,
             const bf16* __restrict__ gwr, bf16* __restrict__ gout) {
  extern __shared__ __align__(128) unsigned char smraw[];
  Smem& sm = *reinterpret_cast<Smem*>(smraw);
  const int tid = threadIdx.x;
  const int cta = blockIdx.x;
  const int c0 = cta * CPC;
  const int lane = tid & 31;
  const int wid = tid >> 5;

  {
    uint4* hs = reinterpret_cast<uint4*>(&sm.z[0][0][0]);
    const int oc = tid >> 2;
    const int r0 = cta * 16 + (tid & 3) * 4;
    uint4 kk[7], vv[4], sk[4];
    if (tid < 320) {
      const uint4* kp = reinterpret_cast<const uint4*>(gk) + (size_t)r0 * 80 + oc;
      const uint4* vp = reinterpret_cast<const uint4*>(gv) + (size_t)r0 * 80 + oc;
#pragma unroll
      for (int i = 0; i < 7; i++) kk[i] = (i >= 3 || r0 > 0) ? __ldg(kp + (i - 3) * 80) : make_uint4(0, 0, 0, 0);
#pragma unroll
      for (int i = 0; i < 4; i++) vv[i] = __ldg(vp + i * 80);
#pragma unroll
      for (int i = 0; i < 4; i++) sk[i] = __ldg(reinterpret_cast<const uint4*>(gsk) + oc * 4 + i);
    } else if (tid == 320) {
      asm volatile("mbarrier.init.shared.b64 [%0], 1;" ::"r"(smem_u32(&sm.mbarh)) : "memory");
      asm volatile("mbarrier.init.shared.b64 [%0], 1;" ::"r"(smem_u32(&sm.mbar)) : "memory");
      asm volatile("mbarrier.init.shared.b64 [%0], 1;" ::"r"(smem_u32(&sm.mbarw)) : "memory");
      asm volatile("mbarrier.init.shared.b64 [%0], 1;" ::"r"(smem_u32(&sm.mbarc)) : "memory");
      asm volatile("mbarrier.init.shared.b64 [%0], 1;" ::"r"(smem_u32(&sm.mbary)) : "memory");
      asm volatile("fence.proxy.async.shared::cta;" ::: "memory");
    } else if (tid == 352) {
      uint32_t v1, v2, v3;
      asm volatile("ld.relaxed.gpu.global.u32 %0, [%1];" : "=r"(v1) : "l"(&g_ctr) : "memory");
      asm volatile("ld.relaxed.gpu.global.u32 %0, [%1];" : "=r"(v2) : "l"(&g_ctr2) : "memory");
      asm volatile("ld.relaxed.gpu.global.u32 %0, [%1];" : "=r"(v3) : "l"(&g_ctr3) : "memory");
      sm.target = (v1 / NCTA + 1u) * NCTA;
      sm.target2 = (v2 / NCTA + 1u) * NCTA;
      sm.target3 = (v3 / NCTA + 1u) * NCTA;
    }
    if (tid < 320) bar_sync(6, 384); else { bar_arrive(6, 384); bar_sync(5, 64); }
    if (tid < 320) {
      uint32_t o[4][4];
#pragma unroll
      for (int p = 0; p < 4; p++) {
        const bf162 w0 = u2b(__byte_perm(sk[p].x, sk[p].z, 0x5410)), w1 = u2b(__byte_perm(sk[p].x, sk[p].z, 0x7632));
        const bf162 w2 = u2b(__byte_perm(sk[p].y, sk[p].w, 0x5410)), w3 = u2b(__byte_perm(sk[p].y, sk[p].w, 0x7632));
        uint32_t kv[4];
#pragma unroll
        for (int i = 0; i < 4; i++) {
          const uint32_t k0 = p == 0 ? kk[i].x : p == 1 ? kk[i].y : p == 2 ? kk[i].z : kk[i].w;
          const uint32_t k1 = p == 0 ? kk[i + 1].x : p == 1 ? kk[i + 1].y : p == 2 ? kk[i + 1].z : kk[i + 1].w;
          const uint32_t k2 = p == 0 ? kk[i + 2].x : p == 1 ? kk[i + 2].y : p == 2 ? kk[i + 2].z : kk[i + 2].w;
          const uint32_t k3 = p == 0 ? kk[i + 3].x : p == 1 ? kk[i + 3].y : p == 2 ? kk[i + 3].z : kk[i + 3].w;
          const uint32_t vx = p == 0 ? vv[i].x : p == 1 ? vv[i].y : p == 2 ? vv[i].z : vv[i].w;
          bf162 a = __hmul2_rn(u2b(k0), w3);
          a = __hadd2_rn(a, __hmul2_rn(u2b(k1), w2));
          a = __hadd2_rn(a, __hmul2_rn(u2b(k2), w1));
          a = __hadd2_rn(a, __hmul2_rn(u2b(k3), w0));
          kv[i] = b2u(__hmul2_rn(a, u2b(vx)));
        }
        o[p][0] = enc(__byte_perm(kv[0], kv[1], 0x5410)); o[p][1] = enc(__byte_perm(kv[2], kv[3], 0x5410));
        o[p][2] = enc(__byte_perm(kv[0], kv[1], 0x7632)); o[p][3] = enc(__byte_perm(kv[2], kv[3], 0x7632));
      }
      uint2* dst = reinterpret_cast<uint2*>(g_kv) + (size_t)(oc * 8) * 512 + (r0 >> 2);
#pragma unroll
      for (int p = 0; p < 4; p++) {
        st_pub2(dst + (2 * p) * 512, o[p][0], o[p][1]);
        st_pub2(dst + (2 * p + 1) * 512, o[p][2], o[p][3]);
      }
      if (wid == 0) bar_sync(4, 320); else bar_arrive(4, 320);
      if (tid == 0) {
        asm volatile("red.relaxed.gpu.global.add.u32 [%0], 1;" ::"l"(&g_ctr2) : "memory");
      }
      __syncwarp();
    } else {
      const int t0 = tid - 320;
      const uint4 zz = make_uint4(0, 0, 0, 0);
      if (tid == 320) {
        mbar_expect(&sm.mbarh, CPC * S_ * 2);
        bulk_g2s(hs, gh + (size_t)c0 * S_, CPC * S_ * 2, &sm.mbarh);
      }
      __syncwarp();
      for (int t = t0; t < CPC * 17; t += 64) *reinterpret_cast<uint4*>(&sm.u[t / 17][(t % 17) * 8]) = zz;
      if (t0 < 40) *reinterpret_cast<uint4*>(&sm.tabA[0][0][0] + tab_off(t0 >> 3) + ((t0 >> 2) & 1) * TABW + 1024 + 4 * (t0 & 3)) = zz;
      (&g_cand[cta][0][0])[t0] = zz;
      (&g_cand[cta][0][0])[64 + t0] = zz;
      if (t0 < 32) (&g_cand[cta][0][0])[128 + t0] = zz;
      else reinterpret_cast<uint4*>(&g_keys[cta][0])[t0 - 32] = zz;
      if (cta >= N1 && cta < N1 + N2) {
#pragma unroll
        for (int i = 0; i < 3; i++) g_act[cta - N1][t0 + 64 * i] = zz;
      }
    }
    mbar_wait(&sm.mbarh);
#pragma unroll
    for (int i = 0; i < 4; i++) {
      const int t = (NTHR - 1 - tid) + NTHR * i;
      if (t < CPC * 256) {
        uint32_t* tb = &sm.tabA[0][0][0] + tab_off(t >> 8) + (255 - (t & 255)) * 4;
        const uint4 h = hs[t];
        const uint32_t hp = (t & 255) ? reinterpret_cast<const uint32_t*>(hs)[4 * t - 1] : 0u;
        uint4 r1, rr;
        r1.x = __byte_perm(h.w, 0, 0x1032); r1.y = __byte_perm(h.z, 0, 0x1032);
        r1.z = __byte_perm(h.y, 0, 0x1032); r1.w = __byte_perm(h.x, 0, 0x1032);
        rr.x = __byte_perm(h.w, h.z, 0x7610); rr.y = __byte_perm(h.z, h.y, 0x7610);
        rr.z = __byte_perm(h.y, h.x, 0x7610); rr.w = __byte_perm(h.x, hp, 0x7610);
        *reinterpret_cast<uint4*>(tb) = rr;
        *reinterpret_cast<uint4*>(tb + TABW) = r1;
      }
    }
  }
  __syncthreads();

  const int wg = __shfl_sync(0xffffffffu, tid >> 7, 0);
  const int wtid = tid & 127;
  uint4* tile = reinterpret_cast<uint4*>(&sm.tabB[0][0][0]);
  if (wg < 2) {
    asm volatile("setmaxnreg.inc.sync.aligned.u32 224;");
    const int w = (tid >> 5) & 3, g = lane >> 2, tq = lane & 3;
    float* zw = sm.z[wg][w];
    const int sw = 3 * (((tq + w) >> 1) & 1);
    const int off_even = 16 * (tq + w) + 4 * ((0 + (g >> 2)) ^ sw) + (g & 3);
    const int off_odd = 16 * (tq + w) + 4 * ((2 + (g >> 2)) ^ sw) + (g & 3);
    uint32_t a[8][8];
    const uint32_t* tp0 = &sm.tabA[0][g & 1][1019 - 8 * w - (g >> 1) + tq];
    load_a_all(a, tp0 + tab_off(wg));
    float acc[8][16];
#pragma unroll
    for (int b = 0; b < 8; b++)
#pragma unroll
      for (int i = 0; i < 16; i++) acc[b][i] = 0.f;
    gather_kv(sm, c0, tid);
#pragma unroll 1
    for (int c = wg; c < CPC; c += 2) {
      const uint64_t desc = (uint64_t)((smem_u32(&sm.u[c][UPAD - 8]) & 0x3FFFF) >> 4) | ((uint64_t)1 << 16) | ((uint64_t)8 << 32);
      if (c > 0) bar_sync(1 + wg, 256);
      issue_g<0>(acc, a[0], desc);
      issue_g<1>(acc, a[1], desc);
      issue_g<2>(acc, a[2], desc);
      issue_g<3>(acc, a[3], desc);
      issue_g<4>(acc, a[4], desc);
      issue_g<5>(acc, a[5], desc);
      if (c + 1 < CPC) bar_arrive(1 + (wg ^ 1), 256);
      issue_g<6>(acc, a[6], desc);
      issue_g<7>(acc, a[7], desc);
      if (c >= 2) bar_sync(5 + wg, 256);
      wg_wait<4>();
      fence_blk<0>(acc); fence_blk<1>(acc); fence_blk<2>(acc); fence_blk<3>(acc);
      sts_blk<0>(acc, zw, off_even, off_odd);
      sts_blk<1>(acc, zw, off_even, off_odd);
      sts_blk<2>(acc, zw, off_even, off_odd);
      sts_blk<3>(acc, zw, off_even, off_odd);
      bar_arrive(9 + wg, 256);
      wg_wait<0>();
      fence_blk<4>(acc); fence_blk<5>(acc); fence_blk<6>(acc); fence_blk<7>(acc);
#pragma unroll
      for (int i = 0; i < 8; i++) fence_a(a[i]);
      sts_blk<4>(acc, zw, off_even, off_odd);
      sts_blk<5>(acc, zw, off_even, off_odd);
      sts_blk<6>(acc, zw, off_even, off_odd);
      sts_blk<7>(acc, zw, off_even, off_odd);
      bar_arrive(3 + wg, 256);
      if (c + 2 < CPC) load_a_all(a, tp0 + tab_off(c + 2));
    }
    asm volatile("setmaxnreg.dec.sync.aligned.u32 168;");
  } else {
    asm volatile("setmaxnreg.dec.sync.aligned.u32 56;");
    if (((wtid & 15) >> 2) < ((wtid >> 4) & 3))
      *reinterpret_cast<uint4*>(&sm.z[wtid >> 6][(wtid >> 4) & 3][(wtid & 15) * 4]) = make_uint4(0, 0, 0, 0);
    if (wtid == 96) {
      __threadfence();
      asm volatile("red.relaxed.gpu.global.add.u32 [%0], 1;" ::"l"(&g_ctr) : "memory");
    }
    if (wtid == 64) {
      const unsigned target = sm.target2;
      uint32_t v;
      int it = 0;
      do {
        asm volatile("ld.relaxed.gpu.global.u32 %0, [%1];" : "=r"(v) : "l"(&g_ctr2) : "memory");
      } while ((int)(v - target) < 0 && ++it < SPIN_LIMIT);
      asm volatile("mbarrier.arrive.shared.b64 _, [%0];" ::"r"(smem_u32(&sm.mbarc)) : "memory");
    }
    __syncwarp();
    gather_kv(sm, c0, tid);
#pragma unroll
    for (int i = 0; i < 10; i++) g_kv[c0 * 256 + wtid + 128 * i] = make_uint4(0, 0, 0, 0);
    if (wtid == 96) wait_ctr(&g_ctr, sm.target);
    __syncwarp();
    if (wtid == 32) {
      const uint32_t mw = smem_u32(&sm.mbarw);
      mbar_expect(&sm.mbar, 17 * D_ * 2);
#pragma unroll 1
      for (int r = 0; r < 16; r++) bulk_g2s(&sm.q[r][0], gq + (size_t)(cta * 16 + r) * D_, D_ * 2, &sm.mbar);
      bulk_g2s(&sm.wr[0], gwr, D_ * 2, &sm.mbar);
      if (cta < N1) {
        asm volatile("mbarrier.arrive.expect_tx.shared.b64 _, [%0], %1;" ::"r"(mw), "r"(3840 * 16) : "memory");
#pragma unroll 1
        for (int i = 0; i < 4; i++) {
          asm volatile("cp.async.bulk.tensor.2d.shared::cluster.global.mbarrier::complete_tx::bytes [%0], [%1, {%3, %4}], [%2];" ::"r"(smem_u32(&sm.w[i * 480])),
                       "l"(&tmg), "r"(mw), "r"(cta * 24), "r"(i * 160) : "memory");
          asm volatile("cp.async.bulk.tensor.2d.shared::cluster.global.mbarrier::complete_tx::bytes [%0], [%1, {%3, %4}], [%2];" ::"r"(smem_u32(&sm.w[1920 + i * 480])),
                       "l"(&tmu), "r"(mw), "r"(cta * 24), "r"(i * 160) : "memory");
        }
      } else if (cta < N1 + N2) {
        asm volatile("mbarrier.arrive.expect_tx.shared.b64 _, [%0], %1;" ::"r"(mw), "r"(3072 * 16) : "memory");
#pragma unroll 1
        for (int i = 0; i < 6; i++)
          asm volatile("cp.async.bulk.tensor.2d.shared::cluster.global.mbarrier::complete_tx::bytes [%0], [%1, {%3, %4}], [%2];" ::"r"(smem_u32(&sm.w[i * 512])),
                       "l"(&tmd), "r"(mw), "r"((cta - N1) * 16), "r"(i * 256) : "memory");
      }
    }
    const int rpb = wtid >> 1, re2 = wtid & 1;
    const int rsw = 3 * ((rpb >> 1) & 1);
    const int roff0 = 16 * rpb + 4 * ((2 * re2 + 0) ^ rsw);
    const int roff1 = 16 * rpb + 4 * ((2 * re2 + 1) ^ rsw);
    const uint32_t dvl = reinterpret_cast<const unsigned short*>(gD)[c0 + (lane < CPC ? lane : 0)];
#pragma unroll 1
    for (int c = 0; c < CPC; c++) {
      const int zg = c & 1;
      const uint32_t dvc = __shfl_sync(0xffffffffu, dvl, c);
      const bf162 d2 = u2b(dvc | (dvc << 16));
#pragma unroll
      for (int half = 0; half < 2; half++) {
        bar_sync((half ? 3 : 9) + zg, 256);
        const float* zb = sm.z[zg][0] + half * 1024;
        float4 x[4][2];
#pragma unroll
        for (int ww = 0; ww < 4; ww++) {
          x[ww][0] = *reinterpret_cast<const float4*>(zb + ww * ZPB * 16 + roff0);
          x[ww][1] = *reinterpret_cast<const float4*>(zb + ww * ZPB * 16 + roff1);
        }
        const int sidx = half * 1024 + wtid * 8;
        const uint4 kvv = *reinterpret_cast<const uint4*>(&sm.u[c][UPAD + sidx]);
        if (half == 1 && c + 2 < CPC) bar_arrive(5 + zg, 256);
        uint4 o;
        o.x = pack2((x[0][0].x + x[1][0].x) + (x[2][0].x + x[3][0].x), (x[0][0].y + x[1][0].y) + (x[2][0].y + x[3][0].y));
        o.y = pack2((x[0][0].z + x[1][0].z) + (x[2][0].z + x[3][0].z), (x[0][0].w + x[1][0].w) + (x[2][0].w + x[3][0].w));
        o.z = pack2((x[0][1].x + x[1][1].x) + (x[2][1].x + x[3][1].x), (x[0][1].y + x[1][1].y) + (x[2][1].y + x[3][1].y));
        o.w = pack2((x[0][1].z + x[1][1].z) + (x[2][1].z + x[3][1].z), (x[0][1].w + x[1][1].w) + (x[2][1].w + x[3][1].w));
        o.x = b2u(__hadd2_rn(u2b(o.x), __hmul2_rn(u2b(kvv.x), d2)));
        o.y = b2u(__hadd2_rn(u2b(o.y), __hmul2_rn(u2b(kvv.y), d2)));
        o.z = b2u(__hadd2_rn(u2b(o.z), __hmul2_rn(u2b(kvv.z), d2)));
        o.w = b2u(__hadd2_rn(u2b(o.w), __hmul2_rn(u2b(kvv.w), d2)));
        st_pub4(g_y2 + ((64 * half + rpb) * 640 + c0 + c) * 2 + re2, enc4(o));
      }
    }
    if (wid == 11) bar_sync(8, 128); else bar_arrive(8, 128);
    asm volatile("setmaxnreg.inc.sync.aligned.u32 168;");
  }

  if (tid == 352) {
    asm volatile("red.relaxed.gpu.global.add.u32 [%0], 1;" ::"l"(&g_ctr3) : "memory");
    wait_ctr(&g_ctr3, sm.target3);
    asm volatile("mbarrier.arrive.shared.b64 _, [%0];" ::"r"(smem_u32(&sm.mbary)) : "memory");
  }
  __syncwarp();
  const int g = lane >> 2, tq = lane & 3;
  const int hh = wid & 1, gqi = wid >> 1;
  const int row = hh * 8 + g;
  uint32_t hreg[20], hnreg[20];
  {
    const uint4* src = g_y2 + cta * 1280 + tid;
    uint4 v[4];
    if (wid < 8) {
      mbar_wait(&sm.mbar);
#pragma unroll
      for (int k = 0; k < 5; k++) {
        const uint4 qv4 = *reinterpret_cast<const uint4*>(&sm.q[row][32 * (5 * gqi + k) + 8 * tq]);
        hreg[4 * k] = qv4.x; hreg[4 * k + 1] = qv4.y; hreg[4 * k + 2] = qv4.z; hreg[4 * k + 3] = qv4.w;
      }
      const float2 ps = row_part_stats(hreg);
      if (tq == 0) sm.stq[row][gqi] = ps;
      bar_sync(7, 256);
      row_normalize<false>(reinterpret_cast<const float4*>(sm.stq[row]), hreg, hnreg);
    }
    mbar_wait(&sm.mbary);
#pragma unroll
    for (int i = 0; i < 4; i++) if (i < 3 || tid < 128) v[i] = ld_poll4(src + NTHR * i);
    int it = 0;
    bool all;
    do {
      all = true;
#pragma unroll
      for (int i = 0; i < 4; i++)
        if ((i < 3 || tid < 128) && !ready4(v[i])) { v[i] = ld_poll4(src + NTHR * i); all = false; }
    } while (!all && ++it < SPIN_LIMIT);
#pragma unroll
    for (int i = 0; i < 4; i++) {
      if (i < 3 || tid < 128) {
        const int t = tid + NTHR * i;
        tile[(t & 1) * 640 + tile_perm(t >> 1)] = make_uint4(~v[i].x, ~v[i].y, ~v[i].z, ~v[i].w);
      }
    }
  }
  __syncthreads();

  if (wid < 8) {
#pragma unroll
    for (int k = 0; k < 5; k++) {
      const int base = 32 * (5 * gqi + k);
      const int lch = base + 8 * ((lane & 7) >> 1) + 2 * (lane >> 3) + (lane & 1);
      uint32_t y[4];
      asm volatile("ldmatrix.sync.aligned.m8n8.x4.trans.shared.b16 {%0,%1,%2,%3}, [%4];"
                   : "=r"(y[0]), "=r"(y[1]), "=r"(y[2]), "=r"(y[3]) : "r"(smem_u32(&tile[hh * 640 + tile_perm(lch)])) : "memory");
#pragma unroll
      for (int i = 0; i < 4; i++)
        hreg[4 * k + i] = b2u(__hadd2_rn(u2b(hreg[4 * k + i]), __hmul2_rn(u2b(hnreg[4 * k + i]), u2b(y[i]))));
    }
    const float2 ps = row_part_stats(hreg);
    if (tq == 0) sm.st[row][gqi] = ps;
    bar_sync(7, 256);
    row_normalize<false>(reinterpret_cast<const float4*>(sm.st[row]), hreg, hnreg);
    float cr[5][4];
#pragma unroll
    for (int k = 0; k < 5; k++) {
      cr[k][0] = cr[k][1] = cr[k][2] = cr[k][3] = 0.f;
      const uint4 w4 = sm.wr[4 * (5 * gqi + k) + tq];
      mma_bf16(cr[k], hnreg[4 * k + 0], hnreg[4 * k + 1], w4.x, w4.y);
      mma_bf16(cr[k], hnreg[4 * k + 2], hnreg[4 * k + 3], w4.z, w4.w);
    }
    if (tq == 0) sm.rp[row][gqi] = ((cr[0][0] + cr[1][0]) + (cr[2][0] + cr[3][0])) + cr[4][0];
  }
  __syncthreads();
  uint32_t best;
  {
    const int rr = lane & 15;
    const float4 rp4 = *reinterpret_cast<const float4*>(sm.rp[rr]);
    const float r = (rp4.x + rp4.y) + (rp4.z + rp4.w);
    const uint32_t bits = __bfloat16_as_ushort(__float2bfloat16_rn(r));
    const uint32_t ord = (bits & 0x8000u) ? (bits ^ 0xFFFFu) : (bits ^ 0x8000u);
    const uint32_t key = (ord << 16) | 0x8000u | (uint32_t)(2047 - (cta * 16 + rr));
    best = __reduce_max_sync(0xffffffffu, key);
  }
  if (wid >= 8) asm volatile("st.relaxed.gpu.global.u32 [%0], %1;" ::"l"(&g_keys[tid - 256][cta]), "r"(best) : "memory");
  const int brow = (2047 - (int)(best & 0x7FFu)) - cta * 16;
  if (wid < 8 && row == brow) {
#pragma unroll
    for (int k = 0; k < 5; k++)
      st_pub4(&g_cand[cta][0][4 * (5 * gqi + k) + tq], enc4(make_uint4(hnreg[4 * k], hnreg[4 * k + 1], hnreg[4 * k + 2], hnreg[4 * k + 3])));
#pragma unroll
    for (int k = 0; k < 5; k++)
      st_pub4(&g_cand[cta][1][4 * (5 * gqi + k) + tq], enc4(make_uint4(hreg[4 * k], hreg[4 * k + 1], hreg[4 * k + 2], hreg[4 * k + 3])));
  }
#pragma unroll
  for (int i = 0; i < 20; i++) hreg[i] = b2u(__hadd2_rn(u2b(hreg[i]), u2b(hnreg[i])));
  if (wid == 11) {
    const uint4* kp = reinterpret_cast<const uint4*>(&g_keys[cta][0]) + lane;
    uint4 v = ld_poll4(kp);
    int it = 0;
    while (!ready4(v) && ++it < SPIN_LIMIT) v = ld_poll4(kp);
    const uint32_t m = max(max(v.x, v.y), max(v.z, v.w));
    const uint32_t wk = __reduce_max_sync(0xffffffffu, m);
    if (lane == 0) sm.win = wk;
  }
  __syncthreads();
  const uint32_t win = sm.win;
  const int wrow = 2047 - (int)(win & 0x7FFu);
  const int wcta = wrow >> 4;
  const bool st_out = wid < 8 && (cta * 16 + row) != wrow;
  uint4* outp = reinterpret_cast<uint4*>(gout + (size_t)(cta * 16 + row) * D_) + 20 * gqi + tq;
  if (cta >= N1) {
    if (st_out) {
#pragma unroll
      for (int k = 0; k < 5; k++) outp[4 * k] = make_uint4(hreg[4 * k], hreg[4 * k + 1], hreg[4 * k + 2], hreg[4 * k + 3]);
    }
  }
  if (cta >= N1) {
#pragma unroll
    for (int i = 0; i < 4; i++) if (i < 3 || tid < 128) g_y2[cta * 1280 + tid + NTHR * i] = make_uint4(0, 0, 0, 0);
  }
  if (cta < N1 + N2) mbar_wait(&sm.mbarw);
  float* xs = &sm.z[0][0][0];
  float* part = xs + 2048;
  if (cta < N1) {
    if (tid < 80) {
      const uint4 v = poll4(&g_cand[wcta][0][tid]);
      float4* xp = reinterpret_cast<float4*>(xs + tid * 8);
      xp[0] = make_float4(lo_f(v.x), hi_f(v.x), lo_f(v.y), hi_f(v.y));
      xp[1] = make_float4(lo_f(v.z), hi_f(v.z), lo_f(v.w), hi_f(v.w));
    }
    __syncthreads();
    const int m = wid / 6, hc = (wid % 6) >> 1, rs = (wid & 1) * 32 + lane;
    float a[8];
#pragma unroll
    for (int j = 0; j < 8; j++) a[j] = 0.f;
#pragma unroll
    for (int it = 0; it < 10; it++) {
      const int r = rs + 64 * it;
      const uint4 wv = sm.w[m * 1920 + r * 3 + hc];
      const float x = xs[r];
      a[0] = fmaf(x, lo_f(wv.x), a[0]); a[1] = fmaf(x, hi_f(wv.x), a[1]);
      a[2] = fmaf(x, lo_f(wv.y), a[2]); a[3] = fmaf(x, hi_f(wv.y), a[3]);
      a[4] = fmaf(x, lo_f(wv.z), a[4]); a[5] = fmaf(x, hi_f(wv.z), a[5]);
      a[6] = fmaf(x, lo_f(wv.w), a[6]); a[7] = fmaf(x, hi_f(wv.w), a[7]);
    }
    {
      const bool up = lane & 16;
#pragma unroll
      for (int j = 0; j < 4; j++) {
        const float send = up ? a[j] : a[j + 4], keep = up ? a[j + 4] : a[j];
        a[j] = keep + __shfl_xor_sync(0xffffffffu, send, 16);
      }
      const bool up2 = lane & 8;
#pragma unroll
      for (int j = 0; j < 2; j++) {
        const float send = up2 ? a[j] : a[j + 2], keep = up2 ? a[j + 2] : a[j];
        a[j] = keep + __shfl_xor_sync(0xffffffffu, send, 8);
      }
      const bool up3 = lane & 4;
      const float send = up3 ? a[0] : a[1], keep = up3 ? a[1] : a[0];
      a[0] = keep + __shfl_xor_sync(0xffffffffu, send, 4);
      a[0] += __shfl_xor_sync(0xffffffffu, a[0], 2);
      a[0] += __shfl_xor_sync(0xffffffffu, a[0], 1);
      if ((lane & 3) == 0) part[wid * 8 + (lane >> 2)] = a[0];
    }
    __syncthreads();
    if (wid == 0) {
      uint32_t bits = 0;
      if (lane < 24) {
        const int hc2 = lane >> 3, j = lane & 7;
        const float gt = rbf(part[(2 * hc2) * 8 + j] + part[(2 * hc2 + 1) * 8 + j]);
        const float up = rbf(part[(6 + 2 * hc2) * 8 + j] + part[(6 + 2 * hc2 + 1) * 8 + j]);
        const float sg = rbf(gt / (1.f + __expf(-gt)));
        bits = __bfloat16_as_ushort(__float2bfloat16_rn(sg * up));
      }
      const uint32_t nb = __shfl_down_sync(0xffffffffu, bits, 1);
      const uint32_t pw = bits | (nb << 16);
      const uint32_t w1 = __shfl_down_sync(0xffffffffu, pw, 2), w2 = __shfl_down_sync(0xffffffffu, pw, 4), w3 = __shfl_down_sync(0xffffffffu, pw, 6);
      const uint4 mine = enc4(make_uint4(pw, w1, w2, w3));
#pragma unroll
      for (int i = 0; i < 4; i++) {
        const int t = lane + 32 * i;
        const int cons = t / 3, ck = t - 3 * cons;
        uint4 v;
        v.x = __shfl_sync(0xffffffffu, mine.x, 8 * ck); v.y = __shfl_sync(0xffffffffu, mine.y, 8 * ck);
        v.z = __shfl_sync(0xffffffffu, mine.z, 8 * ck); v.w = __shfl_sync(0xffffffffu, mine.w, 8 * ck);
        if (t < 3 * N2) st_pub4(&g_act[cons][cta * 3 + ck], v);
      }
      __syncwarp();
      bar_arrive(7, 384);
    } else {
      bar_sync(7, 384);
    }
#pragma unroll
    for (int i = 0; i < 4; i++) if (i < 3 || tid < 128) g_y2[cta * 1280 + tid + NTHR * i] = make_uint4(0, 0, 0, 0);
    if (st_out) {
#pragma unroll
      for (int k = 0; k < 5; k++) outp[4 * k] = make_uint4(hreg[4 * k], hreg[4 * k + 1], hreg[4 * k + 2], hreg[4 * k + 3]);
    }
  } else if (cta < N1 + N2) {
    const int j2 = cta - N1;
    uint4 rowv = make_uint4(0, 0, 0, 0);
    if (tid < 192) {
      const uint4 v = poll4(&g_act[j2][tid]);
      float4* xp = reinterpret_cast<float4*>(xs + tid * 8);
      xp[0] = make_float4(lo_f(v.x), hi_f(v.x), lo_f(v.y), hi_f(v.y));
      xp[1] = make_float4(lo_f(v.z), hi_f(v.z), lo_f(v.w), hi_f(v.w));
    } else if (tid < 196) {
      const int t = tid - 192;
      rowv = poll4(&g_cand[wcta][t >> 1][j2 * 2 + (t & 1)]);
      reinterpret_cast<uint4*>(part + 256)[t] = rowv;
    }
    __syncthreads();
    const int hc = lane & 1, rs = wid * 16 + (lane >> 1);
    float a[8];
#pragma unroll
    for (int j = 0; j < 8; j++) a[j] = 0.f;
#pragma unroll
    for (int it = 0; it < 8; it++) {
      const int r = rs + 192 * it;
      const uint4 wv = sm.w[r * 2 + hc];
      const float x = xs[r];
      a[0] = fmaf(x, lo_f(wv.x), a[0]); a[1] = fmaf(x, hi_f(wv.x), a[1]);
      a[2] = fmaf(x, lo_f(wv.y), a[2]); a[3] = fmaf(x, hi_f(wv.y), a[3]);
      a[4] = fmaf(x, lo_f(wv.z), a[4]); a[5] = fmaf(x, hi_f(wv.z), a[5]);
      a[6] = fmaf(x, lo_f(wv.w), a[6]); a[7] = fmaf(x, hi_f(wv.w), a[7]);
    }
    {
      const bool up = lane & 16;
#pragma unroll
      for (int j = 0; j < 4; j++) {
        const float send = up ? a[j] : a[j + 4], keep = up ? a[j + 4] : a[j];
        a[j] = keep + __shfl_xor_sync(0xffffffffu, send, 16);
      }
      const bool up2 = lane & 8;
#pragma unroll
      for (int j = 0; j < 2; j++) {
        const float send = up2 ? a[j] : a[j + 2], keep = up2 ? a[j + 2] : a[j];
        a[j] = keep + __shfl_xor_sync(0xffffffffu, send, 8);
      }
      const bool up3 = lane & 4;
      const float send = up3 ? a[0] : a[1], keep = up3 ? a[1] : a[0];
      a[0] = keep + __shfl_xor_sync(0xffffffffu, send, 4);
      a[0] += __shfl_xor_sync(0xffffffffu, a[0], 2);
      if ((lane & 2) == 0) part[wid * 16 + hc * 8 + (lane >> 2)] = a[0];
    }
    __syncthreads();
    if (tid < 16) {
      float y = 0.f;
#pragma unroll
      for (int i = 0; i < 12; i++) y += part[i * 16 + tid];
      const uint32_t ord = win >> 16;
      const uint32_t rb = (ord & 0x8000u) ? (ord ^ 0x8000u) : (ord ^ 0xFFFFu);
      const float r = __uint_as_float(rb << 16);
      const float sg = rbf(1.f / (1.f + __expf(-r)));
      const float yy = rbf(rbf(y) * sg);
      const unsigned short* rv = reinterpret_cast<const unsigned short*>(part + 256);
      const float hn = __uint_as_float((uint32_t)rv[tid] << 16), h = __uint_as_float((uint32_t)rv[16 + tid] << 16);
      gout[(size_t)wrow * D_ + j2 * 16 + tid] = __float2bfloat16_rn(h + rbf(hn + yy));
    }
  }
}

}

typedef CUresult (*EncodeFn)(CUtensorMap*, CUtensorMapDataType, cuuint32_t, void*, const cuuint64_t*, const cuuint64_t*,
                             const cuuint32_t*, const cuuint32_t*, CUtensorMapInterleave, CUtensorMapSwizzle,
                             CUtensorMapL2promotion, CUtensorMapFloatOOBfill);

extern "C" void kernel_launch(void* const* d_in, const int* in_sizes, int n_in, void* d_out, int out_size) {
  (void)in_sizes; (void)n_in; (void)out_size;
  static EncodeFn encode = nullptr;
  static CUtensorMap tmg, tmu, tmd;
  static void* cached[3] = {nullptr, nullptr, nullptr};
  if (!encode) {
    cudaFuncSetAttribute(fused_kernel, cudaFuncAttributeMaxDynamicSharedMemorySize, (int)sizeof(Smem));
    void* fn = nullptr;
    cudaDriverEntryPointQueryResult qr;
    cudaGetDriverEntryPoint("cuTensorMapEncodeTiled", &fn, cudaEnableDefault, &qr);
    encode = (EncodeFn)fn;
  }
  if (cached[0] != d_in[8] || cached[1] != d_in[9] || cached[2] != d_in[10]) {
    const cuuint32_t es[2] = {1, 1};
    {
      const cuuint64_t dims[2] = {F_, D_}, strides[1] = {F_ * 2};
      const cuuint32_t box[2] = {24, 160};
      encode(&tmg, CU_TENSOR_MAP_DATA_TYPE_BFLOAT16, 2, d_in[8], dims, strides, box, es, CU_TENSOR_MAP_INTERLEAVE_NONE,
             CU_TENSOR_MAP_SWIZZLE_NONE, CU_TENSOR_MAP_L2_PROMOTION_NONE, CU_TENSOR_MAP_FLOAT_OOB_FILL_NONE);
      encode(&tmu, CU_TENSOR_MAP_DATA_TYPE_BFLOAT16, 2, d_in[9], dims, strides, box, es, CU_TENSOR_MAP_INTERLEAVE_NONE,
             CU_TENSOR_MAP_SWIZZLE_NONE, CU_TENSOR_MAP_L2_PROMOTION_NONE, CU_TENSOR_MAP_FLOAT_OOB_FILL_NONE);
    }
    {
      const cuuint64_t dims[2] = {D_, F_}, strides[1] = {D_ * 2};
      const cuuint32_t box[2] = {16, 256};
      encode(&tmd, CU_TENSOR_MAP_DATA_TYPE_BFLOAT16, 2, d_in[10], dims, strides, box, es, CU_TENSOR_MAP_INTERLEAVE_NONE,
             CU_TENSOR_MAP_SWIZZLE_NONE, CU_TENSOR_MAP_L2_PROMOTION_NONE, CU_TENSOR_MAP_FLOAT_OOB_FILL_NONE);
    }
    cached[0] = d_in[8]; cached[1] = d_in[9]; cached[2] = d_in[10];
  }
  fused_kernel<<<NCTA, NTHR, sizeof(Smem), cudaStreamPerThread>>>(
      tmg, tmu, tmd, (const bf16*)d_in[0], (const bf16*)d_in[1], (const bf16*)d_in[2], (const bf16*)d_in[3],
      (const bf16*)d_in[4], (const bf16*)d_in[5], (const bf16*)d_in[7], (bf16*)d_out);
}
```

```cpp
#include <cuda_runtime.h>
#include <cuda_bf16.h>
#include <cuda.h>
#include <stdint.h>

namespace {

typedef __nv_bfloat16 bf16;
typedef __nv_bfloat162 bf162;

constexpr int S_ = 2048, D_ = 640, F_ = 1536;
constexpr int NCTA = 128, CPC = 5, NTHR = 384;
constexpr int UPAD = 136, USTR = 2192;
constexpr int TABW = 1040;
constexpr int ZPB = 132;
constexpr int QSTR = 648;
constexpr int N1 = 64;
constexpr int N2 = 40;
constexpr int SPIN_LIMIT = 1 << 19;
constexpr int POLL_NS = 100;

struct __align__(128) Smem {
  uint32_t tabA[3][2][TABW];
  uint32_t extra[1024];
  uint32_t tabB[2][2][TABW];
  bf16 u[CPC][USTR];
  float z[2][4][ZPB * 16];
  bf16 q[16][QSTR];
  alignas(128) uint4 w[3840];
  uint4 wr[80];
  alignas(16) float2 st[16][4];
  alignas(16) float2 stq[16][4];
  alignas(16) float rp[16][4];
  unsigned long long mbar;
  unsigned long long mbarw;
  unsigned long long mbarc;
  unsigned long long mbary;
  unsigned long long mbarh;
  unsigned long long mbarh2;
  uint32_t target;
  uint32_t target2;
  uint32_t target3;
  uint32_t best;
  uint32_t win;
};

__device__ uint4 g_kv[D_ * S_ / 8];
__device__ uint4 g_y2[D_ * S_ / 8];
__device__ uint32_t g_keys[NCTA][NCTA];
__device__ uint4 g_cand[NCTA][2][80];
__device__ uint4 g_act[N2][F_ / 8];
__device__ unsigned int g_ctr;
__device__ unsigned int g_ctr2;
__device__ unsigned int g_ctr3;

__device__ __forceinline__ uint32_t smem_u32(const void* p) { return (uint32_t)__cvta_generic_to_shared(p); }
__device__ __forceinline__ void wg_fence() { asm volatile("wgmma.fence.sync.aligned;" ::: "memory"); }
__device__ __forceinline__ void wg_commit() { asm volatile("wgmma.commit_group.sync.aligned;" ::: "memory"); }
template <int N> __device__ __forceinline__ void wg_wait() { asm volatile("wgmma.wait_group.sync.aligned %0;" ::"n"(N) : "memory"); }
__device__ __forceinline__ void bar_sync(int id, int n) { asm volatile("bar.sync %0, %1;" ::"r"(id), "r"(n) : "memory"); }
__device__ __forceinline__ void bar_arrive(int id, int n) { asm volatile("bar.arrive %0, %1;" ::"r"(id), "r"(n) : "memory"); }
__device__ __forceinline__ bf162 u2b(uint32_t u) { return *reinterpret_cast<bf162*>(&u); }
__device__ __forceinline__ uint32_t b2u(bf162 b) { return *reinterpret_cast<uint32_t*>(&b); }
__device__ __forceinline__ float lo_f(uint32_t u) { return __uint_as_float(u << 16); }
__device__ __forceinline__ float hi_f(uint32_t u) { return __uint_as_float(u & 0xFFFF0000u); }
__device__ __forceinline__ float rbf(float x) { return __bfloat162float(__float2bfloat16_rn(x)); }
__device__ __forceinline__ uint32_t pack2(float a, float b) { return b2u(__floats2bfloat162_rn(a, b)); }
__device__ __forceinline__ uint32_t enc(uint32_t w) { return max(~w, 1u); }
__device__ __forceinline__ uint4 enc4(uint4 v) { return make_uint4(enc(v.x), enc(v.y), enc(v.z), enc(v.w)); }
__device__ __forceinline__ uint4 ld_poll4(const uint4* p) {
  uint4 v;
  asm volatile("ld.relaxed.gpu.global.v4.u32 {%0,%1,%2,%3}, [%4];" : "=r"(v.x), "=r"(v.y), "=r"(v.z), "=r"(v.w) : "l"(p) : "memory");
  return v;
}
__device__ __forceinline__ bool ready4(uint4 v) { return v.x != 0u && v.y != 0u && v.z != 0u && v.w != 0u; }
__device__ __forceinline__ uint4 poll4(const uint4* p) {
  uint4 v = ld_poll4(p);
  int it = 0;
  while (!ready4(v) && ++it < SPIN_LIMIT) v = ld_poll4(p);
  return make_uint4(~v.x, ~v.y, ~v.z, ~v.w);
}
__device__ __forceinline__ void st_pub4(uint4* p, uint4 v) {
  asm volatile("st.relaxed.gpu.global.v4.u32 [%0], {%1,%2,%3,%4};" ::"l"(p), "r"(v.x), "r"(v.y), "r"(v.z), "r"(v.w) : "memory");
}
__device__ __forceinline__ void st_pub2(uint2* p, uint32_t a, uint32_t b) {
  asm volatile("st.relaxed.gpu.global.v2.u32 [%0], {%1,%2};" ::"l"(p), "r"(a), "r"(b) : "memory");
}
__device__ __forceinline__ void mma_bf16(float (&c)[4], uint32_t a0, uint32_t a2, uint32_t b0, uint32_t b1) {
  asm volatile("mma.sync.aligned.m16n8k16.row.col.f32.bf16.bf16.f32 {%0,%1,%2,%3}, {%4,%5,%6,%5}, {%7,%8}, {%0,%1,%2,%3};"
               : "+f"(c[0]), "+f"(c[1]), "+f"(c[2]), "+f"(c[3]) : "r"(a0), "r"(0u), "r"(a2), "r"(b0), "r"(b1));
}
__device__ __forceinline__ void mbar_wait(const unsigned long long* bar) {
  const uint32_t mb = smem_u32(bar);
  uint32_t ok = 0;
  int it = 0;
  while (!ok && ++it < SPIN_LIMIT)
    asm volatile("{ .reg .pred p; mbarrier.try_wait.parity.shared.b64 p, [%1], 0; selp.u32 %0, 1, 0, p; }" : "=r"(ok) : "r"(mb) : "memory");
}
__device__ __forceinline__ void bulk_g2s(void* dst, const void* src, uint32_t bytes, const unsigned long long* bar) {
  asm volatile("cp.async.bulk.shared::cluster.global.mbarrier::complete_tx::bytes [%0], [%1], %2, [%3];" ::"r"(smem_u32(dst)),
               "l"(src), "r"(bytes), "r"(smem_u32(bar)) : "memory");
}
__device__ __forceinline__ void mbar_expect(const unsigned long long* bar, uint32_t bytes) {
  asm volatile("mbarrier.arrive.expect_tx.shared.b64 _, [%0], %1;" ::"r"(smem_u32(bar)), "r"(bytes) : "memory");
}
__device__ __forceinline__ void mma_bf16x(float (&c)[4], uint32_t a0, uint32_t a1, uint32_t a2, uint32_t a3, uint32_t b0, uint32_t b1) {
  asm volatile("mma.sync.aligned.m16n8k16.row.col.f32.bf16.bf16.f32 {%0,%1,%2,%3}, {%4,%5,%6,%7}, {%8,%9}, {%0,%1,%2,%3};"
               : "+f"(c[0]), "+f"(c[1]), "+f"(c[2]), "+f"(c[3]) : "r"(a0), "r"(a1), "r"(a2), "r"(a3), "r"(b0), "r"(b1));
}
__device__ __forceinline__ float fdivr(float a, float d, float r) {
  float q = a * r;
  float e = fmaf(-q, d, a);
  return fmaf(e, r, q);
}

template <bool FIRST> __device__ __forceinline__ void wgmma32(float (&d)[16], const uint32_t* a, uint64_t desc) {
  if (FIRST) {
    asm volatile("wgmma.mma_async.sync.aligned.m64n32k16.f32.bf16.bf16 {%0,%1,%2,%3,%4,%5,%6,%7,%8,%9,%10,%11,%12,%13,%14,%15}, {%16,%17,%18,%19}, %20, 0, 1, 1, 0;"
                 : "+f"(d[0]), "+f"(d[1]), "+f"(d[2]), "+f"(d[3]), "+f"(d[4]), "+f"(d[5]), "+f"(d[6]), "+f"(d[7]),
                   "+f"(d[8]), "+f"(d[9]), "+f"(d[10]), "+f"(d[11]), "+f"(d[12]), "+f"(d[13]), "+f"(d[14]), "+f"(d[15])
                 : "r"(a[0]), "r"(a[1]), "r"(a[2]), "r"(a[3]), "l"(desc));
  } else {
    asm volatile("wgmma.mma_async.sync.aligned.m64n32k16.f32.bf16.bf16 {%0,%1,%2,%3,%4,%5,%6,%7,%8,%9,%10,%11,%12,%13,%14,%15}, {%16,%17,%18,%19}, %20, 1, 1, 1, 0;"
                 : "+f"(d[0]), "+f"(d[1]), "+f"(d[2]), "+f"(d[3]), "+f"(d[4]), "+f"(d[5]), "+f"(d[6]), "+f"(d[7]),
                   "+f"(d[8]), "+f"(d[9]), "+f"(d[10]), "+f"(d[11]), "+f"(d[12]), "+f"(d[13]), "+f"(d[14]), "+f"(d[15])
                 : "r"(a[0]), "r"(a[1]), "r"(a[2]), "r"(a[3]), "l"(desc));
  }
}

template <int G> __device__ __forceinline__ void load_a(uint32_t (&a)[8], const uint32_t* tp) {
#pragma unroll
  for (int q = 0; q < 2; q++) {
    const int e = 2 * G + q;
    a[4 * q + 0] = tp[-64 * e];
    a[4 * q + 1] = tp[-64 * e - 32];
    a[4 * q + 2] = tp[-64 * e + 4];
    a[4 * q + 3] = tp[-64 * e - 28];
  }
}
__device__ __forceinline__ void load_a_all(uint32_t (&a)[8][8], const uint32_t* tp) {
  load_a<0>(a[0], tp); load_a<1>(a[1], tp); load_a<2>(a[2], tp); load_a<3>(a[3], tp);
  load_a<4>(a[4], tp); load_a<5>(a[5], tp); load_a<6>(a[6], tp); load_a<7>(a[7], tp);
}
template <int G> __device__ __forceinline__ void issue_g(float (&acc)[8][16], uint32_t (&a)[8], uint64_t desc0) {
  wg_fence();
#pragma unroll
  for (int q = 0; q < 2; q++) {
#pragma unroll
    for (int b = G; b < 8; b++) {
      const int delta = 2 * b - (2 * G + q);
      if (G == 0 && q == 0) wgmma32<true>(acc[b], &a[4 * q], desc0 + (uint64_t)(int64_t)(16 * delta));
      else wgmma32<false>(acc[b], &a[4 * q], desc0 + (uint64_t)(int64_t)(16 * delta));
    }
  }
  wg_commit();
}
template <int B> __device__ __forceinline__ void fence_blk(float (&acc)[8][16]) {
#pragma unroll
  for (int i = 0; i < 16; i++) asm volatile("" : "+f"(acc[B][i])::"memory");
}
__device__ __forceinline__ void fence_a(uint32_t (&a)[8]) {
#pragma unroll
  for (int i = 0; i < 8; i++) asm volatile("" : "+r"(a[i])::"memory");
}
template <int B> __device__ __forceinline__ void sts_blk(float (&acc)[8][16], float* zw, int off_even, int off_odd) {
#pragma unroll
  for (int jj = 0; jj < 4; jj++) {
    const int j = 4 * B + jj;
    float p0 = acc[B][4 * jj + 0], p1 = acc[B][4 * jj + 1];
    if (jj > 0) { p0 += acc[B][4 * (jj - 1) + 2]; p1 += acc[B][4 * (jj - 1) + 3]; }
    else if (B > 0) { p0 += acc[B > 0 ? B - 1 : 0][14]; p1 += acc[B > 0 ? B - 1 : 0][15]; }
    zw[64 * j + off_even] = p0;
    zw[64 * j + off_odd] = p1;
  }
}
__device__ __forceinline__ int tab_off(int c) { return c == 4 ? 0 : (c + 1) * 2 * TABW + (c >= 2 ? 1024 : 0); }
__device__ __forceinline__ int tile_perm(int ch) { return ch ^ (((ch >> 3) & 3) << 1); }

__device__ __forceinline__ void wait_ctr(const unsigned int* ctr, uint32_t target) {
  uint32_t v;
  int it = 0;
  do {
    asm volatile("ld.acquire.gpu.global.u32 %0, [%1];" : "=r"(v) : "l"(ctr) : "memory");
  } while ((int)(v - target) < 0 && ++it < SPIN_LIMIT);
}

__device__ __forceinline__ float2 row_part_stats(const uint32_t (&x)[20]) {
  float cs[5][4];
#pragma unroll
  for (int k = 0; k < 5; k++) {
    cs[k][0] = cs[k][1] = cs[k][2] = cs[k][3] = 0.f;
    mma_bf16x(cs[k], x[4 * k + 0], x[4 * k + 2], x[4 * k + 1], x[4 * k + 3], 0x3F803F80u, 0x3F803F80u);
  }
  const float mean = ((((cs[0][0] + cs[0][2]) + (cs[1][0] + cs[1][2])) + ((cs[2][0] + cs[2][2]) + (cs[3][0] + cs[3][2]))) + (cs[4][0] + cs[4][2])) * (1.f / 160.f);
  float m2a = 0.f, m2b = 0.f, m2c = 0.f, m2d = 0.f;
#pragma unroll
  for (int i = 0; i < 20; i += 2) {
    const float a = lo_f(x[i]) - mean, b = hi_f(x[i]) - mean, c = lo_f(x[i + 1]) - mean, d = hi_f(x[i + 1]) - mean;
    m2a = fmaf(a, a, m2a); m2b = fmaf(b, b, m2b); m2c = fmaf(c, c, m2c); m2d = fmaf(d, d, m2d);
  }
  float m2 = (m2a + m2b) + (m2c + m2d);
  m2 += __shfl_xor_sync(0xffffffffu, m2, 1);
  m2 += __shfl_xor_sync(0xffffffffu, m2, 2);
  return make_float2(mean, m2);
}
template <bool EXACT> __device__ __forceinline__ void row_normalize(const float4* st, const uint32_t (&x)[20], uint32_t (&y)[20]) {
  const float4 p = st[0], q = st[1];
  const float mean = ((p.x + p.z) + (q.x + q.z)) * 0.25f;
  const float d0 = p.x - mean, d1 = p.z - mean, d2 = q.x - mean, d3 = q.z - mean;
  const float m2 = ((p.y + p.w) + (q.y + q.w)) + 160.f * ((d0 * d0 + d1 * d1) + (d2 * d2 + d3 * d3));
  const float hd = rbf(sqrtf(rbf(rbf(m2 * (1.f / D_)) + 1e-5f)));
  const float hr = __frcp_rn(hd);
  const bf162 hm2 = __float2bfloat162_rn(mean);
#pragma unroll
  for (int i = 0; i < 20; i++) {
    const uint32_t d = b2u(__hsub2_rn(u2b(x[i]), hm2));
    y[i] = EXACT ? pack2(fdivr(lo_f(d), hd, hr), fdivr(hi_f(d), hd, hr)) : pack2(lo_f(d) * hr, hi_f(d) * hr);
  }
}

__device__ __forceinline__ void build_tab(Smem& sm, const uint4* hs, int t, int tl) {
  uint32_t* tb = &sm.tabA[0][0][0] + tab_off(t >> 8) + (255 - (t & 255)) * 4;
  const uint4 h = hs[tl];
  const uint32_t hp = (t & 255) ? reinterpret_cast<const uint32_t*>(hs)[4 * tl - 1] : 0u;
  uint4 r1, rr;
  r1.x = __byte_perm(h.w, 0, 0x1032); r1.y = __byte_perm(h.z, 0, 0x1032);
  r1.z = __byte_perm(h.y, 0, 0x1032); r1.w = __byte_perm(h.x, 0, 0x1032);
  rr.x = __byte_perm(h.w, h.z, 0x7610); rr.y = __byte_perm(h.z, h.y, 0x7610);
  rr.z = __byte_perm(h.y, h.x, 0x7610); rr.w = __byte_perm(h.x, hp, 0x7610);
  *reinterpret_cast<uint4*>(tb) = rr;
  *reinterpret_cast<uint4*>(tb + TABW) = r1;
}

__device__ __forceinline__ void gather_kv(Smem& sm, int c0, int tid) {
  mbar_wait(&sm.mbarc);
  uint4 v[4];
  uint4* src = g_kv + c0 * 256 + tid;
#pragma unroll
  for (int i = 0; i < 4; i++) if (i < 3 || tid >= 256) v[i] = ld_poll4(src + NTHR * i - (i == 3 ? 256 : 0));
#pragma unroll
  for (int i = 0; i < 4; i++) {
    if (i < 3 || tid >= 256) {
      const int t = tid + NTHR * i - (i == 3 ? 256 : 0);
      int it = 0;
      while (!ready4(v[i]) && ++it < SPIN_LIMIT) { __nanosleep(POLL_NS); v[i] = ld_poll4(g_kv + c0 * 256 + t); }
      *reinterpret_cast<uint4*>(&sm.u[t >> 8][UPAD + (t & 255) * 8]) = make_uint4(~v[i].x, ~v[i].y, ~v[i].z, ~v[i].w);
    }
  }
  asm volatile("fence.proxy.async.shared::cta;" ::: "memory");
  __syncthreads();
}

__global__ void __launch_bounds__(NTHR, 1)
fused_kernel(const __grid_constant__ CUtensorMap tmg, const __grid_constant__ CUtensorMap tmu,
             const __grid_constant__ CUtensorMap tmd, const bf16* __restrict__ gq, const bf16* __restrict__ gk, const bf16* __restrict__ gv,
             const bf16* __restrict__ gsk, const bf16* __restrict__ gh, const bf16* __restrict__ gD,
             const bf16* __restrict__ gwr, bf16* __restrict__ gout) {
  extern __shared__ __align__(128) unsigned char smraw[];
  Smem& sm = *reinterpret_cast<Smem*>(smraw);
  const int tid = threadIdx.x;
  const int cta = blockIdx.x;
  const int c0 = cta * CPC;
  const int lane = tid & 31;
  const int wid = tid >> 5;

  {
    uint4* hs = reinterpret_cast<uint4*>(&sm.z[0][0][0]);
    const int oc = tid >> 2;
    const int r0 = cta * 16 + (tid & 3) * 4;
    uint4 kk[7], vv[4], sk[4];
    if (tid < 320) {
      const uint4* kp = reinterpret_cast<const uint4*>(gk) + (size_t)r0 * 80 + oc;
      const uint4* vp = reinterpret_cast<const uint4*>(gv) + (size_t)r0 * 80 + oc;
#pragma unroll
      for (int i = 0; i < 7; i++) kk[i] = (i >= 3 || r0 > 0) ? __ldg(kp + (i - 3) * 80) : make_uint4(0, 0, 0, 0);
#pragma unroll
      for (int i = 0; i < 4; i++) vv[i] = __ldg(vp + i * 80);
#pragma unroll
      for (int i = 0; i < 4; i++) sk[i] = __ldg(reinterpret_cast<const uint4*>(gsk) + oc * 4 + i);
    } else if (tid == 320) {
      asm volatile("mbarrier.init.shared.b64 [%0], 1;" ::"r"(smem_u32(&sm.mbarh)) : "memory");
      asm volatile("mbarrier.init.shared.b64 [%0], 1;" ::"r"(smem_u32(&sm.mbarh2)) : "memory");
      asm volatile("mbarrier.init.shared.b64 [%0], 1;" ::"r"(smem_u32(&sm.mbar)) : "memory");
      asm volatile("mbarrier.init.shared.b64 [%0], 1;" ::"r"(smem_u32(&sm.mbarw)) : "memory");
      asm volatile("mbarrier.init.shared.b64 [%0], 1;" ::"r"(smem_u32(&sm.mbarc)) : "memory");
      asm volatile("mbarrier.init.shared.b64 [%0], 1;" ::"r"(smem_u32(&sm.mbary)) : "memory");
      asm volatile("fence.proxy.async.shared::cta;" ::: "memory");
    } else if (tid == 352) {
      uint32_t v1, v2, v3;
      asm volatile("ld.relaxed.gpu.global.u32 %0, [%1];" : "=r"(v1) : "l"(&g_ctr) : "memory");
      asm volatile("ld.relaxed.gpu.global.u32 %0, [%1];" : "=r"(v2) : "l"(&g_ctr2) : "memory");
      asm volatile("ld.relaxed.gpu.global.u32 %0, [%1];" : "=r"(v3) : "l"(&g_ctr3) : "memory");
      sm.target = (v1 / NCTA + 1u) * NCTA;
      sm.target2 = (v2 / NCTA + 1u) * NCTA;
      sm.target3 = (v3 / NCTA + 1u) * NCTA;
    }
    if (tid < 320) bar_sync(6, 384); else { bar_arrive(6, 384); bar_sync(5, 64); }
    if (tid < 320) {
      uint32_t o[4][4];
#pragma unroll
      for (int p = 0; p < 4; p++) {
        const bf162 w0 = u2b(__byte_perm(sk[p].x, sk[p].z, 0x5410)), w1 = u2b(__byte_perm(sk[p].x, sk[p].z, 0x7632));
        const bf162 w2 = u2b(__byte_perm(sk[p].y, sk[p].w, 0x5410)), w3 = u2b(__byte_perm(sk[p].y, sk[p].w, 0x7632));
        uint32_t kv[4];
#pragma unroll
        for (int i = 0; i < 4; i++) {
          const uint32_t k0 = p == 0 ? kk[i].x : p == 1 ? kk[i].y : p == 2 ? kk[i].z : kk[i].w;
          const uint32_t k1 = p == 0 ? kk[i + 1].x : p == 1 ? kk[i + 1].y : p == 2 ? kk[i + 1].z : kk[i + 1].w;
          const uint32_t k2 = p == 0 ? kk[i + 2].x : p == 1 ? kk[i + 2].y : p == 2 ? kk[i + 2].z : kk[i + 2].w;
          const uint32_t k3 = p == 0 ? kk[i + 3].x : p == 1 ? kk[i + 3].y : p == 2 ? kk[i + 3].z : kk[i + 3].w;
          const uint32_t vx = p == 0 ? vv[i].x : p == 1 ? vv[i].y : p == 2 ? vv[i].z : vv[i].w;
          bf162 a = __hmul2_rn(u2b(k0), w3);
          a = __hadd2_rn(a, __hmul2_rn(u2b(k1), w2));
          a = __hadd2_rn(a, __hmul2_rn(u2b(k2), w1));
          a = __hadd2_rn(a, __hmul2_rn(u2b(k3), w0));
          kv[i] = b2u(__hmul2_rn(a, u2b(vx)));
        }
        o[p][0] = enc(__byte_perm(kv[0], kv[1], 0x5410)); o[p][1] = enc(__byte_perm(kv[2], kv[3], 0x5410));
        o[p][2] = enc(__byte_perm(kv[0], kv[1], 0x7632)); o[p][3] = enc(__byte_perm(kv[2], kv[3], 0x7632));
      }
      uint2* dst = reinterpret_cast<uint2*>(g_kv) + (size_t)(oc * 8) * 512 + (r0 >> 2);
#pragma unroll
      for (int p = 0; p < 4; p++) {
        st_pub2(dst + (2 * p) * 512, o[p][0], o[p][1]);
        st_pub2(dst + (2 * p + 1) * 512, o[p][2], o[p][3]);
      }
      if (wid == 0) bar_sync(4, 320); else bar_arrive(4, 320);
      if (tid == 0) {
        asm volatile("red.relaxed.gpu.global.add.u32 [%0], 1;" ::"l"(&g_ctr2) : "memory");
        mbar_expect(&sm.mbarh2, 3 * S_ * 2);
        bulk_g2s(&sm.w[0], gh + (size_t)(c0 + 2) * S_, 3 * S_ * 2, &sm.mbarh2);
      }
      __syncwarp();
    } else {
      const int t0 = tid - 320;
      const uint4 zz = make_uint4(0, 0, 0, 0);
      if (tid == 320) {
        mbar_expect(&sm.mbarh, 2 * S_ * 2);
        bulk_g2s(hs, gh + (size_t)c0 * S_, 2 * S_ * 2, &sm.mbarh);
      }
      __syncwarp();
      for (int t = t0; t < CPC * 17; t += 64) *reinterpret_cast<uint4*>(&sm.u[t / 17][(t % 17) * 8]) = zz;
      if (t0 < 40) *reinterpret_cast<uint4*>(&sm.tabA[0][0][0] + tab_off(t0 >> 3) + ((t0 >> 2) & 1) * TABW + 1024 + 4 * (t0 & 3)) = zz;
      (&g_cand[cta][0][0])[t0] = zz;
      (&g_cand[cta][0][0])[64 + t0] = zz;
      if (t0 < 32) (&g_cand[cta][0][0])[128 + t0] = zz;
      else reinterpret_cast<uint4*>(&g_keys[cta][0])[t0 - 32] = zz;
      if (cta >= N1 && cta < N1 + N2) {
#pragma unroll
        for (int i = 0; i < 3; i++) g_act[cta - N1][t0 + 64 * i] = zz;
      }
    }
    if (tid < 256) {
      mbar_wait(&sm.mbarh);
      build_tab(sm, hs, tid, tid);
      build_tab(sm, hs, tid + 256, tid + 256);
    }
  }
  __syncthreads();

  const int wg = __shfl_sync(0xffffffffu, tid >> 7, 0);
  const int wtid = tid & 127;
  uint4* tile = reinterpret_cast<uint4*>(&sm.tabB[0][0][0]);
  if (wg < 2) {
    asm volatile("setmaxnreg.inc.sync.aligned.u32 224;");
    const int w = (tid >> 5) & 3, g = lane >> 2, tq = lane & 3;
    float* zw = sm.z[wg][w];
    const int sw = 3 * (((tq + w) >> 1) & 1);
    const int off_even = 16 * (tq + w) + 4 * ((0 + (g >> 2)) ^ sw) + (g & 3);
    const int off_odd = 16 * (tq + w) + 4 * ((2 + (g >> 2)) ^ sw) + (g & 3);
    uint32_t a[8][8];
    const uint32_t* tp0 = &sm.tabA[0][g & 1][1019 - 8 * w - (g >> 1) + tq];
    load_a_all(a, tp0 + tab_off(wg));
    float acc[8][16];
#pragma unroll
    for (int b = 0; b < 8; b++)
#pragma unroll
      for (int i = 0; i < 16; i++) acc[b][i] = 0.f;
    gather_kv(sm, c0, tid);
#pragma unroll 1
    for (int c = wg; c < CPC; c += 2) {
      const uint64_t desc = (uint64_t)((smem_u32(&sm.u[c][UPAD - 8]) & 0x3FFFF) >> 4) | ((uint64_t)1 << 16) | ((uint64_t)8 << 32);
      if (c > 0) bar_sync(1 + wg, 256);
      issue_g<0>(acc, a[0], desc);
      issue_g<1>(acc, a[1], desc);
      issue_g<2>(acc, a[2], desc);
      issue_g<3>(acc, a[3], desc);
      issue_g<4>(acc, a[4], desc);
      issue_g<5>(acc, a[5], desc);
      if (c + 1 < CPC) bar_arrive(1 + (wg ^ 1), 256);
      issue_g<6>(acc, a[6], desc);
      issue_g<7>(acc, a[7], desc);
      if (c >= 2) bar_sync(5 + wg, 256);
      wg_wait<4>();
      fence_blk<0>(acc); fence_blk<1>(acc); fence_blk<2>(acc); fence_blk<3>(acc);
      sts_blk<0>(acc, zw, off_even, off_odd);
      sts_blk<1>(acc, zw, off_even, off_odd);
      sts_blk<2>(acc, zw, off_even, off_odd);
      sts_blk<3>(acc, zw, off_even, off_odd);
      bar_arrive(9 + wg, 256);
      wg_wait<0>();
      fence_blk<4>(acc); fence_blk<5>(acc); fence_blk<6>(acc); fence_blk<7>(acc);
#pragma unroll
      for (int i = 0; i < 8; i++) fence_a(a[i]);
      sts_blk<4>(acc, zw, off_even, off_odd);
      sts_blk<5>(acc, zw, off_even, off_odd);
      sts_blk<6>(acc, zw, off_even, off_odd);
      sts_blk<7>(acc, zw, off_even, off_odd);
      bar_arrive(3 + wg, 256);
      if (c < 2) bar_sync(11 + wg, 256);
      if (c + 2 < CPC) load_a_all(a, tp0 + tab_off(c + 2));
    }
    asm volatile("setmaxnreg.dec.sync.aligned.u32 168;");
  } else {
    asm volatile("setmaxnreg.dec.sync.aligned.u32 56;");
    if (((wtid & 15) >> 2) < ((wtid >> 4) & 3))
      *reinterpret_cast<uint4*>(&sm.z[wtid >> 6][(wtid >> 4) & 3][(wtid & 15) * 4]) = make_uint4(0, 0, 0, 0);
    if (wtid == 96) {
      __threadfence();
      asm volatile("red.relaxed.gpu.global.add.u32 [%0], 1;" ::"l"(&g_ctr) : "memory");
    }
    if (wtid == 64) {
      const unsigned target = sm.target2;
      uint32_t v;
      int it = 0;
      do {
        asm volatile("ld.relaxed.gpu.global.u32 %0, [%1];" : "=r"(v) : "l"(&g_ctr2) : "memory");
      } while ((int)(v - target) < 0 && ++it < SPIN_LIMIT);
      asm volatile("mbarrier.arrive.shared.b64 _, [%0];" ::"r"(smem_u32(&sm.mbarc)) : "memory");
    }
    __syncwarp();
    gather_kv(sm, c0, tid);
#pragma unroll
    for (int i = 0; i < 10; i++) g_kv[c0 * 256 + wtid + 128 * i] = make_uint4(0, 0, 0, 0);
    if (wtid == 96) wait_ctr(&g_ctr, sm.target);
    __syncwarp();
    mbar_wait(&sm.mbarh2);
#pragma unroll 2
    for (int i = 0; i < 6; i++) build_tab(sm, sm.w, 512 + wtid + 128 * i, wtid + 128 * i);
    bar_arrive(11, 256);
    bar_arrive(12, 256);
    asm volatile("fence.proxy.async.shared::cta;" ::: "memory");
    bar_sync(8, 128);
    if (wtid == 32) {
      const uint32_t mw = smem_u32(&sm.mbarw);
      mbar_expect(&sm.mbar, 17 * D_ * 2);
#pragma unroll 1
      for (int r = 0; r < 16; r++) bulk_g2s(&sm.q[r][0], gq + (size_t)(cta * 16 + r) * D_, D_ * 2, &sm.mbar);
      bulk_g2s(&sm.wr[0], gwr, D_ * 2, &sm.mbar);
      if (cta < N1) {
        asm volatile("mbarrier.arrive.expect_tx.shared.b64 _, [%0], %1;" ::"r"(mw), "r"(3840 * 16) : "memory");
#pragma unroll 1
        for (int i = 0; i < 4; i++) {
          asm volatile("cp.async.bulk.tensor.2d.shared::cluster.global.mbarrier::complete_tx::bytes [%0], [%1, {%3, %4}], [%2];" ::"r"(smem_u32(&sm.w[i * 480])),
                       "l"(&tmg), "r"(mw), "r"(cta * 24), "r"(i * 160) : "memory");
          asm volatile("cp.async.bulk.tensor.2d.shared::cluster.global.mbarrier::complete_tx::bytes [%0], [%1, {%3, %4}], [%2];" ::"r"(smem_u32(&sm.w[1920 + i * 480])),
                       "l"(&tmu), "r"(mw), "r"(cta * 24), "r"(i * 160) : "memory");
        }
      } else if (cta < N1 + N2) {
        asm volatile("mbarrier.arrive.expect_tx.shared.b64 _, [%0], %1;" ::"r"(mw), "r"(3072 * 16) : "memory");
#pragma unroll 1
        for (int i = 0; i < 6; i++)
          asm volatile("cp.async.bulk.tensor.2d.shared::cluster.global.mbarrier::complete_tx::bytes [%0], [%1, {%3, %4}], [%2];" ::"r"(smem_u32(&sm.w[i * 512])),
                       "l"(&tmd), "r"(mw), "r"((cta - N1) * 16), "r"(i * 256) : "memory");
      }
    }
    const int rpb = wtid >> 1, re2 = wtid & 1;
    const int rsw = 3 * ((rpb >> 1) & 1);
    const int roff0 = 16 * rpb + 4 * ((2 * re2 + 0) ^ rsw);
    const int roff1 = 16 * rpb + 4 * ((2 * re2 + 1) ^ rsw);
    const uint32_t dvl = reinterpret_cast<const unsigned short*>(gD)[c0 + (lane < CPC ? lane : 0)];
#pragma unroll 1
    for (int c = 0; c < CPC; c++) {
      const int zg = c & 1;
      const uint32_t dvc = __shfl_sync(0xffffffffu, dvl, c);
      const bf162 d2 = u2b(dvc | (dvc << 16));
#pragma unroll
      for (int half = 0; half < 2; half++) {
        bar_sync((half ? 3 : 9) + zg, 256);
        const float* zb = sm.z[zg][0] + half * 1024;
        float4 x[4][2];
#pragma unroll
        for (int ww = 0; ww < 4; ww++) {
          x[ww][0] = *reinterpret_cast<const float4*>(zb + ww * ZPB * 16 + roff0);
          x[ww][1] = *reinterpret_cast<const float4*>(zb + ww * ZPB * 16 + roff1);
        }
        const int sidx = half * 1024 + wtid * 8;
        const uint4 kvv = *reinterpret_cast<const uint4*>(&sm.u[c][UPAD + sidx]);
        if (half == 1 && c + 2 < CPC) bar_arrive(5 + zg, 256);
        uint4 o;
        o.x = pack2((x[0][0].x + x[1][0].x) + (x[2][0].x + x[3][0].x), (x[0][0].y + x[1][0].y) + (x[2][0].y + x[3][0].y));
        o.y = pack2((x[0][0].z + x[1][0].z) + (x[2][0].z + x[3][0].z), (x[0][0].w + x[1][0].w) + (x[2][0].w + x[3][0].w));
        o.z = pack2((x[0][1].x + x[1][1].x) + (x[2][1].x + x[3][1].x), (x[0][1].y + x[1][1].y) + (x[2][1].y + x[3][1].y));
        o.w = pack2((x[0][1].z + x[1][1].z) + (x[2][1].z + x[3][1].z), (x[0][1].w + x[1][1].w) + (x[2][1].w + x[3][1].w));
        o.x = b2u(__hadd2_rn(u2b(o.x), __hmul2_rn(u2b(kvv.x), d2)));
        o.y = b2u(__hadd2_rn(u2b(o.y), __hmul2_rn(u2b(kvv.y), d2)));
        o.z = b2u(__hadd2_rn(u2b(o.z), __hmul2_rn(u2b(kvv.z), d2)));
        o.w = b2u(__hadd2_rn(u2b(o.w), __hmul2_rn(u2b(kvv.w), d2)));
        st_pub4(g_y2 + ((64 * half + rpb) * 640 + c0 + c) * 2 + re2, enc4(o));
      }
    }
    if (wid == 11) bar_sync(8, 128); else bar_arrive(8, 128);
    asm volatile("setmaxnreg.inc.sync.aligned.u32 168;");
  }

  if (tid == 352) {
    asm volatile("red.relaxed.gpu.global.add.u32 [%0], 1;" ::"l"(&g_ctr3) : "memory");
    wait_ctr(&g_ctr3, sm.target3);
    asm volatile("mbarrier.arrive.shared.b64 _, [%0];" ::"r"(smem_u32(&sm.mbary)) : "memory");
  }
  __syncwarp();
  const int g = lane >> 2, tq = lane & 3;
  const int hh = wid & 1, gqi = wid >> 1;
  const int row = hh * 8 + g;
  uint32_t hreg[20], hnreg[20];
  {
    const uint4* src = g_y2 + cta * 1280 + tid;
    uint4 v[4];
    if (wid < 8) {
      mbar_wait(&sm.mbar);
#pragma unroll
      for (int k = 0; k < 5; k++) {
        const uint4 qv4 = *reinterpret_cast<const uint4*>(&sm.q[row][32 * (5 * gqi + k) + 8 * tq]);
        hreg[4 * k] = qv4.x; hreg[4 * k + 1] = qv4.y; hreg[4 * k + 2] = qv4.z; hreg[4 * k + 3] = qv4.w;
      }
      const float2 ps = row_part_stats(hreg);
      if (tq == 0) sm.stq[row][gqi] = ps;
      bar_sync(7, 256);
      row_normalize<false>(reinterpret_cast<const float4*>(sm.stq[row]), hreg, hnreg);
    }
    mbar_wait(&sm.mbary);
#pragma unroll
    for (int i = 0; i < 4; i++) if (i < 3 || tid < 128) v[i] = ld_poll4(src + NTHR * i);
    int it = 0;
    bool all;
    do {
      all = true;
#pragma unroll
      for (int i = 0; i < 4; i++)
        if ((i < 3 || tid < 128) && !ready4(v[i])) { v[i] = ld_poll4(src + NTHR * i); all = false; }
    } while (!all && ++it < SPIN_LIMIT);
#pragma unroll
    for (int i = 0; i < 4; i++) {
      if (i < 3 || tid < 128) {
        const int t = tid + NTHR * i;
        tile[(t & 1) * 640 + tile_perm(t >> 1)] = make_uint4(~v[i].x, ~v[i].y, ~v[i].z, ~v[i].w);
      }
    }
  }
  __syncthreads();

  if (wid < 8) {
#pragma unroll
    for (int k = 0; k < 5; k++) {
      const int base = 32 * (5 * gqi + k);
      const int lch = base + 8 * ((lane & 7) >> 1) + 2 * (lane >> 3) + (lane & 1);
      uint32_t y[4];
      asm volatile("ldmatrix.sync.aligned.m8n8.x4.trans.shared.b16 {%0,%1,%2,%3}, [%4];"
                   : "=r"(y[0]), "=r"(y[1]), "=r"(y[2]), "=r"(y[3]) : "r"(smem_u32(&tile[hh * 640 + tile_perm(lch)])) : "memory");
#pragma unroll
      for (int i = 0; i < 4; i++)
        hreg[4 * k + i] = b2u(__hadd2_rn(u2b(hreg[4 * k + i]), __hmul2_rn(u2b(hnreg[4 * k + i]), u2b(y[i]))));
    }
    const float2 ps = row_part_stats(hreg);
    if (tq == 0) sm.st[row][gqi] = ps;
    bar_sync(7, 256);
    row_normalize<false>(reinterpret_cast<const float4*>(sm.st[row]), hreg, hnreg);
    float cr[5][4];
#pragma unroll
    for (int k = 0; k < 5; k++) {
      cr[k][0] = cr[k][1] = cr[k][2] = cr[k][3] = 0.f;
      const uint4 w4 = sm.wr[4 * (5 * gqi + k) + tq];
      mma_bf16(cr[k], hnreg[4 * k + 0], hnreg[4 * k + 1], w4.x, w4.y);
      mma_bf16(cr[k], hnreg[4 * k + 2], hnreg[4 * k + 3], w4.z, w4.w);
    }
    if (tq == 0) sm.rp[row][gqi] = ((cr[0][0] + cr[1][0]) + (cr[2][0] + cr[3][0])) + cr[4][0];
  }
  __syncthreads();
  uint32_t best;
  {
    const int rr = lane & 15;
    const float4 rp4 = *reinterpret_cast<const float4*>(sm.rp[rr]);
    const float r = (rp4.x + rp4.y) + (rp4.z + rp4.w);
    const uint32_t bits = __bfloat16_as_ushort(__float2bfloat16_rn(r));
    const uint32_t ord = (bits & 0x8000u) ? (bits ^ 0xFFFFu) : (bits ^ 0x8000u);
    const uint32_t key = (ord << 16) | 0x8000u | (uint32_t)(2047 - (cta * 16 + rr));
    best = __reduce_max_sync(0xffffffffu, key);
  }
  if (wid >= 8) asm volatile("st.relaxed.gpu.global.u32 [%0], %1;" ::"l"(&g_keys[tid - 256][cta]), "r"(best) : "memory");
  const int brow = (2047 - (int)(best & 0x7FFu)) - cta * 16;
  if (wid < 8 && row == brow) {
#pragma unroll
    for (int k = 0; k < 5; k++)
      st_pub4(&g_cand[cta][0][4 * (5 * gqi + k) + tq], enc4(make_uint4(hnreg[4 * k], hnreg[4 * k + 1], hnreg[4 * k + 2], hnreg[4 * k + 3])));
#pragma unroll
    for (int k = 0; k < 5; k++)
      st_pub4(&g_cand[cta][1][4 * (5 * gqi + k) + tq], enc4(make_uint4(hreg[4 * k], hreg[4 * k + 1], hreg[4 * k + 2], hreg[4 * k + 3])));
  }
#pragma unroll
  for (int i = 0; i < 20; i++) hreg[i] = b2u(__hadd2_rn(u2b(hreg[i]), u2b(hnreg[i])));
  if (wid == 11) {
    const uint4* kp = reinterpret_cast<const uint4*>(&g_keys[cta][0]) + lane;
    uint4 v = ld_poll4(kp);
    int it = 0;
    while (!ready4(v) && ++it < SPIN_LIMIT) v = ld_poll4(kp);
    const uint32_t m = max(max(v.x, v.y), max(v.z, v.w));
    const uint32_t wk = __reduce_max_sync(0xffffffffu, m);
    if (lane == 0) sm.win = wk;
  }
  __syncthreads();
  const uint32_t win = sm.win;
  const int wrow = 2047 - (int)(win & 0x7FFu);
  const int wcta = wrow >> 4;
  const bool st_out = wid < 8 && (cta * 16 + row) != wrow;
  uint4* outp = reinterpret_cast<uint4*>(gout + (size_t)(cta * 16 + row) * D_) + 20 * gqi + tq;
  if (cta >= N1) {
    if (st_out) {
#pragma unroll
      for (int k = 0; k < 5; k++) outp[4 * k] = make_uint4(hreg[4 * k], hreg[4 * k + 1], hreg[4 * k + 2], hreg[4 * k + 3]);
    }
  }
  if (cta >= N1) {
#pragma unroll
    for (int i = 0; i < 4; i++) if (i < 3 || tid < 128) g_y2[cta * 1280 + tid + NTHR * i] = make_uint4(0, 0, 0, 0);
  }
  if (cta < N1 + N2) mbar_wait(&sm.mbarw);
  float* xs = &sm.z[0][0][0];
  float* part = xs + 2048;
  if (cta < N1) {
    if (tid < 80) {
      const uint4 v = poll4(&g_cand[wcta][0][tid]);
      float4* xp = reinterpret_cast<float4*>(xs + tid * 8);
      xp[0] = make_float4(lo_f(v.x), hi_f(v.x), lo_f(v.y), hi_f(v.y));
      xp[1] = make_float4(lo_f(v.z), hi_f(v.z), lo_f(v.w), hi_f(v.w));
    }
    __syncthreads();
    const int m = wid / 6, hc = (wid % 6) >> 1, rs = (wid & 1) * 32 + lane;
    float a[8];
#pragma unroll
    for (int j = 0; j < 8; j++) a[j] = 0.f;
#pragma unroll
    for (int it = 0; it < 10; it++) {
      const int r = rs + 64 * it;
      const uint4 wv = sm.w[m * 1920 + r * 3 + hc];
      const float x = xs[r];
      a[0] = fmaf(x, lo_f(wv.x), a[0]); a[1] = fmaf(x, hi_f(wv.x), a[1]);
      a[2] = fmaf(x, lo_f(wv.y), a[2]); a[3] = fmaf(x, hi_f(wv.y), a[3]);
      a[4] = fmaf(x, lo_f(wv.z), a[4]); a[5] = fmaf(x, hi_f(wv.z), a[5]);
      a[6] = fmaf(x, lo_f(wv.w), a[6]); a[7] = fmaf(x, hi_f(wv.w), a[7]);
    }
    {
      const bool up = lane & 16;
#pragma unroll
      for (int j = 0; j < 4; j++) {
        const float send = up ? a[j] : a[j + 4], keep = up ? a[j + 4] : a[j];
        a[j] = keep + __shfl_xor_sync(0xffffffffu, send, 16);
      }
      const bool up2 = lane & 8;
#pragma unroll
      for (int j = 0; j < 2; j++) {
        const float send = up2 ? a[j] : a[j + 2], keep = up2 ? a[j + 2] : a[j];
        a[j] = keep + __shfl_xor_sync(0xffffffffu, send, 8);
      }
      const bool up3 = lane & 4;
      const float send = up3 ? a[0] : a[1], keep = up3 ? a[1] : a[0];
      a[0] = keep + __shfl_xor_sync(0xffffffffu, send, 4);
      a[0] += __shfl_xor_sync(0xffffffffu, a[0], 2);
      a[0] += __shfl_xor_sync(0xffffffffu, a[0], 1);
      if ((lane & 3) == 0) part[wid * 8 + (lane >> 2)] = a[0];
    }
    __syncthreads();
    if (wid == 0) {
      uint32_t bits = 0;
      if (lane < 24) {
        const int hc2 = lane >> 3, j = lane & 7;
        const float gt = rbf(part[(2 * hc2) * 8 + j] + part[(2 * hc2 + 1) * 8 + j]);
        const float up = rbf(part[(6 + 2 * hc2) * 8 + j] + part[(6 + 2 * hc2 + 1) * 8 + j]);
        const float sg = rbf(gt / (1.f + __expf(-gt)));
        bits = __bfloat16_as_ushort(__float2bfloat16_rn(sg * up));
      }
      const uint32_t nb = __shfl_down_sync(0xffffffffu, bits, 1);
      const uint32_t pw = bits | (nb << 16);
      const uint32_t w1 = __shfl_down_sync(0xffffffffu, pw, 2), w2 = __shfl_down_sync(0xffffffffu, pw, 4), w3 = __shfl_down_sync(0xffffffffu, pw, 6);
      const uint4 mine = enc4(make_uint4(pw, w1, w2, w3));
#pragma unroll
      for (int i = 0; i < 4; i++) {
        const int t = lane + 32 * i;
        const int cons = t / 3, ck = t - 3 * cons;
        uint4 v;
        v.x = __shfl_sync(0xffffffffu, mine.x, 8 * ck); v.y = __shfl_sync(0xffffffffu, mine.y, 8 * ck);
        v.z = __shfl_sync(0xffffffffu, mine.z, 8 * ck); v.w = __shfl_sync(0xffffffffu, mine.w, 8 * ck);
        if (t < 3 * N2) st_pub4(&g_act[cons][cta * 3 + ck], v);
      }
      __syncwarp();
      bar_arrive(7, 384);
    } else {
      bar_sync(7, 384);
    }
#pragma unroll
    for (int i = 0; i < 4; i++) if (i < 3 || tid < 128) g_y2[cta * 1280 + tid + NTHR * i] = make_uint4(0, 0, 0, 0);
    if (st_out) {
#pragma unroll
      for (int k = 0; k < 5; k++) outp[4 * k] = make_uint4(hreg[4 * k], hreg[4 * k + 1], hreg[4 * k + 2], hreg[4 * k + 3]);
    }
  } else if (cta < N1 + N2) {
    const int j2 = cta - N1;
    uint4 rowv = make_uint4(0, 0, 0, 0);
    if (tid < 192) {
      const uint4 v = poll4(&g_act[j2][tid]);
      float4* xp = reinterpret_cast<float4*>(xs + tid * 8);
      xp[0] = make_float4(lo_f(v.x), hi_f(v.x), lo_f(v.y), hi_f(v.y));
      xp[1] = make_float4(lo_f(v.z), hi_f(v.z), lo_f(v.w), hi_f(v.w));
    } else if (tid < 196) {
      const int t = tid - 192;
      rowv = poll4(&g_cand[wcta][t >> 1][j2 * 2 + (t & 1)]);
      reinterpret_cast<uint4*>(part + 256)[t] = rowv;
    }
    __syncthreads();
    const int hc = lane & 1, rs = wid * 16 + (lane >> 1);
    float a[8];
#pragma unroll
    for (int j = 0; j < 8; j++) a[j] = 0.f;
#pragma unroll
    for (int it = 0; it < 8; it++) {
      const int r = rs + 192 * it;
      const uint4 wv = sm.w[r * 2 + hc];
      const float x = xs[r];
      a[0] = fmaf(x, lo_f(wv.x), a[0]); a[1] = fmaf(x, hi_f(wv.x), a[1]);
      a[2] = fmaf(x, lo_f(wv.y), a[2]); a[3] = fmaf(x, hi_f(wv.y), a[3]);
      a[4] = fmaf(x, lo_f(wv.z), a[4]); a[5] = fmaf(x, hi_f(wv.z), a[5]);
      a[6] = fmaf(x, lo_f(wv.w), a[6]); a[7] = fmaf(x, hi_f(wv.w), a[7]);
    }
    {
      const bool up = lane & 16;
#pragma unroll
      for (int j = 0; j < 4; j++) {
        const float send = up ? a[j] : a[j + 4], keep = up ? a[j + 4] : a[j];
        a[j] = keep + __shfl_xor_sync(0xffffffffu, send, 16);
      }
      const bool up2 = lane & 8;
#pragma unroll
      for (int j = 0; j < 2; j++) {
        const float send = up2 ? a[j] : a[j + 2], keep = up2 ? a[j + 2] : a[j];
        a[j] = keep + __shfl_xor_sync(0xffffffffu, send, 8);
      }
      const bool up3 = lane & 4;
      const float send = up3 ? a[0] : a[1], keep = up3 ? a[1] : a[0];
      a[0] = keep + __shfl_xor_sync(0xffffffffu, send, 4);
      a[0] += __shfl_xor_sync(0xffffffffu, a[0], 2);
      if ((lane & 2) == 0) part[wid * 16 + hc * 8 + (lane >> 2)] = a[0];
    }
    __syncthreads();
    if (tid < 16) {
      float y = 0.f;
#pragma unroll
      for (int i = 0; i < 12; i++) y += part[i * 16 + tid];
      const uint32_t ord = win >> 16;
      const uint32_t rb = (ord & 0x8000u) ? (ord ^ 0x8000u) : (ord ^ 0xFFFFu);
      const float r = __uint_as_float(rb << 16);
      const float sg = rbf(1.f / (1.f + __expf(-r)));
      const float yy = rbf(rbf(y) * sg);
      const unsigned short* rv = reinterpret_cast<const unsigned short*>(part + 256);
      const float hn = __uint_as_float((uint32_t)rv[tid] << 16), h = __uint_as_float((uint32_t)rv[16 + tid] << 16);
      gout[(size_t)wrow * D_ + j2 * 16 + tid] = __float2bfloat16_rn(h + rbf(hn + yy));
    }
  }
}

}

typedef CUresult (*EncodeFn)(CUtensorMap*, CUtensorMapDataType, cuuint32_t, void*, const cuuint64_t*, const cuuint64_t*,
                             const cuuint32_t*, const cuuint32_t*, CUtensorMapInterleave, CUtensorMapSwizzle,
                             CUtensorMapL2promotion, CUtensorMapFloatOOBfill);

extern "C" void kernel_launch(void* const* d_in, const int* in_sizes, int n_in, void* d_out, int out_size) {
  (void)in_sizes; (void)n_in; (void)out_size;
  static EncodeFn encode = nullptr;
  static CUtensorMap tmg, tmu, tmd;
  static void* cached[3] = {nullptr, nullptr, nullptr};
  if (!encode) {
    cudaFuncSetAttribute(fused_kernel, cudaFuncAttributeMaxDynamicSharedMemorySize, (int)sizeof(Smem));
    void* fn = nullptr;
    cudaDriverEntryPointQueryResult qr;
    cudaGetDriverEntryPoint("cuTensorMapEncodeTiled", &fn, cudaEnableDefault, &qr);
    encode = (EncodeFn)fn;
  }
  if (cached[0] != d_in[8] || cached[1] != d_in[9] || cached[2] != d_in[10]) {
    const cuuint32_t es[2] = {1, 1};
    {
      const cuuint64_t dims[2] = {F_, D_}, strides[1] = {F_ * 2};
      const cuuint32_t box[2] = {24, 160};
      encode(&tmg, CU_TENSOR_MAP_DATA_TYPE_BFLOAT16, 2, d_in[8], dims, strides, box, es, CU_TENSOR_MAP_INTERLEAVE_NONE,
             CU_TENSOR_MAP_SWIZZLE_NONE, CU_TENSOR_MAP_L2_PROMOTION_NONE, CU_TENSOR_MAP_FLOAT_OOB_FILL_NONE);
      encode(&tmu, CU_TENSOR_MAP_DATA_TYPE_BFLOAT16, 2, d_in[9], dims, strides, box, es, CU_TENSOR_MAP_INTERLEAVE_NONE,
             CU_TENSOR_MAP_SWIZZLE_NONE, CU_TENSOR_MAP_L2_PROMOTION_NONE, CU_TENSOR_MAP_FLOAT_OOB_FILL_NONE);
    }
    {
      const cuuint64_t dims[2] = {D_, F_}, strides[1] = {D_ * 2};
      const cuuint32_t box[2] = {16, 256};
      encode(&tmd, CU_TENSOR_MAP_DATA_TYPE_BFLOAT16, 2, d_in[10], dims, strides, box, es, CU_TENSOR_MAP_INTERLEAVE_NONE,
             CU_TENSOR_MAP_SWIZZLE_NONE, CU_TENSOR_MAP_L2_PROMOTION_NONE, CU_TENSOR_MAP_FLOAT_OOB_FILL_NONE);
    }
    cached[0] = d_in[8]; cached[1] = d_in[9]; cached[2] = d_in[10];
  }
  fused_kernel<<<NCTA, NTHR, sizeof(Smem), cudaStreamPerThread>>>(
      tmg, tmu, tmd, (const bf16*)d_in[0], (const bf16*)d_in[1], (const bf16*)d_in[2], (const bf16*)d_in[3],
      (const bf16*)d_in[4], (const bf16*)d_in[5], (const bf16*)d_in[7], (bf16*)d_out);
}
```

```cpp
#include <cuda_runtime.h>
#include <cuda_bf16.h>
#include <cuda.h>
#include <stdint.h>

namespace {

typedef __nv_bfloat16 bf16;
typedef __nv_bfloat162 bf162;

constexpr int S_ = 2048, D_ = 640, F_ = 1536;
constexpr int NCTA = 128, CPC = 5, NTHR = 384;
constexpr int UPAD = 136, USTR = 2192;
constexpr int TABW = 1040;
constexpr int ZPB = 132;
constexpr int QSTR = 648;
constexpr int N1 = 64;
constexpr int N2 = 40;
constexpr int SPIN_LIMIT = 1 << 19;
constexpr int POLL_NS = 100;

struct __align__(128) Smem {
  uint32_t tabA[3][2][TABW];
  uint32_t extra[1024];
  uint32_t tabB[2][2][TABW];
  bf16 u[CPC][USTR];
  float z[2][4][ZPB * 16];
  bf16 q[16][QSTR];
  alignas(128) uint4 w[3840];
  uint4 wr[80];
  alignas(16) float2 st[16][4];
  alignas(16) float2 stq[16][4];
  alignas(16) float rp[16][4];
  unsigned long long mbar;
  unsigned long long mbarw;
  unsigned long long mbarc;
  unsigned long long mbary;
  unsigned long long mbarh;
  uint32_t target;
  uint32_t target2;
  uint32_t target3;
  uint32_t best;
  uint32_t win;
};

__device__ uint4 g_kv[D_ * S_ / 8];
__device__ uint4 g_y2[D_ * S_ / 8];
__device__ uint32_t g_keys[NCTA][NCTA];
__device__ uint4 g_cand[NCTA][2][80];
__device__ uint4 g_act[N2][F_ / 8];
__device__ unsigned int g_ctr;
__device__ unsigned int g_ctr2;
__device__ unsigned int g_ctr3;

__device__ __forceinline__ uint32_t smem_u32(const void* p) { return (uint32_t)__cvta_generic_to_shared(p); }
__device__ __forceinline__ void wg_fence() { asm volatile("wgmma.fence.sync.aligned;" ::: "memory"); }
__device__ __forceinline__ void wg_commit() { asm volatile("wgmma.commit_group.sync.aligned;" ::: "memory"); }
template <int N> __device__ __forceinline__ void wg_wait() { asm volatile("wgmma.wait_group.sync.aligned %0;" ::"n"(N) : "memory"); }
__device__ __forceinline__ void bar_sync(int id, int n) { asm volatile("bar.sync %0, %1;" ::"r"(id), "r"(n) : "memory"); }
__device__ __forceinline__ void bar_arrive(int id, int n) { asm volatile("bar.arrive %0, %1;" ::"r"(id), "r"(n) : "memory"); }
__device__ __forceinline__ bf162 u2b(uint32_t u) { return *reinterpret_cast<bf162*>(&u); }
__device__ __forceinline__ uint32_t b2u(bf162 b) { return *reinterpret_cast<uint32_t*>(&b); }
__device__ __forceinline__ float lo_f(uint32_t u) { return __uint_as_float(u << 16); }
__device__ __forceinline__ float hi_f(uint32_t u) { return __uint_as_float(u & 0xFFFF0000u); }
__device__ __forceinline__ float rbf(float x) { return __bfloat162float(__float2bfloat16_rn(x)); }
__device__ __forceinline__ uint32_t pack2(float a, float b) { return b2u(__floats2bfloat162_rn(a, b)); }
__device__ __forceinline__ uint32_t enc(uint32_t w) { return max(~w, 1u); }
__device__ __forceinline__ uint4 enc4(uint4 v) { return make_uint4(enc(v.x), enc(v.y), enc(v.z), enc(v.w)); }
__device__ __forceinline__ uint4 ld_poll4(const uint4* p) {
  uint4 v;
  asm volatile("ld.relaxed.gpu.global.v4.u32 {%0,%1,%2,%3}, [%4];" : "=r"(v.x), "=r"(v.y), "=r"(v.z), "=r"(v.w) : "l"(p) : "memory");
  return v;
}
__device__ __forceinline__ bool ready4(uint4 v) { return v.x != 0u && v.y != 0u && v.z != 0u && v.w != 0u; }
__device__ __forceinline__ uint4 poll4(const uint4* p) {
  uint4 v = ld_poll4(p);
  int it = 0;
  while (!ready4(v) && ++it < SPIN_LIMIT) v = ld_poll4(p);
  return make_uint4(~v.x, ~v.y, ~v.z, ~v.w);
}
__device__ __forceinline__ void st_pub4(uint4* p, uint4 v) {
  asm volatile("st.relaxed.gpu.global.v4.u32 [%0], {%1,%2,%3,%4};" ::"l"(p), "r"(v.x), "r"(v.y), "r"(v.z), "r"(v.w) : "memory");
}
__device__ __forceinline__ void st_pub2(uint2* p, uint32_t a, uint32_t b) {
  asm volatile("st.relaxed.gpu.global.v2.u32 [%0], {%1,%2};" ::"l"(p), "r"(a), "r"(b) : "memory");
}
__device__ __forceinline__ void mma_bf16(float (&c)[4], uint32_t a0, uint32_t a2, uint32_t b0, uint32_t b1) {
  asm volatile("mma.sync.aligned.m16n8k16.row.col.f32.bf16.bf16.f32 {%0,%1,%2,%3}, {%4,%5,%6,%5}, {%7,%8}, {%0,%1,%2,%3};"
               : "+f"(c[0]), "+f"(c[1]), "+f"(c[2]), "+f"(c[3]) : "r"(a0), "r"(0u), "r"(a2), "r"(b0), "r"(b1));
}
__device__ __forceinline__ void mbar_wait(const unsigned long long* bar) {
  const uint32_t mb = smem_u32(bar);
  uint32_t ok = 0;
  int it = 0;
  while (!ok && ++it < SPIN_LIMIT)
    asm volatile("{ .reg .pred p; mbarrier.try_wait.parity.shared.b64 p, [%1], 0; selp.u32 %0, 1, 0, p; }" : "=r"(ok) : "r"(mb) : "memory");
}
__device__ __forceinline__ void bulk_g2s(void* dst, const void* src, uint32_t bytes, const unsigned long long* bar) {
  asm volatile("cp.async.bulk.shared::cluster.global.mbarrier::complete_tx::bytes [%0], [%1], %2, [%3];" ::"r"(smem_u32(dst)),
               "l"(src), "r"(bytes), "r"(smem_u32(bar)) : "memory");
}
__device__ __forceinline__ void mbar_expect(const unsigned long long* bar, uint32_t bytes) {
  asm volatile("mbarrier.arrive.expect_tx.shared.b64 _, [%0], %1;" ::"r"(smem_u32(bar)), "r"(bytes) : "memory");
}
__device__ __forceinline__ void mma_bf16x(float (&c)[4], uint32_t a0, uint32_t a1, uint32_t a2, uint32_t a3, uint32_t b0, uint32_t b1) {
  asm volatile("mma.sync.aligned.m16n8k16.row.col.f32.bf16.bf16.f32 {%0,%1,%2,%3}, {%4,%5,%6,%7}, {%8,%9}, {%0,%1,%2,%3};"
               : "+f"(c[0]), "+f"(c[1]), "+f"(c[2]), "+f"(c[3]) : "r"(a0), "r"(a1), "r"(a2), "r"(a3), "r"(b0), "r"(b1));
}
__device__ __forceinline__ float fdivr(float a, float d, float r) {
  float q = a * r;
  float e = fmaf(-q, d, a);
  return fmaf(e, r, q);
}

template <bool FIRST> __device__ __forceinline__ void wgmma32(float (&d)[16], const uint32_t* a, uint64_t desc) {
  if (FIRST) {
    asm volatile("wgmma.mma_async.sync.aligned.m64n32k16.f32.bf16.bf16 {%0,%1,%2,%3,%4,%5,%6,%7,%8,%9,%10,%11,%12,%13,%14,%15}, {%16,%17,%18,%19}, %20, 0, 1, 1, 0;"
                 : "+f"(d[0]), "+f"(d[1]), "+f"(d[2]), "+f"(d[3]), "+f"(d[4]), "+f"(d[5]), "+f"(d[6]), "+f"(d[7]),
                   "+f"(d[8]), "+f"(d[9]), "+f"(d[10]), "+f"(d[11]), "+f"(d[12]), "+f"(d[13]), "+f"(d[14]), "+f"(d[15])
                 : "r"(a[0]), "r"(a[1]), "r"(a[2]), "r"(a[3]), "l"(desc));
  } else {
    asm volatile("wgmma.mma_async.sync.aligned.m64n32k16.f32.bf16.bf16 {%0,%1,%2,%3,%4,%5,%6,%7,%8,%9,%10,%11,%12,%13,%14,%15}, {%16,%17,%18,%19}, %20, 1, 1, 1, 0;"
                 : "+f"(d[0]), "+f"(d[1]), "+f"(d[2]), "+f"(d[3]), "+f"(d[4]), "+f"(d[5]), "+f"(d[6]), "+f"(d[7]),
                   "+f"(d[8]), "+f"(d[9]), "+f"(d[10]), "+f"(d[11]), "+f"(d[12]), "+f"(d[13]), "+f"(d[14]), "+f"(d[15])
                 : "r"(a[0]), "r"(a[1]), "r"(a[2]), "r"(a[3]), "l"(desc));
  }
}

template <int G> __device__ __forceinline__ void load_a(uint32_t (&a)[8], const uint32_t* tp) {
#pragma unroll
  for (int q = 0; q < 2; q++) {
    const int e = 2 * G + q;
    a[4 * q + 0] = tp[-64 * e];
    a[4 * q + 1] = tp[-64 * e - 32];
    a[4 * q + 2] = tp[-64 * e + 4];
    a[4 * q + 3] = tp[-64 * e - 28];
  }
}
__device__ __forceinline__ void load_a_all(uint32_t (&a)[8][8], const uint32_t* tp) {
  load_a<0>(a[0], tp); load_a<1>(a[1], tp); load_a<2>(a[2], tp); load_a<3>(a[3], tp);
  load_a<4>(a[4], tp); load_a<5>(a[5], tp); load_a<6>(a[6], tp); load_a<7>(a[7], tp);
}
template <int G> __device__ __forceinline__ void issue_g(float (&acc)[8][16], uint32_t (&a)[8], uint64_t desc0) {
  wg_fence();
#pragma unroll
  for (int q = 0; q < 2; q++) {
#pragma unroll
    for (int b = G; b < 8; b++) {
      const int delta = 2 * b - (2 * G + q);
      if (G == 0 && q == 0) wgmma32<true>(acc[b], &a[4 * q], desc0 + (uint64_t)(int64_t)(16 * delta));
      else wgmma32<false>(acc[b], &a[4 * q], desc0 + (uint64_t)(int64_t)(16 * delta));
    }
  }
  wg_commit();
}
template <int B> __device__ __forceinline__ void fence_blk(float (&acc)[8][16]) {
#pragma unroll
  for (int i = 0; i < 16; i++) asm volatile("" : "+f"(acc[B][i])::"memory");
}
__device__ __forceinline__ void fence_a(uint32_t (&a)[8]) {
#pragma unroll
  for (int i = 0; i < 8; i++) asm volatile("" : "+r"(a[i])::"memory");
}
template <int B> __device__ __forceinline__ void sts_blk(float (&acc)[8][16], float* zw, int off_even, int off_odd) {
#pragma unroll
  for (int jj = 0; jj < 4; jj++) {
    const int j = 4 * B + jj;
    float p0 = acc[B][4 * jj + 0], p1 = acc[B][4 * jj + 1];
    if (jj > 0) { p0 += acc[B][4 * (jj - 1) + 2]; p1 += acc[B][4 * (jj - 1) + 3]; }
    else if (B > 0) { p0 += acc[B > 0 ? B - 1 : 0][14]; p1 += acc[B > 0 ? B - 1 : 0][15]; }
    zw[64 * j + off_even] = p0;
    zw[64 * j + off_odd] = p1;
  }
}
__device__ __forceinline__ int tab_off(int c) { return c == 4 ? 0 : (c + 1) * 2 * TABW + (c >= 2 ? 1024 : 0); }
__device__ __forceinline__ int tile_perm(int ch) { return ch ^ (((ch >> 3) & 3) << 1); }

__device__ __forceinline__ void wait_ctr(const unsigned int* ctr, uint32_t target) {
  uint32_t v;
  int it = 0;
  do {
    asm volatile("ld.acquire.gpu.global.u32 %0, [%1];" : "=r"(v) : "l"(ctr) : "memory");
  } while ((int)(v - target) < 0 && ++it < SPIN_LIMIT);
}

__device__ __forceinline__ float2 row_part_stats(const uint32_t (&x)[20]) {
  float cs[5][4];
#pragma unroll
  for (int k = 0; k < 5; k++) {
    cs[k][0] = cs[k][1] = cs[k][2] = cs[k][3] = 0.f;
    mma_bf16x(cs[k], x[4 * k + 0], x[4 * k + 2], x[4 * k + 1], x[4 * k + 3], 0x3F803F80u, 0x3F803F80u);
  }
  const float mean = ((((cs[0][0] + cs[0][2]) + (cs[1][0] + cs[1][2])) + ((cs[2][0] + cs[2][2]) + (cs[3][0] + cs[3][2]))) + (cs[4][0] + cs[4][2])) * (1.f / 160.f);
  float m2a = 0.f, m2b = 0.f, m2c = 0.f, m2d = 0.f;
#pragma unroll
  for (int i = 0; i < 20; i += 2) {
    const float a = lo_f(x[i]) - mean, b = hi_f(x[i]) - mean, c = lo_f(x[i + 1]) - mean, d = hi_f(x[i + 1]) - mean;
    m2a = fmaf(a, a, m2a); m2b = fmaf(b, b, m2b); m2c = fmaf(c, c, m2c); m2d = fmaf(d, d, m2d);
  }
  float m2 = (m2a + m2b) + (m2c + m2d);
  m2 += __shfl_xor_sync(0xffffffffu, m2, 1);
  m2 += __shfl_xor_sync(0xffffffffu, m2, 2);
  return make_float2(mean, m2);
}
template <bool EXACT> __device__ __forceinline__ void row_normalize(const float4* st, const uint32_t (&x)[20], uint32_t (&y)[20]) {
  const float4 p = st[0], q = st[1];
  const float mean = ((p.x + p.z) + (q.x + q.z)) * 0.25f;
  const float d0 = p.x - mean, d1 = p.z - mean, d2 = q.x - mean, d3 = q.z - mean;
  const float m2 = ((p.y + p.w) + (q.y + q.w)) + 160.f * ((d0 * d0 + d1 * d1) + (d2 * d2 + d3 * d3));
  const float hd = rbf(sqrtf(rbf(rbf(m2 * (1.f / D_)) + 1e-5f)));
  const float hr = __frcp_rn(hd);
  const bf162 hm2 = __float2bfloat162_rn(mean);
#pragma unroll
  for (int i = 0; i < 20; i++) {
    const uint32_t d = b2u(__hsub2_rn(u2b(x[i]), hm2));
    y[i] = EXACT ? pack2(fdivr(lo_f(d), hd, hr), fdivr(hi_f(d), hd, hr)) : pack2(lo_f(d) * hr, hi_f(d) * hr);
  }
}

__device__ __forceinline__ void reduce_half(Smem& sm, int c0, int c, int half, int wtid, uint32_t dvc, bool release) {
  const int rpb = wtid >> 1, re2 = wtid & 1;
  const int rsw = 3 * ((rpb >> 1) & 1);
  const int roff0 = 16 * rpb + 4 * ((2 * re2 + 0) ^ rsw);
  const int roff1 = 16 * rpb + 4 * ((2 * re2 + 1) ^ rsw);
  const int zg = c & 1;
  const bf162 d2 = u2b(dvc | (dvc << 16));
  bar_sync((half ? 3 : 9) + zg, 256);
  const float* zb = sm.z[zg][0] + half * 1024;
  float4 x[4][2];
#pragma unroll
  for (int ww = 0; ww < 4; ww++) {
    x[ww][0] = *reinterpret_cast<const float4*>(zb + ww * ZPB * 16 + roff0);
    x[ww][1] = *reinterpret_cast<const float4*>(zb + ww * ZPB * 16 + roff1);
  }
  const uint4 kvv = *reinterpret_cast<const uint4*>(&sm.u[c][UPAD + half * 1024 + wtid * 8]);
  if (release) bar_arrive(5 + zg, 256);
  uint4 o;
  o.x = pack2((x[0][0].x + x[1][0].x) + (x[2][0].x + x[3][0].x), (x[0][0].y + x[1][0].y) + (x[2][0].y + x[3][0].y));
  o.y = pack2((x[0][0].z + x[1][0].z) + (x[2][0].z + x[3][0].z), (x[0][0].w + x[1][0].w) + (x[2][0].w + x[3][0].w));
  o.z = pack2((x[0][1].x + x[1][1].x) + (x[2][1].x + x[3][1].x), (x[0][1].y + x[1][1].y) + (x[2][1].y + x[3][1].y));
  o.w = pack2((x[0][1].z + x[1][1].z) + (x[2][1].z + x[3][1].z), (x[0][1].w + x[1][1].w) + (x[2][1].w + x[3][1].w));
  o.x = b2u(__hadd2_rn(u2b(o.x), __hmul2_rn(u2b(kvv.x), d2)));
  o.y = b2u(__hadd2_rn(u2b(o.y), __hmul2_rn(u2b(kvv.y), d2)));
  o.z = b2u(__hadd2_rn(u2b(o.z), __hmul2_rn(u2b(kvv.z), d2)));
  o.w = b2u(__hadd2_rn(u2b(o.w), __hmul2_rn(u2b(kvv.w), d2)));
  st_pub4(g_y2 + ((64 * half + rpb) * 640 + c0 + c) * 2 + re2, enc4(o));
}

__device__ __forceinline__ void gather_kv(Smem& sm, int c0, int tid) {
  mbar_wait(&sm.mbarc);
  uint4 v[4];
  uint4* src = g_kv + c0 * 256 + tid;
#pragma unroll
  for (int i = 0; i < 4; i++) if (i < 3 || tid >= 256) v[i] = ld_poll4(src + NTHR * i - (i == 3 ? 256 : 0));
#pragma unroll
  for (int i = 0; i < 4; i++) {
    if (i < 3 || tid >= 256) {
      const int t = tid + NTHR * i - (i == 3 ? 256 : 0);
      int it = 0;
      while (!ready4(v[i]) && ++it < SPIN_LIMIT) { __nanosleep(POLL_NS); v[i] = ld_poll4(g_kv + c0 * 256 + t); }
      *reinterpret_cast<uint4*>(&sm.u[t >> 8][UPAD + (t & 255) * 8]) = make_uint4(~v[i].x, ~v[i].y, ~v[i].z, ~v[i].w);
    }
  }
  asm volatile("fence.proxy.async.shared::cta;" ::: "memory");
  __syncthreads();
}

__global__ void __launch_bounds__(NTHR, 1)
fused_kernel(const __grid_constant__ CUtensorMap tmg, const __grid_constant__ CUtensorMap tmu,
             const __grid_constant__ CUtensorMap tmd, const bf16* __restrict__ gq, const bf16* __restrict__ gk, const bf16* __restrict__ gv,
             const bf16* __restrict__ gsk, const bf16* __restrict__ gh, const bf16* __restrict__ gD,
             const bf16* __restrict__ gwr, bf16* __restrict__ gout) {
  extern __shared__ __align__(128) unsigned char smraw[];
  Smem& sm = *reinterpret_cast<Smem*>(smraw);
  const int tid = threadIdx.x;
  const int cta = blockIdx.x;
  const int c0 = cta * CPC;
  const int lane = tid & 31;
  const int wid = tid >> 5;

  {
    uint4* hs = reinterpret_cast<uint4*>(&sm.z[0][0][0]);
    const int oc = tid >> 2;
    const int r0 = cta * 16 + (tid & 3) * 4;
    uint4 kk[7], vv[4], sk[4];
    if (tid < 320) {
      const uint4* kp = reinterpret_cast<const uint4*>(gk) + (size_t)r0 * 80 + oc;
      const uint4* vp = reinterpret_cast<const uint4*>(gv) + (size_t)r0 * 80 + oc;
#pragma unroll
      for (int i = 0; i < 7; i++) kk[i] = (i >= 3 || r0 > 0) ? __ldg(kp + (i - 3) * 80) : make_uint4(0, 0, 0, 0);
#pragma unroll
      for (int i = 0; i < 4; i++) vv[i] = __ldg(vp + i * 80);
#pragma unroll
      for (int i = 0; i < 4; i++) sk[i] = __ldg(reinterpret_cast<const uint4*>(gsk) + oc * 4 + i);
    } else if (tid == 320) {
      asm volatile("mbarrier.init.shared.b64 [%0], 1;" ::"r"(smem_u32(&sm.mbarh)) : "memory");
      asm volatile("mbarrier.init.shared.b64 [%0], 1;" ::"r"(smem_u32(&sm.mbar)) : "memory");
      asm volatile("mbarrier.init.shared.b64 [%0], 1;" ::"r"(smem_u32(&sm.mbarw)) : "memory");
      asm volatile("mbarrier.init.shared.b64 [%0], 1;" ::"r"(smem_u32(&sm.mbarc)) : "memory");
      asm volatile("mbarrier.init.shared.b64 [%0], 1;" ::"r"(smem_u32(&sm.mbary)) : "memory");
      asm volatile("fence.proxy.async.shared::cta;" ::: "memory");
    } else if (tid == 352) {
      uint32_t v1, v2, v3;
      asm volatile("ld.relaxed.gpu.global.u32 %0, [%1];" : "=r"(v1) : "l"(&g_ctr) : "memory");
      asm volatile("ld.relaxed.gpu.global.u32 %0, [%1];" : "=r"(v2) : "l"(&g_ctr2) : "memory");
      asm volatile("ld.relaxed.gpu.global.u32 %0, [%1];" : "=r"(v3) : "l"(&g_ctr3) : "memory");
      sm.target = (v1 / NCTA + 1u) * NCTA;
      sm.target2 = (v2 / NCTA + 1u) * NCTA;
      sm.target3 = (v3 / NCTA + 1u) * NCTA;
    }
    if (tid < 320) bar_sync(6, 384); else { bar_arrive(6, 384); bar_sync(5, 64); }
    if (tid < 320) {
      uint32_t o[4][4];
#pragma unroll
      for (int p = 0; p < 4; p++) {
        const bf162 w0 = u2b(__byte_perm(sk[p].x, sk[p].z, 0x5410)), w1 = u2b(__byte_perm(sk[p].x, sk[p].z, 0x7632));
        const bf162 w2 = u2b(__byte_perm(sk[p].y, sk[p].w, 0x5410)), w3 = u2b(__byte_perm(sk[p].y, sk[p].w, 0x7632));
        uint32_t kv[4];
#pragma unroll
        for (int i = 0; i < 4; i++) {
          const uint32_t k0 = p == 0 ? kk[i].x : p == 1 ? kk[i].y : p == 2 ? kk[i].z : kk[i].w;
          const uint32_t k1 = p == 0 ? kk[i + 1].x : p == 1 ? kk[i + 1].y : p == 2 ? kk[i + 1].z : kk[i + 1].w;
          const uint32_t k2 = p == 0 ? kk[i + 2].x : p == 1 ? kk[i + 2].y : p == 2 ? kk[i + 2].z : kk[i + 2].w;
          const uint32_t k3 = p == 0 ? kk[i + 3].x : p == 1 ? kk[i + 3].y : p == 2 ? kk[i + 3].z : kk[i + 3].w;
          const uint32_t vx = p == 0 ? vv[i].x : p == 1 ? vv[i].y : p == 2 ? vv[i].z : vv[i].w;
          bf162 a = __hmul2_rn(u2b(k0), w3);
          a = __hadd2_rn(a, __hmul2_rn(u2b(k1), w2));
          a = __hadd2_rn(a, __hmul2_rn(u2b(k2), w1));
          a = __hadd2_rn(a, __hmul2_rn(u2b(k3), w0));
          kv[i] = b2u(__hmul2_rn(a, u2b(vx)));
        }
        o[p][0] = enc(__byte_perm(kv[0], kv[1], 0x5410)); o[p][1] = enc(__byte_perm(kv[2], kv[3], 0x5410));
        o[p][2] = enc(__byte_perm(kv[0], kv[1], 0x7632)); o[p][3] = enc(__byte_perm(kv[2], kv[3], 0x7632));
      }
      uint2* dst = reinterpret_cast<uint2*>(g_kv) + (size_t)(oc * 8) * 512 + (r0 >> 2);
#pragma unroll
      for (int p = 0; p < 4; p++) {
        st_pub2(dst + (2 * p) * 512, o[p][0], o[p][1]);
        st_pub2(dst + (2 * p + 1) * 512, o[p][2], o[p][3]);
      }
      if (wid == 0) bar_sync(4, 320); else bar_arrive(4, 320);
      if (tid == 0) {
        asm volatile("red.relaxed.gpu.global.add.u32 [%0], 1;" ::"l"(&g_ctr2) : "memory");
      }
      __syncwarp();
    } else {
      const int t0 = tid - 320;
      const uint4 zz = make_uint4(0, 0, 0, 0);
      if (tid == 320) {
        mbar_expect(&sm.mbarh, CPC * S_ * 2);
        bulk_g2s(hs, gh + (size_t)c0 * S_, CPC * S_ * 2, &sm.mbarh);
      }
      __syncwarp();
      for (int t = t0; t < CPC * 17; t += 64) *reinterpret_cast<uint4*>(&sm.u[t / 17][(t % 17) * 8]) = zz;
      if (t0 < 40) *reinterpret_cast<uint4*>(&sm.tabA[0][0][0] + tab_off(t0 >> 3) + ((t0 >> 2) & 1) * TABW + 1024 + 4 * (t0 & 3)) = zz;
      (&g_cand[cta][0][0])[t0] = zz;
      (&g_cand[cta][0][0])[64 + t0] = zz;
      if (t0 < 32) (&g_cand[cta][0][0])[128 + t0] = zz;
      else reinterpret_cast<uint4*>(&g_keys[cta][0])[t0 - 32] = zz;
      if (cta >= N1 && cta < N1 + N2) {
#pragma unroll
        for (int i = 0; i < 3; i++) g_act[cta - N1][t0 + 64 * i] = zz;
      }
    }
    mbar_wait(&sm.mbarh);
#pragma unroll
    for (int i = 0; i < 4; i++) {
      const int t = (NTHR - 1 - tid) + NTHR * i;
      if (t < CPC * 256) {
        uint32_t* tb = &sm.tabA[0][0][0] + tab_off(t >> 8) + (255 - (t & 255)) * 4;
        const uint4 h = hs[t];
        const uint32_t hp = (t & 255) ? reinterpret_cast<const uint32_t*>(hs)[4 * t - 1] : 0u;
        uint4 r1, rr;
        r1.x = __byte_perm(h.w, 0, 0x1032); r1.y = __byte_perm(h.z, 0, 0x1032);
        r1.z = __byte_perm(h.y, 0, 0x1032); r1.w = __byte_perm(h.x, 0, 0x1032);
        rr.x = __byte_perm(h.w, h.z, 0x7610); rr.y = __byte_perm(h.z, h.y, 0x7610);
        rr.z = __byte_perm(h.y, h.x, 0x7610); rr.w = __byte_perm(h.x, hp, 0x7610);
        *reinterpret_cast<uint4*>(tb) = rr;
        *reinterpret_cast<uint4*>(tb + TABW) = r1;
      }
    }
  }
  __syncthreads();

  const int wg = __shfl_sync(0xffffffffu, tid >> 7, 0);
  const int wtid = tid & 127;
  uint4* tile = reinterpret_cast<uint4*>(&sm.tabB[0][0][0]);
  if (wg < 2) {
    asm volatile("setmaxnreg.inc.sync.aligned.u32 224;");
    const int w = (tid >> 5) & 3, g = lane >> 2, tq = lane & 3;
    float* zw = sm.z[wg][w];
    const int sw = 3 * (((tq + w) >> 1) & 1);
    const int off_even = 16 * (tq + w) + 4 * ((0 + (g >> 2)) ^ sw) + (g & 3);
    const int off_odd = 16 * (tq + w) + 4 * ((2 + (g >> 2)) ^ sw) + (g & 3);
    uint32_t a[8][8];
    const uint32_t* tp0 = &sm.tabA[0][g & 1][1019 - 8 * w - (g >> 1) + tq];
    load_a_all(a, tp0 + tab_off(wg));
    float acc[8][16];
#pragma unroll
    for (int b = 0; b < 8; b++)
#pragma unroll
      for (int i = 0; i < 16; i++) acc[b][i] = 0.f;
    gather_kv(sm, c0, tid);
#pragma unroll 1
    for (int c = wg; c < CPC; c += 2) {
      const uint64_t desc = (uint64_t)((smem_u32(&sm.u[c][UPAD - 8]) & 0x3FFFF) >> 4) | ((uint64_t)1 << 16) | ((uint64_t)8 << 32);
      if (c > 0) bar_sync(1 + wg, 256);
      issue_g<0>(acc, a[0], desc);
      issue_g<1>(acc, a[1], desc);
      issue_g<2>(acc, a[2], desc);
      issue_g<3>(acc, a[3], desc);
      issue_g<4>(acc, a[4], desc);
      issue_g<5>(acc, a[5], desc);
      if (c + 1 < CPC) bar_arrive(1 + (wg ^ 1), 256);
      issue_g<6>(acc, a[6], desc);
      issue_g<7>(acc, a[7], desc);
      if (c >= 2) bar_sync(5 + wg, 256);
      wg_wait<4>();
      fence_blk<0>(acc); fence_blk<1>(acc); fence_blk<2>(acc); fence_blk<3>(acc);
      sts_blk<0>(acc, zw, off_even, off_odd);
      sts_blk<1>(acc, zw, off_even, off_odd);
      sts_blk<2>(acc, zw, off_even, off_odd);
      sts_blk<3>(acc, zw, off_even, off_odd);
      bar_arrive(9 + wg, 256);
      wg_wait<0>();
      fence_blk<4>(acc); fence_blk<5>(acc); fence_blk<6>(acc); fence_blk<7>(acc);
#pragma unroll
      for (int i = 0; i < 8; i++) fence_a(a[i]);
      sts_blk<4>(acc, zw, off_even, off_odd);
      sts_blk<5>(acc, zw, off_even, off_odd);
      sts_blk<6>(acc, zw, off_even, off_odd);
      sts_blk<7>(acc, zw, off_even, off_odd);
      bar_arrive(3 + wg, 256);
      if (c + 2 < CPC) load_a_all(a, tp0 + tab_off(c + 2));
    }
    asm volatile("setmaxnreg.dec.sync.aligned.u32 168;");
    if (wg == 1) {
      reduce_half(sm, c0, CPC - 1, 0, wtid, reinterpret_cast<const unsigned short*>(gD)[c0 + CPC - 1], false);
      bar_arrive(8, 256);
    }
  } else {
    asm volatile("setmaxnreg.dec.sync.aligned.u32 56;");
    if (((wtid & 15) >> 2) < ((wtid >> 4) & 3))
      *reinterpret_cast<uint4*>(&sm.z[wtid >> 6][(wtid >> 4) & 3][(wtid & 15) * 4]) = make_uint4(0, 0, 0, 0);
    if (wtid == 96) {
      __threadfence();
      asm volatile("red.relaxed.gpu.global.add.u32 [%0], 1;" ::"l"(&g_ctr) : "memory");
    }
    if (wtid == 64) {
      const unsigned target = sm.target2;
      uint32_t v;
      int it = 0;
      do {
        asm volatile("ld.relaxed.gpu.global.u32 %0, [%1];" : "=r"(v) : "l"(&g_ctr2) : "memory");
      } while ((int)(v - target) < 0 && ++it < SPIN_LIMIT);
      asm volatile("mbarrier.arrive.shared.b64 _, [%0];" ::"r"(smem_u32(&sm.mbarc)) : "memory");
    }
    __syncwarp();
    gather_kv(sm, c0, tid);
#pragma unroll
    for (int i = 0; i < 10; i++) g_kv[c0 * 256 + wtid + 128 * i] = make_uint4(0, 0, 0, 0);
    if (wtid == 96) wait_ctr(&g_ctr, sm.target);
    __syncwarp();
    if (wtid == 32) {
      const uint32_t mw = smem_u32(&sm.mbarw);
      mbar_expect(&sm.mbar, 17 * D_ * 2);
#pragma unroll 1
      for (int r = 0; r < 16; r++) bulk_g2s(&sm.q[r][0], gq + (size_t)(cta * 16 + r) * D_, D_ * 2, &sm.mbar);
      bulk_g2s(&sm.wr[0], gwr, D_ * 2, &sm.mbar);
      if (cta < N1) {
        asm volatile("mbarrier.arrive.expect_tx.shared.b64 _, [%0], %1;" ::"r"(mw), "r"(3840 * 16) : "memory");
#pragma unroll 1
        for (int i = 0; i < 4; i++) {
          asm volatile("cp.async.bulk.tensor.2d.shared::cluster.global.mbarrier::complete_tx::bytes [%0], [%1, {%3, %4}], [%2];" ::"r"(smem_u32(&sm.w[i * 480])),
                       "l"(&tmg), "r"(mw), "r"(cta * 24), "r"(i * 160) : "memory");
          asm volatile("cp.async.bulk.tensor.2d.shared::cluster.global.mbarrier::complete_tx::bytes [%0], [%1, {%3, %4}], [%2];" ::"r"(smem_u32(&sm.w[1920 + i * 480])),
                       "l"(&tmu), "r"(mw), "r"(cta * 24), "r"(i * 160) : "memory");
        }
      } else if (cta < N1 + N2) {
        asm volatile("mbarrier.arrive.expect_tx.shared.b64 _, [%0], %1;" ::"r"(mw), "r"(3072 * 16) : "memory");
#pragma unroll 1
        for (int i = 0; i < 6; i++)
          asm volatile("cp.async.bulk.tensor.2d.shared::cluster.global.mbarrier::complete_tx::bytes [%0], [%1, {%3, %4}], [%2];" ::"r"(smem_u32(&sm.w[i * 512])),
                       "l"(&tmd), "r"(mw), "r"((cta - N1) * 16), "r"(i * 256) : "memory");
      }
    }
    const uint32_t dvl = reinterpret_cast<const unsigned short*>(gD)[c0 + (lane < CPC ? lane : 0)];
#pragma unroll 1
    for (int c = 0; c < CPC; c++) {
      const uint32_t dvc = __shfl_sync(0xffffffffu, dvl, c);
      if (c < CPC - 1) reduce_half(sm, c0, c, 0, wtid, dvc, false);
      reduce_half(sm, c0, c, 1, wtid, dvc, c + 2 < CPC);
    }
    if (wid == 11) bar_sync(8, 256); else bar_arrive(8, 256);
    asm volatile("setmaxnreg.inc.sync.aligned.u32 168;");
  }

  if (tid == 352) {
    asm volatile("red.relaxed.gpu.global.add.u32 [%0], 1;" ::"l"(&g_ctr3) : "memory");
    wait_ctr(&g_ctr3, sm.target3);
    asm volatile("mbarrier.arrive.shared.b64 _, [%0];" ::"r"(smem_u32(&sm.mbary)) : "memory");
  }
  __syncwarp();
  const int g = lane >> 2, tq = lane & 3;
  const int hh = wid & 1, gqi = wid >> 1;
  const int row = hh * 8 + g;
  uint32_t hreg[20], hnreg[20];
  {
    const uint4* src = g_y2 + cta * 1280 + tid;
    uint4 v[4];
    if (wid < 8) {
      mbar_wait(&sm.mbar);
#pragma unroll
      for (int k = 0; k < 5; k++) {
        const uint4 qv4 = *reinterpret_cast<const uint4*>(&sm.q[row][32 * (5 * gqi + k) + 8 * tq]);
        hreg[4 * k] = qv4.x; hreg[4 * k + 1] = qv4.y; hreg[4 * k + 2] = qv4.z; hreg[4 * k + 3] = qv4.w;
      }
      const float2 ps = row_part_stats(hreg);
      if (tq == 0) sm.stq[row][gqi] = ps;
      bar_sync(7, 256);
      row_normalize<false>(reinterpret_cast<const float4*>(sm.stq[row]), hreg, hnreg);
    }
    mbar_wait(&sm.mbary);
#pragma unroll
    for (int i = 0; i < 4; i++) if (i < 3 || tid < 128) v[i] = ld_poll4(src + NTHR * i);
    int it = 0;
    bool all;
    do {
      all = true;
#pragma unroll
      for (int i = 0; i < 4; i++)
        if ((i < 3 || tid < 128) && !ready4(v[i])) { v[i] = ld_poll4(src + NTHR * i); all = false; }
    } while (!all && ++it < SPIN_LIMIT);
#pragma unroll
    for (int i = 0; i < 4; i++) {
      if (i < 3 || tid < 128) {
        const int t = tid + NTHR * i;
        tile[(t & 1) * 640 + tile_perm(t >> 1)] = make_uint4(~v[i].x, ~v[i].y, ~v[i].z, ~v[i].w);
      }
    }
  }
  __syncthreads();

  if (wid < 8) {
#pragma unroll
    for (int k = 0; k < 5; k++) {
      const int base = 32 * (5 * gqi + k);
      const int lch = base + 8 * ((lane & 7) >> 1) + 2 * (lane >> 3) + (lane & 1);
      uint32_t y[4];
      asm volatile("ldmatrix.sync.aligned.m8n8.x4.trans.shared.b16 {%0,%1,%2,%3}, [%4];"
                   : "=r"(y[0]), "=r"(y[1]), "=r"(y[2]), "=r"(y[3]) : "r"(smem_u32(&tile[hh * 640 + tile_perm(lch)])) : "memory");
#pragma unroll
      for (int i = 0; i < 4; i++)
        hreg[4 * k + i] = b2u(__hadd2_rn(u2b(hreg[4 * k + i]), __hmul2_rn(u2b(hnreg[4 * k + i]), u2b(y[i]))));
    }
    const float2 ps = row_part_stats(hreg);
    if (tq == 0) sm.st[row][gqi] = ps;
    bar_sync(7, 256);
    row_normalize<false>(reinterpret_cast<const float4*>(sm.st[row]), hreg, hnreg);
    float cr[5][4];
#pragma unroll
    for (int k = 0; k < 5; k++) {
      cr[k][0] = cr[k][1] = cr[k][2] = cr[k][3] = 0.f;
      const uint4 w4 = sm.wr[4 * (5 * gqi + k) + tq];
      mma_bf16(cr[k], hnreg[4 * k + 0], hnreg[4 * k + 1], w4.x, w4.y);
      mma_bf16(cr[k], hnreg[4 * k + 2], hnreg[4 * k + 3], w4.z, w4.w);
    }
    if (tq == 0) sm.rp[row][gqi] = ((cr[0][0] + cr[1][0]) + (cr[2][0] + cr[3][0])) + cr[4][0];
  }
  __syncthreads();
  uint32_t best;
  {
    const int rr = lane & 15;
    const float4 rp4 = *reinterpret_cast<const float4*>(sm.rp[rr]);
    const float r = (rp4.x + rp4.y) + (rp4.z + rp4.w);
    const uint32_t bits = __bfloat16_as_ushort(__float2bfloat16_rn(r));
    const uint32_t ord = (bits & 0x8000u) ? (bits ^ 0xFFFFu) : (bits ^ 0x8000u);
    const uint32_t key = (ord << 16) | 0x8000u | (uint32_t)(2047 - (cta * 16 + rr));
    best = __reduce_max_sync(0xffffffffu, key);
  }
  if (wid >= 8) asm volatile("st.relaxed.gpu.global.u32 [%0], %1;" ::"l"(&g_keys[tid - 256][cta]), "r"(best) : "memory");
  const int brow = (2047 - (int)(best & 0x7FFu)) - cta * 16;
  if (wid < 8 && row == brow) {
#pragma unroll
    for (int k = 0; k < 5; k++)
      st_pub4(&g_cand[cta][0][4 * (5 * gqi + k) + tq], enc4(make_uint4(hnreg[4 * k], hnreg[4 * k + 1], hnreg[4 * k + 2], hnreg[4 * k + 3])));
#pragma unroll
    for (int k = 0; k < 5; k++)
      st_pub4(&g_cand[cta][1][4 * (5 * gqi + k) + tq], enc4(make_uint4(hreg[4 * k], hreg[4 * k + 1], hreg[4 * k + 2], hreg[4 * k + 3])));
  }
#pragma unroll
  for (int i = 0; i < 20; i++) hreg[i] = b2u(__hadd2_rn(u2b(hreg[i]), u2b(hnreg[i])));
  if (wid == 11) {
    const uint4* kp = reinterpret_cast<const uint4*>(&g_keys[cta][0]) + lane;
    uint4 v = ld_poll4(kp);
    int it = 0;
    while (!ready4(v) && ++it < SPIN_LIMIT) v = ld_poll4(kp);
    const uint32_t m = max(max(v.x, v.y), max(v.z, v.w));
    const uint32_t wk = __reduce_max_sync(0xffffffffu, m);
    if (lane == 0) sm.win = wk;
  }
  __syncthreads();
  const uint32_t win = sm.win;
  const int wrow = 2047 - (int)(win & 0x7FFu);
  const int wcta = wrow >> 4;
  const bool st_out = wid < 8 && (cta * 16 + row) != wrow;
  uint4* outp = reinterpret_cast<uint4*>(gout + (size_t)(cta * 16 + row) * D_) + 20 * gqi + tq;
  if (cta >= N1) {
    if (st_out) {
#pragma unroll
      for (int k = 0; k < 5; k++) outp[4 * k] = make_uint4(hreg[4 * k], hreg[4 * k + 1], hreg[4 * k + 2], hreg[4 * k + 3]);
    }
  }
  if (cta >= N1) {
#pragma unroll
    for (int i = 0; i < 4; i++) if (i < 3 || tid < 128) g_y2[cta * 1280 + tid + NTHR * i] = make_uint4(0, 0, 0, 0);
  }
  if (cta < N1 + N2) mbar_wait(&sm.mbarw);
  float* xs = &sm.z[0][0][0];
  float* part = xs + 2048;
  if (cta < N1) {
    if (tid < 80) {
      const uint4 v = poll4(&g_cand[wcta][0][tid]);
      float4* xp = reinterpret_cast<float4*>(xs + tid * 8);
      xp[0] = make_float4(lo_f(v.x), hi_f(v.x), lo_f(v.y), hi_f(v.y));
      xp[1] = make_float4(lo_f(v.z), hi_f(v.z), lo_f(v.w), hi_f(v.w));
    }
    __syncthreads();
    const int m = wid / 6, hc = (wid % 6) >> 1, rs = (wid & 1) * 32 + lane;
    float a[8];
#pragma unroll
    for (int j = 0; j < 8; j++) a[j] = 0.f;
#pragma unroll
    for (int it = 0; it < 10; it++) {
      const int r = rs + 64 * it;
      const uint4 wv = sm.w[m * 1920 + r * 3 + hc];
      const float x = xs[r];
      a[0] = fmaf(x, lo_f(wv.x), a[0]); a[1] = fmaf(x, hi_f(wv.x), a[1]);
      a[2] = fmaf(x, lo_f(wv.y), a[2]); a[3] = fmaf(x, hi_f(wv.y), a[3]);
      a[4] = fmaf(x, lo_f(wv.z), a[4]); a[5] = fmaf(x, hi_f(wv.z), a[5]);
      a[6] = fmaf(x, lo_f(wv.w), a[6]); a[7] = fmaf(x, hi_f(wv.w), a[7]);
    }
    {
      const bool up = lane & 16;
#pragma unroll
      for (int j = 0; j < 4; j++) {
        const float send = up ? a[j] : a[j + 4], keep = up ? a[j + 4] : a[j];
        a[j] = keep + __shfl_xor_sync(0xffffffffu, send, 16);
      }
      const bool up2 = lane & 8;
#pragma unroll
      for (int j = 0; j < 2; j++) {
        const float send = up2 ? a[j] : a[j + 2], keep = up2 ? a[j + 2] : a[j];
        a[j] = keep + __shfl_xor_sync(0xffffffffu, send, 8);
      }
      const bool up3 = lane & 4;
      const float send = up3 ? a[0] : a[1], keep = up3 ? a[1] : a[0];
      a[0] = keep + __shfl_xor_sync(0xffffffffu, send, 4);
      a[0] += __shfl_xor_sync(0xffffffffu, a[0], 2);
      a[0] += __shfl_xor_sync(0xffffffffu, a[0], 1);
      if ((lane & 3) == 0) part[wid * 8 + (lane >> 2)] = a[0];
    }
    __syncthreads();
    if (wid == 0) {
      uint32_t bits = 0;
      if (lane < 24) {
        const int hc2 = lane >> 3, j = lane & 7;
        const float gt = rbf(part[(2 * hc2) * 8 + j] + part[(2 * hc2 + 1) * 8 + j]);
        const float up = rbf(part[(6 + 2 * hc2) * 8 + j] + part[(6 + 2 * hc2 + 1) * 8 + j]);
        const float sg = rbf(gt / (1.f + __expf(-gt)));
        bits = __bfloat16_as_ushort(__float2bfloat16_rn(sg * up));
      }
      const uint32_t nb = __shfl_down_sync(0xffffffffu, bits, 1);
      const uint32_t pw = bits | (nb << 16);
      const uint32_t w1 = __shfl_down_sync(0xffffffffu, pw, 2), w2 = __shfl_down_sync(0xffffffffu, pw, 4), w3 = __shfl_down_sync(0xffffffffu, pw, 6);
      const uint4 mine = enc4(make_uint4(pw, w1, w2, w3));
#pragma unroll
      for (int i = 0; i < 4; i++) {
        const int t = lane + 32 * i;
        const int cons = t / 3, ck = t - 3 * cons;
        uint4 v;
        v.x = __shfl_sync(0xffffffffu, mine.x, 8 * ck); v.y = __shfl_sync(0xffffffffu, mine.y, 8 * ck);
        v.z = __shfl_sync(0xffffffffu, mine.z, 8 * ck); v.w = __shfl_sync(0xffffffffu, mine.w, 8 * ck);
        if (t < 3 * N2) st_pub4(&g_act[cons][cta * 3 + ck], v);
      }
      __syncwarp();
      bar_arrive(7, 384);
    } else {
      bar_sync(7, 384);
    }
#pragma unroll
    for (int i = 0; i < 4; i++) if (i < 3 || tid < 128) g_y2[cta * 1280 + tid + NTHR * i] = make_uint4(0, 0, 0, 0);
    if (st_out) {
#pragma unroll
      for (int k = 0; k < 5; k++) outp[4 * k] = make_uint4(hreg[4 * k], hreg[4 * k + 1], hreg[4 * k + 2], hreg[4 * k + 3]);
    }
  } else if (cta < N1 + N2) {
    const int j2 = cta - N1;
    uint4 rowv = make_uint4(0, 0, 0, 0);
    if (tid < 192) {
      const uint4 v = poll4(&g_act[j2][tid]);
      float4* xp = reinterpret_cast<float4*>(xs + tid * 8);
      xp[0] = make_float4(lo_f(v.x), hi_f(v.x), lo_f(v.y), hi_f(v.y));
      xp[1] = make_float4(lo_f(v.z), hi_f(v.z), lo_f(v.w), hi_f(v.w));
    } else if (tid < 196) {
      const int t = tid - 192;
      rowv = poll4(&g_cand[wcta][t >> 1][j2 * 2 + (t & 1)]);
      reinterpret_cast<uint4*>(part + 256)[t] = rowv;
    }
    __syncthreads();
    const int hc = lane & 1, rs = wid * 16 + (lane >> 1);
    float a[8];
#pragma unroll
    for (int j = 0; j < 8; j++) a[j] = 0.f;
#pragma unroll
    for (int it = 0; it < 8; it++) {
      const int r = rs + 192 * it;
      const uint4 wv = sm.w[r * 2 + hc];
      const float x = xs[r];
      a[0] = fmaf(x, lo_f(wv.x), a[0]); a[1] = fmaf(x, hi_f(wv.x), a[1]);
      a[2] = fmaf(x, lo_f(wv.y), a[2]); a[3] = fmaf(x, hi_f(wv.y), a[3]);
      a[4] = fmaf(x, lo_f(wv.z), a[4]); a[5] = fmaf(x, hi_f(wv.z), a[5]);
      a[6] = fmaf(x, lo_f(wv.w), a[6]); a[7] = fmaf(x, hi_f(wv.w), a[7]);
    }
    {
      const bool up = lane & 16;
#pragma unroll
      for (int j = 0; j < 4; j++) {
        const float send = up ? a[j] : a[j + 4], keep = up ? a[j + 4] : a[j];
        a[j] = keep + __shfl_xor_sync(0xffffffffu, send, 16);
      }
      const bool up2 = lane & 8;
#pragma unroll
      for (int j = 0; j < 2; j++) {
        const float send = up2 ? a[j] : a[j + 2], keep = up2 ? a[j + 2] : a[j];
        a[j] = keep + __shfl_xor_sync(0xffffffffu, send, 8);
      }
      const bool up3 = lane & 4;
      const float send = up3 ? a[0] : a[1], keep = up3 ? a[1] : a[0];
      a[0] = keep + __shfl_xor_sync(0xffffffffu, send, 4);
      a[0] += __shfl_xor_sync(0xffffffffu, a[0], 2);
      if ((lane & 2) == 0) part[wid * 16 + hc * 8 + (lane >> 2)] = a[0];
    }
    __syncthreads();
    if (tid < 16) {
      float y = 0.f;
#pragma unroll
      for (int i = 0; i < 12; i++) y += part[i * 16 + tid];
      const uint32_t ord = win >> 16;
      const uint32_t rb = (ord & 0x8000u) ? (ord ^ 0x8000u) : (ord ^ 0xFFFFu);
      const float r = __uint_as_float(rb << 16);
      const float sg = rbf(1.f / (1.f + __expf(-r)));
      const float yy = rbf(rbf(y) * sg);
      const unsigned short* rv = reinterpret_cast<const unsigned short*>(part + 256);
      const float hn = __uint_as_float((uint32_t)rv[tid] << 16), h = __uint_as_float((uint32_t)rv[16 + tid] << 16);
      gout[(size_t)wrow * D_ + j2 * 16 + tid] = __float2bfloat16_rn(h + rbf(hn + yy));
    }
  }
}

}

typedef CUresult (*EncodeFn)(CUtensorMap*, CUtensorMapDataType, cuuint32_t, void*, const cuuint64_t*, const cuuint64_t*,
                             const cuuint32_t*, const cuuint32_t*, CUtensorMapInterleave, CUtensorMapSwizzle,
                             CUtensorMapL2promotion, CUtensorMapFloatOOBfill);

extern "C" void kernel_launch(void* const* d_in, const int* in_sizes, int n_in, void* d_out, int out_size) {
  (void)in_sizes; (void)n_in; (void)out_size;
  static EncodeFn encode = nullptr;
  static CUtensorMap tmg, tmu, tmd;
  static void* cached[3] = {nullptr, nullptr, nullptr};
  if (!encode) {
    cudaFuncSetAttribute(fused_kernel, cudaFuncAttributeMaxDynamicSharedMemorySize, (int)sizeof(Smem));
    void* fn = nullptr;
    cudaDriverEntryPointQueryResult qr;
    cudaGetDriverEntryPoint("cuTensorMapEncodeTiled", &fn, cudaEnableDefault, &qr);
    encode = (EncodeFn)fn;
  }
  if (cached[0] != d_in[8] || cached[1] != d_in[9] || cached[2] != d_in[10]) {
    const cuuint32_t es[2] = {1, 1};
    {
      const cuuint64_t dims[2] = {F_, D_}, strides[1] = {F_ * 2};
      const cuuint32_t box[2] = {24, 160};
      encode(&tmg, CU_TENSOR_MAP_DATA_TYPE_BFLOAT16, 2, d_in[8], dims, strides, box, es, CU_TENSOR_MAP_INTERLEAVE_NONE,
             CU_TENSOR_MAP_SWIZZLE_NONE, CU_TENSOR_MAP_L2_PROMOTION_NONE, CU_TENSOR_MAP_FLOAT_OOB_FILL_NONE);
      encode(&tmu, CU_TENSOR_MAP_DATA_TYPE_BFLOAT16, 2, d_in[9], dims, strides, box, es, CU_TENSOR_MAP_INTERLEAVE_NONE,
             CU_TENSOR_MAP_SWIZZLE_NONE, CU_TENSOR_MAP_L2_PROMOTION_NONE, CU_TENSOR_MAP_FLOAT_OOB_FILL_NONE);
    }
    {
      const cuuint64_t dims[2] = {D_, F_}, strides[1] = {D_ * 2};
      const cuuint32_t box[2] = {16, 256};
      encode(&tmd, CU_TENSOR_MAP_DATA_TYPE_BFLOAT16, 2, d_in[10], dims, strides, box, es, CU_TENSOR_MAP_INTERLEAVE_NONE,
             CU_TENSOR_MAP_SWIZZLE_NONE, CU_TENSOR_MAP_L2_PROMOTION_NONE, CU_TENSOR_MAP_FLOAT_OOB_FILL_NONE);
    }
    cached[0] = d_in[8]; cached[1] = d_in[9]; cached[2] = d_in[10];
  }
  fused_kernel<<<NCTA, NTHR, sizeof(Smem), cudaStreamPerThread>>>(
      tmg, tmu, tmd, (const bf16*)d_in[0], (const bf16*)d_in[1], (const bf16*)d_in[2], (const bf16*)d_in[3],
      (const bf16*)d_in[4], (const bf16*)d_in[5], (const bf16*)d_in[7], (bf16*)d_out);
}
```

```cpp
#include <cuda_runtime.h>
#include <cuda_bf16.h>
#include <cuda.h>
#include <stdint.h>

namespace {

typedef __nv_bfloat16 bf16;
typedef __nv_bfloat162 bf162;

constexpr int S_ = 2048, D_ = 640, F_ = 1536;
constexpr int NCTA = 128, CPC = 5, NTHR = 384;
constexpr int UPAD = 136, USTR = 2192;
constexpr int TABW = 1040;
constexpr int ZPB = 132;
constexpr int QSTR = 648;
constexpr int N1 = 64;
constexpr int N2 = 40;
constexpr int SPIN_LIMIT = 1 << 19;
constexpr int POLL_NS = 100;

struct __align__(128) Smem {
  uint32_t tabA[3][2][TABW];
  uint32_t extra[1024];
  uint32_t tabB[2][2][TABW];
  bf16 u[CPC][USTR];
  float z[2][4][ZPB * 16];
  bf16 q[16][QSTR];
  alignas(128) uint4 w[3840];
  uint4 wr[80];
  alignas(16) float2 st[16][4];
  alignas(16) float2 stq[16][4];
  alignas(16) float rp[16][4];
  unsigned long long mbar;
  unsigned long long mbarw;
  unsigned long long mbarc;
  unsigned long long mbary;
  unsigned long long mbarh;
  uint32_t target;
  uint32_t target2;
  uint32_t target3;
  uint32_t best;
  uint32_t win;
};

__device__ uint4 g_kv[D_ * S_ / 8];
__device__ uint4 g_y2[D_ * S_ / 8];
__device__ uint32_t g_keys[NCTA][NCTA];
__device__ uint4 g_cand[NCTA][2][80];
__device__ uint4 g_act[N2][F_ / 8];
__device__ __align__(256) unsigned int g_ctrs[3][64];
#define g_ctr g_ctrs[0][0]
#define g_ctr2 g_ctrs[1][0]
#define g_ctr3 g_ctrs[2][0]

__device__ __forceinline__ uint32_t smem_u32(const void* p) { return (uint32_t)__cvta_generic_to_shared(p); }
__device__ __forceinline__ void wg_fence() { asm volatile("wgmma.fence.sync.aligned;" ::: "memory"); }
__device__ __forceinline__ void wg_commit() { asm volatile("wgmma.commit_group.sync.aligned;" ::: "memory"); }
template <int N> __device__ __forceinline__ void wg_wait() { asm volatile("wgmma.wait_group.sync.aligned %0;" ::"n"(N) : "memory"); }
__device__ __forceinline__ void bar_sync(int id, int n) { asm volatile("bar.sync %0, %1;" ::"r"(id), "r"(n) : "memory"); }
__device__ __forceinline__ void bar_arrive(int id, int n) { asm volatile("bar.arrive %0, %1;" ::"r"(id), "r"(n) : "memory"); }
__device__ __forceinline__ bf162 u2b(uint32_t u) { return *reinterpret_cast<bf162*>(&u); }
__device__ __forceinline__ uint32_t b2u(bf162 b) { return *reinterpret_cast<uint32_t*>(&b); }
__device__ __forceinline__ float lo_f(uint32_t u) { return __uint_as_float(u << 16); }
__device__ __forceinline__ float hi_f(uint32_t u) { return __uint_as_float(u & 0xFFFF0000u); }
__device__ __forceinline__ float rbf(float x) { return __bfloat162float(__float2bfloat16_rn(x)); }
__device__ __forceinline__ uint32_t pack2(float a, float b) { return b2u(__floats2bfloat162_rn(a, b)); }
__device__ __forceinline__ uint32_t enc(uint32_t w) { return max(~w, 1u); }
__device__ __forceinline__ uint4 enc4(uint4 v) { return make_uint4(enc(v.x), enc(v.y), enc(v.z), enc(v.w)); }
__device__ __forceinline__ uint4 ld_poll4(const uint4* p) {
  uint4 v;
  asm volatile("ld.relaxed.gpu.global.v4.u32 {%0,%1,%2,%3}, [%4];" : "=r"(v.x), "=r"(v.y), "=r"(v.z), "=r"(v.w) : "l"(p) : "memory");
  return v;
}
__device__ __forceinline__ bool ready4(uint4 v) { return v.x != 0u && v.y != 0u && v.z != 0u && v.w != 0u; }
__device__ __forceinline__ uint4 poll4(const uint4* p) {
  uint4 v = ld_poll4(p);
  int it = 0;
  while (!ready4(v) && ++it < SPIN_LIMIT) v = ld_poll4(p);
  return make_uint4(~v.x, ~v.y, ~v.z, ~v.w);
}
__device__ __forceinline__ void st_pub4(uint4* p, uint4 v) {
  asm volatile("st.relaxed.gpu.global.v4.u32 [%0], {%1,%2,%3,%4};" ::"l"(p), "r"(v.x), "r"(v.y), "r"(v.z), "r"(v.w) : "memory");
}
__device__ __forceinline__ void st_pub2(uint2* p, uint32_t a, uint32_t b) {
  asm volatile("st.relaxed.gpu.global.v2.u32 [%0], {%1,%2};" ::"l"(p), "r"(a), "r"(b) : "memory");
}
__device__ __forceinline__ void mma_bf16(float (&c)[4], uint32_t a0, uint32_t a2, uint32_t b0, uint32_t b1) {
  asm volatile("mma.sync.aligned.m16n8k16.row.col.f32.bf16.bf16.f32 {%0,%1,%2,%3}, {%4,%5,%6,%5}, {%7,%8}, {%0,%1,%2,%3};"
               : "+f"(c[0]), "+f"(c[1]), "+f"(c[2]), "+f"(c[3]) : "r"(a0), "r"(0u), "r"(a2), "r"(b0), "r"(b1));
}
__device__ __forceinline__ void mbar_wait(const unsigned long long* bar) {
  const uint32_t mb = smem_u32(bar);
  uint32_t ok = 0;
  int it = 0;
  while (!ok && ++it < SPIN_LIMIT)
    asm volatile("{ .reg .pred p; mbarrier.try_wait.parity.shared.b64 p, [%1], 0; selp.u32 %0, 1, 0, p; }" : "=r"(ok) : "r"(mb) : "memory");
}
__device__ __forceinline__ void bulk_g2s(void* dst, const void* src, uint32_t bytes, const unsigned long long* bar) {
  asm volatile("cp.async.bulk.shared::cluster.global.mbarrier::complete_tx::bytes [%0], [%1], %2, [%3];" ::"r"(smem_u32(dst)),
               "l"(src), "r"(bytes), "r"(smem_u32(bar)) : "memory");
}
__device__ __forceinline__ void mbar_expect(const unsigned long long* bar, uint32_t bytes) {
  asm volatile("mbarrier.arrive.expect_tx.shared.b64 _, [%0], %1;" ::"r"(smem_u32(bar)), "r"(bytes) : "memory");
}
__device__ __forceinline__ void mma_bf16x(float (&c)[4], uint32_t a0, uint32_t a1, uint32_t a2, uint32_t a3, uint32_t b0, uint32_t b1) {
  asm volatile("mma.sync.aligned.m16n8k16.row.col.f32.bf16.bf16.f32 {%0,%1,%2,%3}, {%4,%5,%6,%7}, {%8,%9}, {%0,%1,%2,%3};"
               : "+f"(c[0]), "+f"(c[1]), "+f"(c[2]), "+f"(c[3]) : "r"(a0), "r"(a1), "r"(a2), "r"(a3), "r"(b0), "r"(b1));
}
__device__ __forceinline__ float fdivr(float a, float d, float r) {
  float q = a * r;
  float e = fmaf(-q, d, a);
  return fmaf(e, r, q);
}

template <bool FIRST> __device__ __forceinline__ void wgmma32(float (&d)[16], const uint32_t* a, uint64_t desc) {
  if (FIRST) {
    asm volatile("wgmma.mma_async.sync.aligned.m64n32k16.f32.bf16.bf16 {%0,%1,%2,%3,%4,%5,%6,%7,%8,%9,%10,%11,%12,%13,%14,%15}, {%16,%17,%18,%19}, %20, 0, 1, 1, 0;"
                 : "+f"(d[0]), "+f"(d[1]), "+f"(d[2]), "+f"(d[3]), "+f"(d[4]), "+f"(d[5]), "+f"(d[6]), "+f"(d[7]),
                   "+f"(d[8]), "+f"(d[9]), "+f"(d[10]), "+f"(d[11]), "+f"(d[12]), "+f"(d[13]), "+f"(d[14]), "+f"(d[15])
                 : "r"(a[0]), "r"(a[1]), "r"(a[2]), "r"(a[3]), "l"(desc));
  } else {
    asm volatile("wgmma.mma_async.sync.aligned.m64n32k16.f32.bf16.bf16 {%0,%1,%2,%3,%4,%5,%6,%7,%8,%9,%10,%11,%12,%13,%14,%15}, {%16,%17,%18,%19}, %20, 1, 1, 1, 0;"
                 : "+f"(d[0]), "+f"(d[1]), "+f"(d[2]), "+f"(d[3]), "+f"(d[4]), "+f"(d[5]), "+f"(d[6]), "+f"(d[7]),
                   "+f"(d[8]), "+f"(d[9]), "+f"(d[10]), "+f"(d[11]), "+f"(d[12]), "+f"(d[13]), "+f"(d[14]), "+f"(d[15])
                 : "r"(a[0]), "r"(a[1]), "r"(a[2]), "r"(a[3]), "l"(desc));
  }
}

template <int G> __device__ __forceinline__ void load_a(uint32_t (&a)[8], const uint32_t* tp) {
#pragma unroll
  for (int q = 0; q < 2; q++) {
    const int e = 2 * G + q;
    a[4 * q + 0] = tp[-64 * e];
    a[4 * q + 1] = tp[-64 * e - 32];
    a[4 * q + 2] = tp[-64 * e + 4];
    a[4 * q + 3] = tp[-64 * e - 28];
  }
}
__device__ __forceinline__ void load_a_all(uint32_t (&a)[8][8], const uint32_t* tp) {
  load_a<0>(a[0], tp); load_a<1>(a[1], tp); load_a<2>(a[2], tp); load_a<3>(a[3], tp);
  load_a<4>(a[4], tp); load_a<5>(a[5], tp); load_a<6>(a[6], tp); load_a<7>(a[7], tp);
}
template <int G> __device__ __forceinline__ void issue_g(float (&acc)[8][16], uint32_t (&a)[8], uint64_t desc0) {
  wg_fence();
#pragma unroll
  for (int q = 0; q < 2; q++) {
#pragma unroll
    for (int b = G; b < 8; b++) {
      const int delta = 2 * b - (2 * G + q);
      if (G == 0 && q == 0) wgmma32<true>(acc[b], &a[4 * q], desc0 + (uint64_t)(int64_t)(16 * delta));
      else wgmma32<false>(acc[b], &a[4 * q], desc0 + (uint64_t)(int64_t)(16 * delta));
    }
  }
  wg_commit();
}
template <int B> __device__ __forceinline__ void fence_blk(float (&acc)[8][16]) {
#pragma unroll
  for (int i = 0; i < 16; i++) asm volatile("" : "+f"(acc[B][i])::"memory");
}
__device__ __forceinline__ void fence_a(uint32_t (&a)[8]) {
#pragma unroll
  for (int i = 0; i < 8; i++) asm volatile("" : "+r"(a[i])::"memory");
}
template <int B> __device__ __forceinline__ void sts_blk(float (&acc)[8][16], float* zw, int off_even, int off_odd) {
#pragma unroll
  for (int jj = 0; jj < 4; jj++) {
    const int j = 4 * B + jj;
    float p0 = acc[B][4 * jj + 0], p1 = acc[B][4 * jj + 1];
    if (jj > 0) { p0 += acc[B][4 * (jj - 1) + 2]; p1 += acc[B][4 * (jj - 1) + 3]; }
    else if (B > 0) { p0 += acc[B > 0 ? B - 1 : 0][14]; p1 += acc[B > 0 ? B - 1 : 0][15]; }
    zw[64 * j + off_even] = p0;
    zw[64 * j + off_odd] = p1;
  }
}
__device__ __forceinline__ int tab_off(int c) { return c == 4 ? 0 : (c + 1) * 2 * TABW + (c >= 2 ? 1024 : 0); }
__device__ __forceinline__ int tile_perm(int ch) { return ch ^ (((ch >> 3) & 3) << 1); }

__device__ __forceinline__ void wait_ctr(const unsigned int* ctr, uint32_t target) {
  uint32_t v;
  int it = 0;
  do {
    asm volatile("ld.acquire.gpu.global.u32 %0, [%1];" : "=r"(v) : "l"(ctr) : "memory");
  } while ((int)(v - target) < 0 && ++it < SPIN_LIMIT);
}

__device__ __forceinline__ float2 row_part_stats(const uint32_t (&x)[20]) {
  float cs[5][4];
#pragma unroll
  for (int k = 0; k < 5; k++) {
    cs[k][0] = cs[k][1] = cs[k][2] = cs[k][3] = 0.f;
    mma_bf16x(cs[k], x[4 * k + 0], x[4 * k + 2], x[4 * k + 1], x[4 * k + 3], 0x3F803F80u, 0x3F803F80u);
  }
  const float mean = ((((cs[0][0] + cs[0][2]) + (cs[1][0] + cs[1][2])) + ((cs[2][0] + cs[2][2]) + (cs[3][0] + cs[3][2]))) + (cs[4][0] + cs[4][2])) * (1.f / 160.f);
  float m2a = 0.f, m2b = 0.f, m2c = 0.f, m2d = 0.f;
#pragma unroll
  for (int i = 0; i < 20; i += 2) {
    const float a = lo_f(x[i]) - mean, b = hi_f(x[i]) - mean, c = lo_f(x[i + 1]) - mean, d = hi_f(x[i + 1]) - mean;
    m2a = fmaf(a, a, m2a); m2b = fmaf(b, b, m2b); m2c = fmaf(c, c, m2c); m2d = fmaf(d, d, m2d);
  }
  float m2 = (m2a + m2b) + (m2c + m2d);
  m2 += __shfl_xor_sync(0xffffffffu, m2, 1);
  m2 += __shfl_xor_sync(0xffffffffu, m2, 2);
  return make_float2(mean, m2);
}
template <bool EXACT> __device__ __forceinline__ void row_normalize(const float4* st, const uint32_t (&x)[20], uint32_t (&y)[20]) {
  const float4 p = st[0], q = st[1];
  const float mean = ((p.x + p.z) + (q.x + q.z)) * 0.25f;
  const float d0 = p.x - mean, d1 = p.z - mean, d2 = q.x - mean, d3 = q.z - mean;
  const float m2 = ((p.y + p.w) + (q.y + q.w)) + 160.f * ((d0 * d0 + d1 * d1) + (d2 * d2 + d3 * d3));
  const float hd = rbf(sqrtf(rbf(rbf(m2 * (1.f / D_)) + 1e-5f)));
  const float hr = __frcp_rn(hd);
  const bf162 hm2 = __float2bfloat162_rn(mean);
#pragma unroll
  for (int i = 0; i < 20; i++) {
    const uint32_t d = b2u(__hsub2_rn(u2b(x[i]), hm2));
    y[i] = EXACT ? pack2(fdivr(lo_f(d), hd, hr), fdivr(hi_f(d), hd, hr)) : pack2(lo_f(d) * hr, hi_f(d) * hr);
  }
}

__device__ __forceinline__ void gather_kv(Smem& sm, int c0, int tid) {
  mbar_wait(&sm.mbarc);
  uint4 v[4];
  uint4* src = g_kv + c0 * 256 + tid;
#pragma unroll
  for (int i = 0; i < 4; i++) if (i < 3 || tid >= 256) v[i] = ld_poll4(src + NTHR * i - (i == 3 ? 256 : 0));
#pragma unroll
  for (int i = 0; i < 4; i++) {
    if (i < 3 || tid >= 256) {
      const int t = tid + NTHR * i - (i == 3 ? 256 : 0);
      int it = 0;
      while (!ready4(v[i]) && ++it < SPIN_LIMIT) { __nanosleep(POLL_NS); v[i] = ld_poll4(g_kv + c0 * 256 + t); }
      *reinterpret_cast<uint4*>(&sm.u[t >> 8][UPAD + (t & 255) * 8]) = make_uint4(~v[i].x, ~v[i].y, ~v[i].z, ~v[i].w);
    }
  }
  asm volatile("fence.proxy.async.shared::cta;" ::: "memory");
  __syncthreads();
}

__global__ void __launch_bounds__(NTHR, 1)
fused_kernel(const __grid_constant__ CUtensorMap tmg, const __grid_constant__ CUtensorMap tmu,
             const __grid_constant__ CUtensorMap tmd, const bf16* __restrict__ gq, const bf16* __restrict__ gk, const bf16* __restrict__ gv,
             const bf16* __restrict__ gsk, const bf16* __restrict__ gh, const bf16* __restrict__ gD,
             const bf16* __restrict__ gwr, bf16* __restrict__ gout) {
  extern __shared__ __align__(128) unsigned char smraw[];
  Smem& sm = *reinterpret_cast<Smem*>(smraw);
  const int tid = threadIdx.x;
  const int cta = blockIdx.x;
  const int c0 = cta * CPC;
  const int lane = tid & 31;
  const int wid = tid >> 5;

  {
    uint4* hs = reinterpret_cast<uint4*>(&sm.z[0][0][0]);
    const int oc = tid >> 2;
    const int r0 = cta * 16 + (tid & 3) * 4;
    uint4 kk[7], vv[4], sk[4];
    if (tid < 320) {
      const uint4* kp = reinterpret_cast<const uint4*>(gk) + (size_t)r0 * 80 + oc;
      const uint4* vp = reinterpret_cast<const uint4*>(gv) + (size_t)r0 * 80 + oc;
#pragma unroll
      for (int i = 0; i < 7; i++) kk[i] = (i >= 3 || r0 > 0) ? __ldg(kp + (i - 3) * 80) : make_uint4(0, 0, 0, 0);
#pragma unroll
      for (int i = 0; i < 4; i++) vv[i] = __ldg(vp + i * 80);
#pragma unroll
      for (int i = 0; i < 4; i++) sk[i] = __ldg(reinterpret_cast<const uint4*>(gsk) + oc * 4 + i);
    } else if (tid == 320) {
      asm volatile("mbarrier.init.shared.b64 [%0], 1;" ::"r"(smem_u32(&sm.mbarh)) : "memory");
      asm volatile("mbarrier.init.shared.b64 [%0], 1;" ::"r"(smem_u32(&sm.mbar)) : "memory");
      asm volatile("mbarrier.init.shared.b64 [%0], 1;" ::"r"(smem_u32(&sm.mbarw)) : "memory");
      asm volatile("mbarrier.init.shared.b64 [%0], 1;" ::"r"(smem_u32(&sm.mbarc)) : "memory");
      asm volatile("mbarrier.init.shared.b64 [%0], 1;" ::"r"(smem_u32(&sm.mbary)) : "memory");
      asm volatile("fence.proxy.async.shared::cta;" ::: "memory");
    } else if (tid == 352) {
      uint32_t v1, v2, v3;
      asm volatile("ld.relaxed.gpu.global.u32 %0, [%1];" : "=r"(v1) : "l"(&g_ctr) : "memory");
      asm volatile("ld.relaxed.gpu.global.u32 %0, [%1];" : "=r"(v2) : "l"(&g_ctr2) : "memory");
      asm volatile("ld.relaxed.gpu.global.u32 %0, [%1];" : "=r"(v3) : "l"(&g_ctr3) : "memory");
      sm.target = (v1 / NCTA + 1u) * NCTA;
      sm.target2 = (v2 / NCTA + 1u) * NCTA;
      sm.target3 = (v3 / NCTA + 1u) * NCTA;
    }
    if (tid < 320) bar_sync(6, 384); else { bar_arrive(6, 384); bar_sync(5, 64); }
    if (tid < 320) {
      uint32_t o[4][4];
#pragma unroll
      for (int p = 0; p < 4; p++) {
        const bf162 w0 = u2b(__byte_perm(sk[p].x, sk[p].z, 0x5410)), w1 = u2b(__byte_perm(sk[p].x, sk[p].z, 0x7632));
        const bf162 w2 = u2b(__byte_perm(sk[p].y, sk[p].w, 0x5410)), w3 = u2b(__byte_perm(sk[p].y, sk[p].w, 0x7632));
        uint32_t kv[4];
#pragma unroll
        for (int i = 0; i < 4; i++) {
          const uint32_t k0 = p == 0 ? kk[i].x : p == 1 ? kk[i].y : p == 2 ? kk[i].z : kk[i].w;
          const uint32_t k1 = p == 0 ? kk[i + 1].x : p == 1 ? kk[i + 1].y : p == 2 ? kk[i + 1].z : kk[i + 1].w;
          const uint32_t k2 = p == 0 ? kk[i + 2].x : p == 1 ? kk[i + 2].y : p == 2 ? kk[i + 2].z : kk[i + 2].w;
          const uint32_t k3 = p == 0 ? kk[i + 3].x : p == 1 ? kk[i + 3].y : p == 2 ? kk[i + 3].z : kk[i + 3].w;
          const uint32_t vx = p == 0 ? vv[i].x : p == 1 ? vv[i].y : p == 2 ? vv[i].z : vv[i].w;
          bf162 a = __hmul2_rn(u2b(k0), w3);
          a = __hadd2_rn(a, __hmul2_rn(u2b(k1), w2));
          a = __hadd2_rn(a, __hmul2_rn(u2b(k2), w1));
          a = __hadd2_rn(a, __hmul2_rn(u2b(k3), w0));
          kv[i] = b2u(__hmul2_rn(a, u2b(vx)));
        }
        o[p][0] = enc(__byte_perm(kv[0], kv[1], 0x5410)); o[p][1] = enc(__byte_perm(kv[2], kv[3], 0x5410));
        o[p][2] = enc(__byte_perm(kv[0], kv[1], 0x7632)); o[p][3] = enc(__byte_perm(kv[2], kv[3], 0x7632));
      }
      uint2* dst = reinterpret_cast<uint2*>(g_kv) + (size_t)(oc * 8) * 512 + (r0 >> 2);
#pragma unroll
      for (int p = 0; p < 4; p++) {
        st_pub2(dst + (2 * p) * 512, o[p][0], o[p][1]);
        st_pub2(dst + (2 * p + 1) * 512, o[p][2], o[p][3]);
      }
      if (wid == 0) bar_sync(4, 320); else bar_arrive(4, 320);
      if (tid == 0) {
        asm volatile("red.relaxed.gpu.global.add.u32 [%0], 1;" ::"l"(&g_ctr2) : "memory");
      }
      __syncwarp();
    } else {
      const int t0 = tid - 320;
      const uint4 zz = make_uint4(0, 0, 0, 0);
      if (tid == 320) {
        mbar_expect(&sm.mbarh, CPC * S_ * 2);
        bulk_g2s(hs, gh + (size_t)c0 * S_, CPC * S_ * 2, &sm.mbarh);
      }
      __syncwarp();
      for (int t = t0; t < CPC * 17; t += 64) *reinterpret_cast<uint4*>(&sm.u[t / 17][(t % 17) * 8]) = zz;
      if (t0 < 40) *reinterpret_cast<uint4*>(&sm.tabA[0][0][0] + tab_off(t0 >> 3) + ((t0 >> 2) & 1) * TABW + 1024 + 4 * (t0 & 3)) = zz;
      (&g_cand[cta][0][0])[t0] = zz;
      (&g_cand[cta][0][0])[64 + t0] = zz;
      if (t0 < 32) (&g_cand[cta][0][0])[128 + t0] = zz;
      else reinterpret_cast<uint4*>(&g_keys[cta][0])[t0 - 32] = zz;
      if (cta >= N1 && cta < N1 + N2) {
#pragma unroll
        for (int i = 0; i < 3; i++) g_act[cta - N1][t0 + 64 * i] = zz;
      }
    }
    mbar_wait(&sm.mbarh);
#pragma unroll
    for (int i = 0; i < 4; i++) {
      const int t = (NTHR - 1 - tid) + NTHR * i;
      if (t < CPC * 256) {
        uint32_t* tb = &sm.tabA[0][0][0] + tab_off(t >> 8) + (255 - (t & 255)) * 4;
        const uint4 h = hs[t];
        const uint32_t hp = (t & 255) ? reinterpret_cast<const uint32_t*>(hs)[4 * t - 1] : 0u;
        uint4 r1, rr;
        r1.x = __byte_perm(h.w, 0, 0x1032); r1.y = __byte_perm(h.z, 0, 0x1032);
        r1.z = __byte_perm(h.y, 0, 0x1032); r1.w = __byte_perm(h.x, 0, 0x1032);
        rr.x = __byte_perm(h.w, h.z, 0x7610); rr.y = __byte_perm(h.z, h.y, 0x7610);
        rr.z = __byte_perm(h.y, h.x, 0x7610); rr.w = __byte_perm(h.x, hp, 0x7610);
        *reinterpret_cast<uint4*>(tb) = rr;
        *reinterpret_cast<uint4*>(tb + TABW) = r1;
      }
    }
  }
  __syncthreads();

  const int wg = __shfl_sync(0xffffffffu, tid >> 7, 0);
  const int wtid = tid & 127;
  uint4* tile = reinterpret_cast<uint4*>(&sm.tabB[0][0][0]);
  if (wg < 2) {
    asm volatile("setmaxnreg.inc.sync.aligned.u32 224;");
    const int w = (tid >> 5) & 3, g = lane >> 2, tq = lane & 3;
    float* zw = sm.z[wg][w];
    const int sw = 3 * (((tq + w) >> 1) & 1);
    const int off_even = 16 * (tq + w) + 4 * ((0 + (g >> 2)) ^ sw) + (g & 3);
    const int off_odd = 16 * (tq + w) + 4 * ((2 + (g >> 2)) ^ sw) + (g & 3);
    uint32_t a[8][8];
    const uint32_t* tp0 = &sm.tabA[0][g & 1][1019 - 8 * w - (g >> 1) + tq];
    load_a_all(a, tp0 + tab_off(wg));
    float acc[8][16];
#pragma unroll
    for (int b = 0; b < 8; b++)
#pragma unroll
      for (int i = 0; i < 16; i++) acc[b][i] = 0.f;
    gather_kv(sm, c0, tid);
#pragma unroll 1
    for (int c = wg; c < CPC; c += 2) {
      const uint64_t desc = (uint64_t)((smem_u32(&sm.u[c][UPAD - 8]) & 0x3FFFF) >> 4) | ((uint64_t)1 << 16) | ((uint64_t)8 << 32);
      if (c > 0) bar_sync(1 + wg, 256);
      issue_g<0>(acc, a[0], desc);
      issue_g<1>(acc, a[1], desc);
      issue_g<2>(acc, a[2], desc);
      issue_g<3>(acc, a[3], desc);
      issue_g<4>(acc, a[4], desc);
      issue_g<5>(acc, a[5], desc);
      if (c + 1 < CPC) bar_arrive(1 + (wg ^ 1), 256);
      issue_g<6>(acc, a[6], desc);
      issue_g<7>(acc, a[7], desc);
      if (c >= 2) bar_sync(5 + wg, 256);
      wg_wait<4>();
      fence_blk<0>(acc); fence_blk<1>(acc); fence_blk<2>(acc); fence_blk<3>(acc);
      sts_blk<0>(acc, zw, off_even, off_odd);
      sts_blk<1>(acc, zw, off_even, off_odd);
      sts_blk<2>(acc, zw, off_even, off_odd);
      sts_blk<3>(acc, zw, off_even, off_odd);
      bar_arrive(9 + wg, 256);
      wg_wait<0>();
      fence_blk<4>(acc); fence_blk<5>(acc); fence_blk<6>(acc); fence_blk<7>(acc);
#pragma unroll
      for (int i = 0; i < 8; i++) fence_a(a[i]);
      sts_blk<4>(acc, zw, off_even, off_odd);
      sts_blk<5>(acc, zw, off_even, off_odd);
      sts_blk<6>(acc, zw, off_even, off_odd);
      sts_blk<7>(acc, zw, off_even, off_odd);
      bar_arrive(3 + wg, 256);
      if (c + 2 < CPC) load_a_all(a, tp0 + tab_off(c + 2));
    }
    asm volatile("setmaxnreg.dec.sync.aligned.u32 168;");
  } else {
    asm volatile("setmaxnreg.dec.sync.aligned.u32 56;");
    if (((wtid & 15) >> 2) < ((wtid >> 4) & 3))
      *reinterpret_cast<uint4*>(&sm.z[wtid >> 6][(wtid >> 4) & 3][(wtid & 15) * 4]) = make_uint4(0, 0, 0, 0);
    if (wtid == 96) {
      __threadfence();
      asm volatile("red.relaxed.gpu.global.add.u32 [%0], 1;" ::"l"(&g_ctr) : "memory");
    }
    if (wtid == 64) {
      const unsigned target = sm.target2;
      uint32_t v;
      int it = 0;
      do {
        asm volatile("ld.relaxed.gpu.global.u32 %0, [%1];" : "=r"(v) : "l"(&g_ctr2) : "memory");
      } while ((int)(v - target) < 0 && ++it < SPIN_LIMIT);
      asm volatile("mbarrier.arrive.shared.b64 _, [%0];" ::"r"(smem_u32(&sm.mbarc)) : "memory");
    }
    __syncwarp();
    gather_kv(sm, c0, tid);
#pragma unroll
    for (int i = 0; i < 10; i++) g_kv[c0 * 256 + wtid + 128 * i] = make_uint4(0, 0, 0, 0);
    if (wtid == 96) wait_ctr(&g_ctr, sm.target);
    __syncwarp();
    if (wtid == 32) {
      const uint32_t mw = smem_u32(&sm.mbarw);
      mbar_expect(&sm.mbar, 17 * D_ * 2);
#pragma unroll 1
      for (int r = 0; r < 16; r++) bulk_g2s(&sm.q[r][0], gq + (size_t)(cta * 16 + r) * D_, D_ * 2, &sm.mbar);
      bulk_g2s(&sm.wr[0], gwr, D_ * 2, &sm.mbar);
      if (cta < N1) {
        asm volatile("mbarrier.arrive.expect_tx.shared.b64 _, [%0], %1;" ::"r"(mw), "r"(3840 * 16) : "memory");
#pragma unroll 1
        for (int i = 0; i < 4; i++) {
          asm volatile("cp.async.bulk.tensor.2d.shared::cluster.global.mbarrier::complete_tx::bytes [%0], [%1, {%3, %4}], [%2];" ::"r"(smem_u32(&sm.w[i * 480])),
                       "l"(&tmg), "r"(mw), "r"(cta * 24), "r"(i * 160) : "memory");
          asm volatile("cp.async.bulk.tensor.2d.shared::cluster.global.mbarrier::complete_tx::bytes [%0], [%1, {%3, %4}], [%2];" ::"r"(smem_u32(&sm.w[1920 + i * 480])),
                       "l"(&tmu), "r"(mw), "r"(cta * 24), "r"(i * 160) : "memory");
        }
      } else if (cta < N1 + N2) {
        asm volatile("mbarrier.arrive.expect_tx.shared.b64 _, [%0], %1;" ::"r"(mw), "r"(3072 * 16) : "memory");
#pragma unroll 1
        for (int i = 0; i < 6; i++)
          asm volatile("cp.async.bulk.tensor.2d.shared::cluster.global.mbarrier::complete_tx::bytes [%0], [%1, {%3, %4}], [%2];" ::"r"(smem_u32(&sm.w[i * 512])),
                       "l"(&tmd), "r"(mw), "r"((cta - N1) * 16), "r"(i * 256) : "memory");
      }
    }
    const int rpb = wtid >> 1, re2 = wtid & 1;
    const int rsw = 3 * ((rpb >> 1) & 1);
    const int roff0 = 16 * rpb + 4 * ((2 * re2 + 0) ^ rsw);
    const int roff1 = 16 * rpb + 4 * ((2 * re2 + 1) ^ rsw);
    const uint32_t dvl = reinterpret_cast<const unsigned short*>(gD)[c0 + (lane < CPC ? lane : 0)];
#pragma unroll 1
    for (int c = 0; c < CPC; c++) {
      const int zg = c & 1;
      const uint32_t dvc = __shfl_sync(0xffffffffu, dvl, c);
      const bf162 d2 = u2b(dvc | (dvc << 16));
#pragma unroll
      for (int half = 0; half < 2; half++) {
        bar_sync((half ? 3 : 9) + zg, 256);
        const float* zb = sm.z[zg][0] + half * 1024;
        float4 x[4][2];
#pragma unroll
        for (int ww = 0; ww < 4; ww++) {
          x[ww][0] = *reinterpret_cast<const float4*>(zb + ww * ZPB * 16 + roff0);
          x[ww][1] = *reinterpret_cast<const float4*>(zb + ww * ZPB * 16 + roff1);
        }
        const int sidx = half * 1024 + wtid * 8;
        const uint4 kvv = *reinterpret_cast<const uint4*>(&sm.u[c][UPAD + sidx]);
        if (half == 1 && c + 2 < CPC) bar_arrive(5 + zg, 256);
        uint4 o;
        o.x = pack2((x[0][0].x + x[1][0].x) + (x[2][0].x + x[3][0].x), (x[0][0].y + x[1][0].y) + (x[2][0].y + x[3][0].y));
        o.y = pack2((x[0][0].z + x[1][0].z) + (x[2][0].z + x[3][0].z), (x[0][0].w + x[1][0].w) + (x[2][0].w + x[3][0].w));
        o.z = pack2((x[0][1].x + x[1][1].x) + (x[2][1].x + x[3][1].x), (x[0][1].y + x[1][1].y) + (x[2][1].y + x[3][1].y));
        o.w = pack2((x[0][1].z + x[1][1].z) + (x[2][1].z + x[3][1].z), (x[0][1].w + x[1][1].w) + (x[2][1].w + x[3][1].w));
        o.x = b2u(__hadd2_rn(u2b(o.x), __hmul2_rn(u2b(kvv.x), d2)));
        o.y = b2u(__hadd2_rn(u2b(o.y), __hmul2_rn(u2b(kvv.y), d2)));
        o.z = b2u(__hadd2_rn(u2b(o.z), __hmul2_rn(u2b(kvv.z), d2)));
        o.w = b2u(__hadd2_rn(u2b(o.w), __hmul2_rn(u2b(kvv.w), d2)));
        st_pub4(g_y2 + ((64 * half + rpb) * 640 + c0 + c) * 2 + re2, enc4(o));
      }
    }
    if (wid == 11) bar_sync(8, 128); else bar_arrive(8, 128);
    asm volatile("setmaxnreg.inc.sync.aligned.u32 168;");
  }

  if (tid == 352) {
    asm volatile("red.relaxed.gpu.global.add.u32 [%0], 1;" ::"l"(&g_ctr3) : "memory");
    wait_ctr(&g_ctr3, sm.target3);
    asm volatile("mbarrier.arrive.shared.b64 _, [%0];" ::"r"(smem_u32(&sm.mbary)) : "memory");
  }
  __syncwarp();
  const int g = lane >> 2, tq = lane & 3;
  const int hh = wid & 1, gqi = wid >> 1;
  const int row = hh * 8 + g;
  uint32_t hreg[20], hnreg[20];
  {
    const uint4* src = g_y2 + cta * 1280 + tid;
    uint4 v[4];
    if (wid < 8) {
      mbar_wait(&sm.mbar);
#pragma unroll
      for (int k = 0; k < 5; k++) {
        const uint4 qv4 = *reinterpret_cast<const uint4*>(&sm.q[row][32 * (5 * gqi + k) + 8 * tq]);
        hreg[4 * k] = qv4.x; hreg[4 * k + 1] = qv4.y; hreg[4 * k + 2] = qv4.z; hreg[4 * k + 3] = qv4.w;
      }
      const float2 ps = row_part_stats(hreg);
      if (tq == 0) sm.stq[row][gqi] = ps;
      bar_sync(7, 256);
      row_normalize<false>(reinterpret_cast<const float4*>(sm.stq[row]), hreg, hnreg);
    }
    mbar_wait(&sm.mbary);
#pragma unroll
    for (int i = 0; i < 4; i++) if (i < 3 || tid < 128) v[i] = ld_poll4(src + NTHR * i);
    int it = 0;
    bool all;
    do {
      all = true;
#pragma unroll
      for (int i = 0; i < 4; i++)
        if ((i < 3 || tid < 128) && !ready4(v[i])) { v[i] = ld_poll4(src + NTHR * i); all = false; }
    } while (!all && ++it < SPIN_LIMIT);
#pragma unroll
    for (int i = 0; i < 4; i++) {
      if (i < 3 || tid < 128) {
        const int t = tid + NTHR * i;
        tile[(t & 1) * 640 + tile_perm(t >> 1)] = make_uint4(~v[i].x, ~v[i].y, ~v[i].z, ~v[i].w);
      }
    }
  }
  __syncthreads();

  if (wid < 8) {
#pragma unroll
    for (int k = 0; k < 5; k++) {
      const int base = 32 * (5 * gqi + k);
      const int lch = base + 8 * ((lane & 7) >> 1) + 2 * (lane >> 3) + (lane & 1);
      uint32_t y[4];
      asm volatile("ldmatrix.sync.aligned.m8n8.x4.trans.shared.b16 {%0,%1,%2,%3}, [%4];"
                   : "=r"(y[0]), "=r"(y[1]), "=r"(y[2]), "=r"(y[3]) : "r"(smem_u32(&tile[hh * 640 + tile_perm(lch)])) : "memory");
#pragma unroll
      for (int i = 0; i < 4; i++)
        hreg[4 * k + i] = b2u(__hadd2_rn(u2b(hreg[4 * k + i]), __hmul2_rn(u2b(hnreg[4 * k + i]), u2b(y[i]))));
    }
    const float2 ps = row_part_stats(hreg);
    if (tq == 0) sm.st[row][gqi] = ps;
    bar_sync(7, 256);
    row_normalize<false>(reinterpret_cast<const float4*>(sm.st[row]), hreg, hnreg);
    float cr[5][4];
#pragma unroll
    for (int k = 0; k < 5; k++) {
      cr[k][0] = cr[k][1] = cr[k][2] = cr[k][3] = 0.f;
      const uint4 w4 = sm.wr[4 * (5 * gqi + k) + tq];
      mma_bf16(cr[k], hnreg[4 * k + 0], hnreg[4 * k + 1], w4.x, w4.y);
      mma_bf16(cr[k], hnreg[4 * k + 2], hnreg[4 * k + 3], w4.z, w4.w);
    }
    if (tq == 0) sm.rp[row][gqi] = ((cr[0][0] + cr[1][0]) + (cr[2][0] + cr[3][0])) + cr[4][0];
  }
  __syncthreads();
  uint32_t best;
  {
    const int rr = lane & 15;
    const float4 rp4 = *reinterpret_cast<const float4*>(sm.rp[rr]);
    const float r = (rp4.x + rp4.y) + (rp4.z + rp4.w);
    const uint32_t bits = __bfloat16_as_ushort(__float2bfloat16_rn(r));
    const uint32_t ord = (bits & 0x8000u) ? (bits ^ 0xFFFFu) : (bits ^ 0x8000u);
    const uint32_t key = (ord << 16) | 0x8000u | (uint32_t)(2047 - (cta * 16 + rr));
    best = __reduce_max_sync(0xffffffffu, key);
  }
  if (wid >= 8) asm volatile("st.relaxed.gpu.global.u32 [%0], %1;" ::"l"(&g_keys[tid - 256][cta]), "r"(best) : "memory");
  const int brow = (2047 - (int)(best & 0x7FFu)) - cta * 16;
  if (wid < 8 && row == brow) {
#pragma unroll
    for (int k = 0; k < 5; k++)
      st_pub4(&g_cand[cta][0][4 * (5 * gqi + k) + tq], enc4(make_uint4(hnreg[4 * k], hnreg[4 * k + 1], hnreg[4 * k + 2], hnreg[4 * k + 3])));
#pragma unroll
    for (int k = 0; k < 5; k++)
      st_pub4(&g_cand[cta][1][4 * (5 * gqi + k) + tq], enc4(make_uint4(hreg[4 * k], hreg[4 * k + 1], hreg[4 * k + 2], hreg[4 * k + 3])));
  }
#pragma unroll
  for (int i = 0; i < 20; i++) hreg[i] = b2u(__hadd2_rn(u2b(hreg[i]), u2b(hnreg[i])));
  if (wid == 11) {
    const uint4* kp = reinterpret_cast<const uint4*>(&g_keys[cta][0]) + lane;
    uint4 v = ld_poll4(kp);
    int it = 0;
    while (!ready4(v) && ++it < SPIN_LIMIT) v = ld_poll4(kp);
    const uint32_t m = max(max(v.x, v.y), max(v.z, v.w));
    const uint32_t wk = __reduce_max_sync(0xffffffffu, m);
    if (lane == 0) sm.win = wk;
  }
  __syncthreads();
  const uint32_t win = sm.win;
  const int wrow = 2047 - (int)(win & 0x7FFu);
  const int wcta = wrow >> 4;
  const bool st_out = wid < 8 && (cta * 16 + row) != wrow;
  uint4* outp = reinterpret_cast<uint4*>(gout + (size_t)(cta * 16 + row) * D_) + 20 * gqi + tq;
  if (cta >= N1) {
    if (st_out) {
#pragma unroll
      for (int k = 0; k < 5; k++) outp[4 * k] = make_uint4(hreg[4 * k], hreg[4 * k + 1], hreg[4 * k + 2], hreg[4 * k + 3]);
    }
  }
  if (cta >= N1) {
#pragma unroll
    for (int i = 0; i < 4; i++) if (i < 3 || tid < 128) g_y2[cta * 1280 + tid + NTHR * i] = make_uint4(0, 0, 0, 0);
  }
  if (cta < N1 + N2) mbar_wait(&sm.mbarw);
  float* xs = &sm.z[0][0][0];
  float* part = xs + 2048;
  if (cta < N1) {
    if (tid < 80) {
      const uint4 v = poll4(&g_cand[wcta][0][tid]);
      float4* xp = reinterpret_cast<float4*>(xs + tid * 8);
      xp[0] = make_float4(lo_f(v.x), hi_f(v.x), lo_f(v.y), hi_f(v.y));
      xp[1] = make_float4(lo_f(v.z), hi_f(v.z), lo_f(v.w), hi_f(v.w));
    }
    __syncthreads();
    const int m = wid / 6, hc = (wid % 6) >> 1, rs = (wid & 1) * 32 + lane;
    float a[8];
#pragma unroll
    for (int j = 0; j < 8; j++) a[j] = 0.f;
#pragma unroll
    for (int it = 0; it < 10; it++) {
      const int r = rs + 64 * it;
      const uint4 wv = sm.w[m * 1920 + r * 3 + hc];
      const float x = xs[r];
      a[0] = fmaf(x, lo_f(wv.x), a[0]); a[1] = fmaf(x, hi_f(wv.x), a[1]);
      a[2] = fmaf(x, lo_f(wv.y), a[2]); a[3] = fmaf(x, hi_f(wv.y), a[3]);
      a[4] = fmaf(x, lo_f(wv.z), a[4]); a[5] = fmaf(x, hi_f(wv.z), a[5]);
      a[6] = fmaf(x, lo_f(wv.w), a[6]); a[7] = fmaf(x, hi_f(wv.w), a[7]);
    }
    {
      const bool up = lane & 16;
#pragma unroll
      for (int j = 0; j < 4; j++) {
        const float send = up ? a[j] : a[j + 4], keep = up ? a[j + 4] : a[j];
        a[j] = keep + __shfl_xor_sync(0xffffffffu, send, 16);
      }
      const bool up2 = lane & 8;
#pragma unroll
      for (int j = 0; j < 2; j++) {
        const float send = up2 ? a[j] : a[j + 2], keep = up2 ? a[j + 2] : a[j];
        a[j] = keep + __shfl_xor_sync(0xffffffffu, send, 8);
      }
      const bool up3 = lane & 4;
      const float send = up3 ? a[0] : a[1], keep = up3 ? a[1] : a[0];
      a[0] = keep + __shfl_xor_sync(0xffffffffu, send, 4);
      a[0] += __shfl_xor_sync(0xffffffffu, a[0], 2);
      a[0] += __shfl_xor_sync(0xffffffffu, a[0], 1);
      if ((lane & 3) == 0) part[wid * 8 + (lane >> 2)] = a[0];
    }
    __syncthreads();
    if (wid == 0) {
      uint32_t bits = 0;
      if (lane < 24) {
        const int hc2 = lane >> 3, j = lane & 7;
        const float gt = rbf(part[(2 * hc2) * 8 + j] + part[(2 * hc2 + 1) * 8 + j]);
        const float up = rbf(part[(6 + 2 * hc2) * 8 + j] + part[(6 + 2 * hc2 + 1) * 8 + j]);
        const float sg = rbf(gt / (1.f + __expf(-gt)));
        bits = __bfloat16_as_ushort(__float2bfloat16_rn(sg * up));
      }
      const uint32_t nb = __shfl_down_sync(0xffffffffu, bits, 1);
      const uint32_t pw = bits | (nb << 16);
      const uint32_t w1 = __shfl_down_sync(0xffffffffu, pw, 2), w2 = __shfl_down_sync(0xffffffffu, pw, 4), w3 = __shfl_down_sync(0xffffffffu, pw, 6);
      const uint4 mine = enc4(make_uint4(pw, w1, w2, w3));
#pragma unroll
      for (int i = 0; i < 4; i++) {
        const int t = lane + 32 * i;
        const int cons = t / 3, ck = t - 3 * cons;
        uint4 v;
        v.x = __shfl_sync(0xffffffffu, mine.x, 8 * ck); v.y = __shfl_sync(0xffffffffu, mine.y, 8 * ck);
        v.z = __shfl_sync(0xffffffffu, mine.z, 8 * ck); v.w = __shfl_sync(0xffffffffu, mine.w, 8 * ck);
        if (t < 3 * N2) st_pub4(&g_act[cons][cta * 3 + ck], v);
      }
      __syncwarp();
      bar_arrive(7, 384);
    } else {
      bar_sync(7, 384);
    }
#pragma unroll
    for (int i = 0; i < 4; i++) if (i < 3 || tid < 128) g_y2[cta * 1280 + tid + NTHR * i] = make_uint4(0, 0, 0, 0);
    if (st_out) {
#pragma unroll
      for (int k = 0; k < 5; k++) outp[4 * k] = make_uint4(hreg[4 * k], hreg[4 * k + 1], hreg[4 * k + 2], hreg[4 * k + 3]);
    }
  } else if (cta < N1 + N2) {
    const int j2 = cta - N1;
    uint4 rowv = make_uint4(0, 0, 0, 0);
    if (tid < 192) {
      const uint4 v = poll4(&g_act[j2][tid]);
      float4* xp = reinterpret_cast<float4*>(xs + tid * 8);
      xp[0] = make_float4(lo_f(v.x), hi_f(v.x), lo_f(v.y), hi_f(v.y));
      xp[1] = make_float4(lo_f(v.z), hi_f(v.z), lo_f(v.w), hi_f(v.w));
    } else if (tid < 196) {
      const int t = tid - 192;
      rowv = poll4(&g_cand[wcta][t >> 1][j2 * 2 + (t & 1)]);
      reinterpret_cast<uint4*>(part + 256)[t] = rowv;
    }
    __syncthreads();
    const int hc = lane & 1, rs = wid * 16 + (lane >> 1);
    float a[8];
#pragma unroll
    for (int j = 0; j < 8; j++) a[j] = 0.f;
#pragma unroll
    for (int it = 0; it < 8; it++) {
      const int r = rs + 192 * it;
      const uint4 wv = sm.w[r * 2 + hc];
      const float x = xs[r];
      a[0] = fmaf(x, lo_f(wv.x), a[0]); a[1] = fmaf(x, hi_f(wv.x), a[1]);
      a[2] = fmaf(x, lo_f(wv.y), a[2]); a[3] = fmaf(x, hi_f(wv.y), a[3]);
      a[4] = fmaf(x, lo_f(wv.z), a[4]); a[5] = fmaf(x, hi_f(wv.z), a[5]);
      a[6] = fmaf(x, lo_f(wv.w), a[6]); a[7] = fmaf(x, hi_f(wv.w), a[7]);
    }
    {
      const bool up = lane & 16;
#pragma unroll
      for (int j = 0; j < 4; j++) {
        const float send = up ? a[j] : a[j + 4], keep = up ? a[j + 4] : a[j];
        a[j] = keep + __shfl_xor_sync(0xffffffffu, send, 16);
      }
      const bool up2 = lane & 8;
#pragma unroll
      for (int j = 0; j < 2; j++) {
        const float send = up2 ? a[j] : a[j + 2], keep = up2 ? a[j + 2] : a[j];
        a[j] = keep + __shfl_xor_sync(0xffffffffu, send, 8);
      }
      const bool up3 = lane & 4;
      const float send = up3 ? a[0] : a[1], keep = up3 ? a[1] : a[0];
      a[0] = keep + __shfl_xor_sync(0xffffffffu, send, 4);
      a[0] += __shfl_xor_sync(0xffffffffu, a[0], 2);
      if ((lane & 2) == 0) part[wid * 16 + hc * 8 + (lane >> 2)] = a[0];
    }
    __syncthreads();
    if (tid < 16) {
      float y = 0.f;
#pragma unroll
      for (int i = 0; i < 12; i++) y += part[i * 16 + tid];
      const uint32_t ord = win >> 16;
      const uint32_t rb = (ord & 0x8000u) ? (ord ^ 0x8000u) : (ord ^ 0xFFFFu);
      const float r = __uint_as_float(rb << 16);
      const float sg = rbf(1.f / (1.f + __expf(-r)));
      const float yy = rbf(rbf(y) * sg);
      const unsigned short* rv = reinterpret_cast<const unsigned short*>(part + 256);
      const float hn = __uint_as_float((uint32_t)rv[tid] << 16), h = __uint_as_float((uint32_t)rv[16 + tid] << 16);
      gout[(size_t)wrow * D_ + j2 * 16 + tid] = __float2bfloat16_rn(h + rbf(hn + yy));
    }
  }
}

}

typedef CUresult (*EncodeFn)(CUtensorMap*, CUtensorMapDataType, cuuint32_t, void*, const cuuint64_t*, const cuuint64_t*,
                             const cuuint32_t*, const cuuint32_t*, CUtensorMapInterleave, CUtensorMapSwizzle,
                             CUtensorMapL2promotion, CUtensorMapFloatOOBfill);

extern "C" void kernel_launch(void* const* d_in, const int* in_sizes, int n_in, void* d_out, int out_size) {
  (void)in_sizes; (void)n_in; (void)out_size;
  static EncodeFn encode = nullptr;
  static CUtensorMap tmg, tmu, tmd;
  static void* cached[3] = {nullptr, nullptr, nullptr};
  if (!encode) {
    cudaFuncSetAttribute(fused_kernel, cudaFuncAttributeMaxDynamicSharedMemorySize, (int)sizeof(Smem));
    void* fn = nullptr;
    cudaDriverEntryPointQueryResult qr;
    cudaGetDriverEntryPoint("cuTensorMapEncodeTiled", &fn, cudaEnableDefault, &qr);
    encode = (EncodeFn)fn;
  }
  if (cached[0] != d_in[8] || cached[1] != d_in[9] || cached[2] != d_in[10]) {
    const cuuint32_t es[2] = {1, 1};
    {
      const cuuint64_t dims[2] = {F_, D_}, strides[1] = {F_ * 2};
      const cuuint32_t box[2] = {24, 160};
      encode(&tmg, CU_TENSOR_MAP_DATA_TYPE_BFLOAT16, 2, d_in[8], dims, strides, box, es, CU_TENSOR_MAP_INTERLEAVE_NONE,
             CU_TENSOR_MAP_SWIZZLE_NONE, CU_TENSOR_MAP_L2_PROMOTION_NONE, CU_TENSOR_MAP_FLOAT_OOB_FILL_NONE);
      encode(&tmu, CU_TENSOR_MAP_DATA_TYPE_BFLOAT16, 2, d_in[9], dims, strides, box, es, CU_TENSOR_MAP_INTERLEAVE_NONE,
             CU_TENSOR_MAP_SWIZZLE_NONE, CU_TENSOR_MAP_L2_PROMOTION_NONE, CU_TENSOR_MAP_FLOAT_OOB_FILL_NONE);
    }
    {
      const cuuint64_t dims[2] = {D_, F_}, strides[1] = {D_ * 2};
      const cuuint32_t box[2] = {16, 256};
      encode(&tmd, CU_TENSOR_MAP_DATA_TYPE_BFLOAT16, 2, d_in[10], dims, strides, box, es, CU_TENSOR_MAP_INTERLEAVE_NONE,
             CU_TENSOR_MAP_SWIZZLE_NONE, CU_TENSOR_MAP_L2_PROMOTION_NONE, CU_TENSOR_MAP_FLOAT_OOB_FILL_NONE);
    }
    cached[0] = d_in[8]; cached[1] = d_in[9]; cached[2] = d_in[10];
  }
  fused_kernel<<<NCTA, NTHR, sizeof(Smem), cudaStreamPerThread>>>(
      tmg, tmu, tmd, (const bf16*)d_in[0], (const bf16*)d_in[1], (const bf16*)d_in[2], (const bf16*)d_in[3],
      (const bf16*)d_in[4], (const bf16*)d_in[5], (const bf16*)d_in[7], (bf16*)d_out);
}
```

```cpp
#include <cuda_runtime.h>
#include <cuda_bf16.h>
#include <cuda.h>
#include <stdint.h>

namespace {

typedef __nv_bfloat16 bf16;
typedef __nv_bfloat162 bf162;

constexpr int S_ = 2048, D_ = 640, F_ = 1536;
constexpr int NCTA = 128, CPC = 5, NTHR = 384;
constexpr int UPAD = 136, USTR = 2192;
constexpr int TABW = 1040;
constexpr int ZPB = 132;
constexpr int QSTR = 648;
constexpr int N1 = 64;
constexpr int N2 = 40;
constexpr int SPIN_LIMIT = 1 << 19;
constexpr int POLL_NS = 100;

struct __align__(128) Smem {
  uint32_t tabA[3][2][TABW];
  uint32_t extra[1024];
  uint32_t tabB[2][2][TABW];
  bf16 u[CPC][USTR];
  float z[2][4][ZPB * 16];
  bf16 q[16][QSTR];
  alignas(128) uint4 w[3840];
  uint4 wr[80];
  alignas(16) float2 st[16][4];
  alignas(16) float2 stq[16][4];
  alignas(16) float rp[16][4];
  unsigned long long mbar;
  unsigned long long mbarw;
  unsigned long long mbarc;
  unsigned long long mbary;
  unsigned long long mbarh;
  uint32_t target;
  uint32_t target2;
  uint32_t target3;
  uint32_t best;
  uint32_t win;
};

__device__ uint4 g_kv[D_ * S_ / 8];
__device__ uint4 g_y2[D_ * S_ / 8];
__device__ uint32_t g_keys[NCTA][NCTA];
__device__ uint4 g_cand[NCTA][2][80];
__device__ uint4 g_act[N2][F_ / 8];
__device__ __align__(256) unsigned int g_ctrs[3][64];
#define g_ctr g_ctrs[0][0]
#define g_ctr2 g_ctrs[1][0]
#define g_ctr3 g_ctrs[2][0]

__device__ __forceinline__ uint32_t smem_u32(const void* p) { return (uint32_t)__cvta_generic_to_shared(p); }
__device__ __forceinline__ void wg_fence() { asm volatile("wgmma.fence.sync.aligned;" ::: "memory"); }
__device__ __forceinline__ void wg_commit() { asm volatile("wgmma.commit_group.sync.aligned;" ::: "memory"); }
template <int N> __device__ __forceinline__ void wg_wait() { asm volatile("wgmma.wait_group.sync.aligned %0;" ::"n"(N) : "memory"); }
__device__ __forceinline__ void bar_sync(int id, int n) { asm volatile("bar.sync %0, %1;" ::"r"(id), "r"(n) : "memory"); }
__device__ __forceinline__ void bar_arrive(int id, int n) { asm volatile("bar.arrive %0, %1;" ::"r"(id), "r"(n) : "memory"); }
__device__ __forceinline__ bf162 u2b(uint32_t u) { return *reinterpret_cast<bf162*>(&u); }
__device__ __forceinline__ uint32_t b2u(bf162 b) { return *reinterpret_cast<uint32_t*>(&b); }
__device__ __forceinline__ float lo_f(uint32_t u) { return __uint_as_float(u << 16); }
__device__ __forceinline__ float hi_f(uint32_t u) { return __uint_as_float(u & 0xFFFF0000u); }
__device__ __forceinline__ float rbf(float x) { return __bfloat162float(__float2bfloat16_rn(x)); }
__device__ __forceinline__ uint32_t pack2(float a, float b) { return b2u(__floats2bfloat162_rn(a, b)); }
__device__ __forceinline__ uint32_t enc(uint32_t w) { return max(~w, 1u); }
__device__ __forceinline__ uint4 enc4(uint4 v) { return make_uint4(enc(v.x), enc(v.y), enc(v.z), enc(v.w)); }
__device__ __forceinline__ uint4 ld_poll4(const uint4* p) {
  uint4 v;
  asm volatile("ld.relaxed.gpu.global.v4.u32 {%0,%1,%2,%3}, [%4];" : "=r"(v.x), "=r"(v.y), "=r"(v.z), "=r"(v.w) : "l"(p) : "memory");
  return v;
}
__device__ __forceinline__ bool ready4(uint4 v) { return v.x != 0u && v.y != 0u && v.z != 0u && v.w != 0u; }
__device__ __forceinline__ uint4 poll4(const uint4* p) {
  uint4 v = ld_poll4(p);
  int it = 0;
  while (!ready4(v) && ++it < SPIN_LIMIT) v = ld_poll4(p);
  return make_uint4(~v.x, ~v.y, ~v.z, ~v.w);
}
__device__ __forceinline__ void st_pub4(uint4* p, uint4 v) {
  asm volatile("st.relaxed.gpu.global.v4.u32 [%0], {%1,%2,%3,%4};" ::"l"(p), "r"(v.x), "r"(v.y), "r"(v.z), "r"(v.w) : "memory");
}
__device__ __forceinline__ void st_pub2(uint2* p, uint32_t a, uint32_t b) {
  asm volatile("st.relaxed.gpu.global.v2.u32 [%0], {%1,%2};" ::"l"(p), "r"(a), "r"(b) : "memory");
}
__device__ __forceinline__ void mma_bf16(float (&c)[4], uint32_t a0, uint32_t a2, uint32_t b0, uint32_t b1) {
  asm volatile("mma.sync.aligned.m16n8k16.row.col.f32.bf16.bf16.f32 {%0,%1,%2,%3}, {%4,%5,%6,%5}, {%7,%8}, {%0,%1,%2,%3};"
               : "+f"(c[0]), "+f"(c[1]), "+f"(c[2]), "+f"(c[3]) : "r"(a0), "r"(0u), "r"(a2), "r"(b0), "r"(b1));
}
__device__ __forceinline__ void mbar_wait(const unsigned long long* bar) {
  const uint32_t mb = smem_u32(bar);
  uint32_t ok = 0;
  int it = 0;
  while (!ok && ++it < SPIN_LIMIT)
    asm volatile("{ .reg .pred p; mbarrier.try_wait.parity.shared.b64 p, [%1], 0; selp.u32 %0, 1, 0, p; }" : "=r"(ok) : "r"(mb) : "memory");
}
__device__ __forceinline__ void bulk_g2s(void* dst, const void* src, uint32_t bytes, const unsigned long long* bar) {
  asm volatile("cp.async.bulk.shared::cluster.global.mbarrier::complete_tx::bytes [%0], [%1], %2, [%3];" ::"r"(smem_u32(dst)),
               "l"(src), "r"(bytes), "r"(smem_u32(bar)) : "memory");
}
__device__ __forceinline__ void mbar_expect(const unsigned long long* bar, uint32_t bytes) {
  asm volatile("mbarrier.arrive.expect_tx.shared.b64 _, [%0], %1;" ::"r"(smem_u32(bar)), "r"(bytes) : "memory");
}
__device__ __forceinline__ void mma_bf16x(float (&c)[4], uint32_t a0, uint32_t a1, uint32_t a2, uint32_t a3, uint32_t b0, uint32_t b1) {
  asm volatile("mma.sync.aligned.m16n8k16.row.col.f32.bf16.bf16.f32 {%0,%1,%2,%3}, {%4,%5,%6,%7}, {%8,%9}, {%0,%1,%2,%3};"
               : "+f"(c[0]), "+f"(c[1]), "+f"(c[2]), "+f"(c[3]) : "r"(a0), "r"(a1), "r"(a2), "r"(a3), "r"(b0), "r"(b1));
}
__device__ __forceinline__ float fdivr(float a, float d, float r) {
  float q = a * r;
  float e = fmaf(-q, d, a);
  return fmaf(e, r, q);
}

template <bool FIRST> __device__ __forceinline__ void wgmma32(float (&d)[16], const uint32_t* a, uint64_t desc) {
  if (FIRST) {
    asm volatile("wgmma.mma_async.sync.aligned.m64n32k16.f32.bf16.bf16 {%0,%1,%2,%3,%4,%5,%6,%7,%8,%9,%10,%11,%12,%13,%14,%15}, {%16,%17,%18,%19}, %20, 0, 1, 1, 0;"
                 : "+f"(d[0]), "+f"(d[1]), "+f"(d[2]), "+f"(d[3]), "+f"(d[4]), "+f"(d[5]), "+f"(d[6]), "+f"(d[7]),
                   "+f"(d[8]), "+f"(d[9]), "+f"(d[10]), "+f"(d[11]), "+f"(d[12]), "+f"(d[13]), "+f"(d[14]), "+f"(d[15])
                 : "r"(a[0]), "r"(a[1]), "r"(a[2]), "r"(a[3]), "l"(desc));
  } else {
    asm volatile("wgmma.mma_async.sync.aligned.m64n32k16.f32.bf16.bf16 {%0,%1,%2,%3,%4,%5,%6,%7,%8,%9,%10,%11,%12,%13,%14,%15}, {%16,%17,%18,%19}, %20, 1, 1, 1, 0;"
                 : "+f"(d[0]), "+f"(d[1]), "+f"(d[2]), "+f"(d[3]), "+f"(d[4]), "+f"(d[5]), "+f"(d[6]), "+f"(d[7]),
                   "+f"(d[8]), "+f"(d[9]), "+f"(d[10]), "+f"(d[11]), "+f"(d[12]), "+f"(d[13]), "+f"(d[14]), "+f"(d[15])
                 : "r"(a[0]), "r"(a[1]), "r"(a[2]), "r"(a[3]), "l"(desc));
  }
}

template <int G> __device__ __forceinline__ void load_a(uint32_t (&a)[8], const uint32_t* tp) {
#pragma unroll
  for (int q = 0; q < 2; q++) {
    const int e = 2 * G + q;
    a[4 * q + 0] = tp[-64 * e];
    a[4 * q + 1] = tp[-64 * e - 32];
    a[4 * q + 2] = tp[-64 * e + 4];
    a[4 * q + 3] = tp[-64 * e - 28];
  }
}
__device__ __forceinline__ void load_a_all(uint32_t (&a)[8][8], const uint32_t* tp) {
  load_a<0>(a[0], tp); load_a<1>(a[1], tp); load_a<2>(a[2], tp); load_a<3>(a[3], tp);
  load_a<4>(a[4], tp); load_a<5>(a[5], tp); load_a<6>(a[6], tp); load_a<7>(a[7], tp);
}
template <int G> __device__ __forceinline__ void issue_g(float (&acc)[8][16], uint32_t (&a)[8], uint64_t desc0) {
  wg_fence();
#pragma unroll
  for (int q = 0; q < 2; q++) {
#pragma unroll
    for (int b = G; b < 8; b++) {
      const int delta = 2 * b - (2 * G + q);
      if (G == 0 && q == 0) wgmma32<true>(acc[b], &a[4 * q], desc0 + (uint64_t)(int64_t)(16 * delta));
      else wgmma32<false>(acc[b], &a[4 * q], desc0 + (uint64_t)(int64_t)(16 * delta));
    }
  }
  wg_commit();
}
template <int B> __device__ __forceinline__ void fence_blk(float (&acc)[8][16]) {
#pragma unroll
  for (int i = 0; i < 16; i++) asm volatile("" : "+f"(acc[B][i])::"memory");
}
__device__ __forceinline__ void fence_a(uint32_t (&a)[8]) {
#pragma unroll
  for (int i = 0; i < 8; i++) asm volatile("" : "+r"(a[i])::"memory");
}
template <int B> __device__ __forceinline__ void sts_blk(float (&acc)[8][16], float* zw, int off_even, int off_odd) {
#pragma unroll
  for (int jj = 0; jj < 4; jj++) {
    const int j = 4 * B + jj;
    float p0 = acc[B][4 * jj + 0], p1 = acc[B][4 * jj + 1];
    if (jj > 0) { p0 += acc[B][4 * (jj - 1) + 2]; p1 += acc[B][4 * (jj - 1) + 3]; }
    else if (B > 0) { p0 += acc[B > 0 ? B - 1 : 0][14]; p1 += acc[B > 0 ? B - 1 : 0][15]; }
    zw[64 * j + off_even] = p0;
    zw[64 * j + off_odd] = p1;
  }
}
__device__ __forceinline__ int tab_off(int c) { return c == 4 ? 0 : (c + 1) * 2 * TABW + (c >= 2 ? 1024 : 0); }
__device__ __forceinline__ int tile_perm(int ch) { return ch ^ (((ch >> 3) & 3) << 1); }

__device__ __forceinline__ void wait_ctr(const unsigned int* ctr, uint32_t target) {
  uint32_t v;
  int it = 0;
  do {
    asm volatile("ld.acquire.gpu.global.u32 %0, [%1];" : "=r"(v) : "l"(ctr) : "memory");
  } while ((int)(v - target) < 0 && ++it < SPIN_LIMIT);
}

__device__ __forceinline__ float2 row_part_stats(const uint32_t (&x)[20]) {
  float cs[5][4];
#pragma unroll
  for (int k = 0; k < 5; k++) {
    cs[k][0] = cs[k][1] = cs[k][2] = cs[k][3] = 0.f;
    mma_bf16x(cs[k], x[4 * k + 0], x[4 * k + 2], x[4 * k + 1], x[4 * k + 3], 0x3F803F80u, 0x3F803F80u);
  }
  const float mean = ((((cs[0][0] + cs[0][2]) + (cs[1][0] + cs[1][2])) + ((cs[2][0] + cs[2][2]) + (cs[3][0] + cs[3][2]))) + (cs[4][0] + cs[4][2])) * (1.f / 160.f);
  float m2a = 0.f, m2b = 0.f, m2c = 0.f, m2d = 0.f;
#pragma unroll
  for (int i = 0; i < 20; i += 2) {
    const float a = lo_f(x[i]) - mean, b = hi_f(x[i]) - mean, c = lo_f(x[i + 1]) - mean, d = hi_f(x[i + 1]) - mean;
    m2a = fmaf(a, a, m2a); m2b = fmaf(b, b, m2b); m2c = fmaf(c, c, m2c); m2d = fmaf(d, d, m2d);
  }
  float m2 = (m2a + m2b) + (m2c + m2d);
  m2 += __shfl_xor_sync(0xffffffffu, m2, 1);
  m2 += __shfl_xor_sync(0xffffffffu, m2, 2);
  return make_float2(mean, m2);
}
template <bool EXACT> __device__ __forceinline__ void row_normalize(const float4* st, const uint32_t (&x)[20], uint32_t (&y)[20]) {
  const float4 p = st[0], q = st[1];
  const float mean = ((p.x + p.z) + (q.x + q.z)) * 0.25f;
  const float d0 = p.x - mean, d1 = p.z - mean, d2 = q.x - mean, d3 = q.z - mean;
  const float m2 = ((p.y + p.w) + (q.y + q.w)) + 160.f * ((d0 * d0 + d1 * d1) + (d2 * d2 + d3 * d3));
  const float hd = rbf(sqrtf(rbf(rbf(m2 * (1.f / D_)) + 1e-5f)));
  const float hr = __frcp_rn(hd);
  const bf162 hm2 = __float2bfloat162_rn(mean);
#pragma unroll
  for (int i = 0; i < 20; i++) {
    const uint32_t d = b2u(__hsub2_rn(u2b(x[i]), hm2));
    y[i] = EXACT ? pack2(fdivr(lo_f(d), hd, hr), fdivr(hi_f(d), hd, hr)) : pack2(lo_f(d) * hr, hi_f(d) * hr);
  }
}

__device__ __forceinline__ void gather_kv(Smem& sm, int c0, int tid) {
  mbar_wait(&sm.mbarc);
  uint4 v[4];
  uint4* src = g_kv + c0 * 256 + tid;
#pragma unroll
  for (int i = 0; i < 4; i++) if (i < 3 || tid >= 256) v[i] = ld_poll4(src + NTHR * i - (i == 3 ? 256 : 0));
#pragma unroll
  for (int i = 0; i < 4; i++) {
    if (i < 3 || tid >= 256) {
      const int t = tid + NTHR * i - (i == 3 ? 256 : 0);
      int it = 0;
      while (!ready4(v[i]) && ++it < SPIN_LIMIT) { __nanosleep(POLL_NS); v[i] = ld_poll4(g_kv + c0 * 256 + t); }
      *reinterpret_cast<uint4*>(&sm.u[t >> 8][UPAD + (t & 255) * 8]) = make_uint4(~v[i].x, ~v[i].y, ~v[i].z, ~v[i].w);
    }
  }
  asm volatile("fence.proxy.async.shared::cta;" ::: "memory");
  __syncthreads();
}

__global__ void __launch_bounds__(NTHR, 1)
fused_kernel(const __grid_constant__ CUtensorMap tmg, const __grid_constant__ CUtensorMap tmu,
             const __grid_constant__ CUtensorMap tmd, const bf16* __restrict__ gq, const bf16* __restrict__ gk, const bf16* __restrict__ gv,
             const bf16* __restrict__ gsk, const bf16* __restrict__ gh, const bf16* __restrict__ gD,
             const bf16* __restrict__ gwr, bf16* __restrict__ gout) {
  extern __shared__ __align__(128) unsigned char smraw[];
  Smem& sm = *reinterpret_cast<Smem*>(smraw);
  const int tid = threadIdx.x;
  const int cta = blockIdx.x;
  const int c0 = cta * CPC;
  const int lane = tid & 31;
  const int wid = tid >> 5;

  {
    uint4* hs = reinterpret_cast<uint4*>(&sm.z[0][0][0]);
    const int oc = tid >> 2;
    const int r0 = cta * 16 + (tid & 3) * 4;
    uint4 kk[7], vv[4], sk[4];
    if (tid < 320) {
      const uint4* kp = reinterpret_cast<const uint4*>(gk) + (size_t)r0 * 80 + oc;
      const uint4* vp = reinterpret_cast<const uint4*>(gv) + (size_t)r0 * 80 + oc;
#pragma unroll
      for (int i = 0; i < 7; i++) kk[i] = (i >= 3 || r0 > 0) ? __ldg(kp + (i - 3) * 80) : make_uint4(0, 0, 0, 0);
#pragma unroll
      for (int i = 0; i < 4; i++) vv[i] = __ldg(vp + i * 80);
#pragma unroll
      for (int i = 0; i < 4; i++) sk[i] = __ldg(reinterpret_cast<const uint4*>(gsk) + oc * 4 + i);
    } else if (tid == 320) {
      asm volatile("mbarrier.init.shared.b64 [%0], 1;" ::"r"(smem_u32(&sm.mbarh)) : "memory");
      asm volatile("mbarrier.init.shared.b64 [%0], 1;" ::"r"(smem_u32(&sm.mbar)) : "memory");
      asm volatile("mbarrier.init.shared.b64 [%0], 1;" ::"r"(smem_u32(&sm.mbarw)) : "memory");
      asm volatile("mbarrier.init.shared.b64 [%0], 1;" ::"r"(smem_u32(&sm.mbarc)) : "memory");
      asm volatile("mbarrier.init.shared.b64 [%0], 1;" ::"r"(smem_u32(&sm.mbary)) : "memory");
      asm volatile("fence.proxy.async.shared::cta;" ::: "memory");
    } else if (tid == 352) {
      uint32_t v1, v2, v3;
      asm volatile("ld.relaxed.gpu.global.u32 %0, [%1];" : "=r"(v1) : "l"(&g_ctr) : "memory");
      asm volatile("ld.relaxed.gpu.global.u32 %0, [%1];" : "=r"(v2) : "l"(&g_ctr2) : "memory");
      asm volatile("ld.relaxed.gpu.global.u32 %0, [%1];" : "=r"(v3) : "l"(&g_ctr3) : "memory");
      sm.target = (v1 / NCTA + 1u) * NCTA;
      sm.target2 = (v2 / NCTA + 1u) * NCTA;
      sm.target3 = (v3 / NCTA + 1u) * NCTA;
    }
    if (tid < 320) bar_sync(6, 384); else { bar_arrive(6, 384); bar_sync(5, 64); }
    if (tid < 320) {
      uint32_t o[4][4];
#pragma unroll
      for (int p = 0; p < 4; p++) {
        const bf162 w0 = u2b(__byte_perm(sk[p].x, sk[p].z, 0x5410)), w1 = u2b(__byte_perm(sk[p].x, sk[p].z, 0x7632));
        const bf162 w2 = u2b(__byte_perm(sk[p].y, sk[p].w, 0x5410)), w3 = u2b(__byte_perm(sk[p].y, sk[p].w, 0x7632));
        uint32_t kv[4];
#pragma unroll
        for (int i = 0; i < 4; i++) {
          const uint32_t k0 = p == 0 ? kk[i].x : p == 1 ? kk[i].y : p == 2 ? kk[i].z : kk[i].w;
          const uint32_t k1 = p == 0 ? kk[i + 1].x : p == 1 ? kk[i + 1].y : p == 2 ? kk[i + 1].z : kk[i + 1].w;
          const uint32_t k2 = p == 0 ? kk[i + 2].x : p == 1 ? kk[i + 2].y : p == 2 ? kk[i + 2].z : kk[i + 2].w;
          const uint32_t k3 = p == 0 ? kk[i + 3].x : p == 1 ? kk[i + 3].y : p == 2 ? kk[i + 3].z : kk[i + 3].w;
          const uint32_t vx = p == 0 ? vv[i].x : p == 1 ? vv[i].y : p == 2 ? vv[i].z : vv[i].w;
          bf162 a = __hmul2_rn(u2b(k0), w3);
          a = __hadd2_rn(a, __hmul2_rn(u2b(k1), w2));
          a = __hadd2_rn(a, __hmul2_rn(u2b(k2), w1));
          a = __hadd2_rn(a, __hmul2_rn(u2b(k3), w0));
          kv[i] = b2u(__hmul2_rn(a, u2b(vx)));
        }
        o[p][0] = enc(__byte_perm(kv[0], kv[1], 0x5410)); o[p][1] = enc(__byte_perm(kv[2], kv[3], 0x5410));
        o[p][2] = enc(__byte_perm(kv[0], kv[1], 0x7632)); o[p][3] = enc(__byte_perm(kv[2], kv[3], 0x7632));
      }
      uint2* dst = reinterpret_cast<uint2*>(g_kv) + (size_t)(oc * 8) * 512 + (r0 >> 2);
#pragma unroll
      for (int p = 0; p < 4; p++) {
        st_pub2(dst + (2 * p) * 512, o[p][0], o[p][1]);
        st_pub2(dst + (2 * p + 1) * 512, o[p][2], o[p][3]);
      }
      if (wid == 0) bar_sync(4, 320); else bar_arrive(4, 320);
      if (tid == 0) {
        asm volatile("red.relaxed.gpu.global.add.u32 [%0], 1;" ::"l"(&g_ctr2) : "memory");
      }
      __syncwarp();
    } else {
      const int t0 = tid - 320;
      const uint4 zz = make_uint4(0, 0, 0, 0);
      if (tid == 320) {
        mbar_expect(&sm.mbarh, CPC * S_ * 2);
        bulk_g2s(hs, gh + (size_t)c0 * S_, CPC * S_ * 2, &sm.mbarh);
      }
      __syncwarp();
      for (int t = t0; t < CPC * 17; t += 64) *reinterpret_cast<uint4*>(&sm.u[t / 17][(t % 17) * 8]) = zz;
      if (t0 < 40) *reinterpret_cast<uint4*>(&sm.tabA[0][0][0] + tab_off(t0 >> 3) + ((t0 >> 2) & 1) * TABW + 1024 + 4 * (t0 & 3)) = zz;
      (&g_cand[cta][0][0])[t0] = zz;
      (&g_cand[cta][0][0])[64 + t0] = zz;
      if (t0 < 32) (&g_cand[cta][0][0])[128 + t0] = zz;
      else reinterpret_cast<uint4*>(&g_keys[cta][0])[t0 - 32] = zz;
      if (cta >= N1 && cta < N1 + N2) {
#pragma unroll
        for (int i = 0; i < 3; i++) g_act[cta - N1][t0 + 64 * i] = zz;
      }
    }
    mbar_wait(&sm.mbarh);
#pragma unroll
    for (int i = 0; i < 4; i++) {
      const int t = (NTHR - 1 - tid) + NTHR * i;
      if (t < CPC * 256) {
        uint32_t* tb = &sm.tabA[0][0][0] + tab_off(t >> 8) + (255 - (t & 255)) * 4;
        const uint4 h = hs[t];
        const uint32_t hp = (t & 255) ? reinterpret_cast<const uint32_t*>(hs)[4 * t - 1] : 0u;
        uint4 r1, rr;
        r1.x = __byte_perm(h.w, 0, 0x1032); r1.y = __byte_perm(h.z, 0, 0x1032);
        r1.z = __byte_perm(h.y, 0, 0x1032); r1.w = __byte_perm(h.x, 0, 0x1032);
        rr.x = __byte_perm(h.w, h.z, 0x7610); rr.y = __byte_perm(h.z, h.y, 0x7610);
        rr.z = __byte_perm(h.y, h.x, 0x7610); rr.w = __byte_perm(h.x, hp, 0x7610);
        *reinterpret_cast<uint4*>(tb) = rr;
        *reinterpret_cast<uint4*>(tb + TABW) = r1;
      }
    }
  }
  __syncthreads();

  const int wg = __shfl_sync(0xffffffffu, tid >> 7, 0);
  const int wtid = tid & 127;
  uint4* tile = reinterpret_cast<uint4*>(&sm.tabB[0][0][0]);
  if (wg < 2) {
    asm volatile("setmaxnreg.inc.sync.aligned.u32 224;");
    const int w = (tid >> 5) & 3, g = lane >> 2, tq = lane & 3;
    float* zw = sm.z[wg][w];
    const int sw = 3 * (((tq + w) >> 1) & 1);
    const int off_even = 16 * (tq + w) + 4 * ((0 + (g >> 2)) ^ sw) + (g & 3);
    const int off_odd = 16 * (tq + w) + 4 * ((2 + (g >> 2)) ^ sw) + (g & 3);
    uint32_t a[8][8];
    const uint32_t* tp0 = &sm.tabA[0][g & 1][1019 - 8 * w - (g >> 1) + tq];
    load_a_all(a, tp0 + tab_off(wg));
    float acc[8][16];
#pragma unroll
    for (int b = 0; b < 8; b++)
#pragma unroll
      for (int i = 0; i < 16; i++) acc[b][i] = 0.f;
    gather_kv(sm, c0, tid);
#pragma unroll 1
    for (int c = wg; c < CPC; c += 2) {
      const uint64_t desc = (uint64_t)((smem_u32(&sm.u[c][UPAD - 8]) & 0x3FFFF) >> 4) | ((uint64_t)1 << 16) | ((uint64_t)8 << 32);
      if (c > 0) bar_sync(1 + wg, 256);
      issue_g<0>(acc, a[0], desc);
      issue_g<1>(acc, a[1], desc);
      issue_g<2>(acc, a[2], desc);
      issue_g<3>(acc, a[3], desc);
      issue_g<4>(acc, a[4], desc);
      issue_g<5>(acc, a[5], desc);
      if (c + 1 < CPC) bar_arrive(1 + (wg ^ 1), 256);
      issue_g<6>(acc, a[6], desc);
      issue_g<7>(acc, a[7], desc);
      if (c >= 2) bar_sync(5 + wg, 256);
      wg_wait<4>();
      fence_blk<0>(acc); fence_blk<1>(acc); fence_blk<2>(acc); fence_blk<3>(acc);
      sts_blk<0>(acc, zw, off_even, off_odd);
      sts_blk<1>(acc, zw, off_even, off_odd);
      sts_blk<2>(acc, zw, off_even, off_odd);
      sts_blk<3>(acc, zw, off_even, off_odd);
      bar_arrive(9 + wg, 256);
      wg_wait<0>();
      fence_blk<4>(acc); fence_blk<5>(acc); fence_blk<6>(acc); fence_blk<7>(acc);
#pragma unroll
      for (int i = 0; i < 8; i++) fence_a(a[i]);
      sts_blk<4>(acc, zw, off_even, off_odd);
      sts_blk<5>(acc, zw, off_even, off_odd);
      sts_blk<6>(acc, zw, off_even, off_odd);
      sts_blk<7>(acc, zw, off_even, off_odd);
      bar_arrive(3 + wg, 256);
      if (c + 2 < CPC) load_a_all(a, tp0 + tab_off(c + 2));
    }
    asm volatile("setmaxnreg.dec.sync.aligned.u32 168;");
  } else {
    asm volatile("setmaxnreg.dec.sync.aligned.u32 56;");
    if (((wtid & 15) >> 2) < ((wtid >> 4) & 3))
      *reinterpret_cast<uint4*>(&sm.z[wtid >> 6][(wtid >> 4) & 3][(wtid & 15) * 4]) = make_uint4(0, 0, 0, 0);
    if (wtid == 96) {
      __threadfence();
      asm volatile("red.relaxed.gpu.global.add.u32 [%0], 1;" ::"l"(&g_ctr) : "memory");
    }
    if (wtid == 64) {
      const unsigned target = sm.target2;
      uint32_t v;
      int it = 0;
      do {
        asm volatile("ld.relaxed.gpu.global.u32 %0, [%1];" : "=r"(v) : "l"(&g_ctr2) : "memory");
      } while ((int)(v - target) < 0 && ++it < SPIN_LIMIT);
      asm volatile("mbarrier.arrive.shared.b64 _, [%0];" ::"r"(smem_u32(&sm.mbarc)) : "memory");
    }
    __syncwarp();
    gather_kv(sm, c0, tid);
#pragma unroll
    for (int i = 0; i < 10; i++) g_kv[c0 * 256 + wtid + 128 * i] = make_uint4(0, 0, 0, 0);
    if (wtid == 96) wait_ctr(&g_ctr, sm.target);
    __syncwarp();
    if (wtid == 32) {
      const uint32_t mw = smem_u32(&sm.mbarw);
      mbar_expect(&sm.mbar, 17 * D_ * 2);
#pragma unroll 1
      for (int r = 0; r < 16; r++) bulk_g2s(&sm.q[r][0], gq + (size_t)(cta * 16 + r) * D_, D_ * 2, &sm.mbar);
      bulk_g2s(&sm.wr[0], gwr, D_ * 2, &sm.mbar);
      if (cta < N1) {
        asm volatile("mbarrier.arrive.expect_tx.shared.b64 _, [%0], %1;" ::"r"(mw), "r"(3840 * 16) : "memory");
#pragma unroll 1
        for (int i = 0; i < 4; i++) {
          asm volatile("cp.async.bulk.tensor.2d.shared::cluster.global.mbarrier::complete_tx::bytes [%0], [%1, {%3, %4}], [%2];" ::"r"(smem_u32(&sm.w[i * 480])),
                       "l"(&tmg), "r"(mw), "r"(cta * 24), "r"(i * 160) : "memory");
          asm volatile("cp.async.bulk.tensor.2d.shared::cluster.global.mbarrier::complete_tx::bytes [%0], [%1, {%3, %4}], [%2];" ::"r"(smem_u32(&sm.w[1920 + i * 480])),
                       "l"(&tmu), "r"(mw), "r"(cta * 24), "r"(i * 160) : "memory");
        }
      } else if (cta < N1 + N2) {
        asm volatile("mbarrier.arrive.expect_tx.shared.b64 _, [%0], %1;" ::"r"(mw), "r"(3072 * 16) : "memory");
#pragma unroll 1
        for (int i = 0; i < 6; i++)
          asm volatile("cp.async.bulk.tensor.2d.shared::cluster.global.mbarrier::complete_tx::bytes [%0], [%1, {%3, %4}], [%2];" ::"r"(smem_u32(&sm.w[i * 512])),
                       "l"(&tmd), "r"(mw), "r"((cta - N1) * 16), "r"(i * 256) : "memory");
      }
    }
    const int rpb = wtid >> 1, re2 = wtid & 1;
    const int rsw = 3 * ((rpb >> 1) & 1);
    const int roff0 = 16 * rpb + 4 * ((2 * re2 + 0) ^ rsw);
    const int roff1 = 16 * rpb + 4 * ((2 * re2 + 1) ^ rsw);
    const uint32_t dvl = reinterpret_cast<const unsigned short*>(gD)[c0 + (lane < CPC ? lane : 0)];
#pragma unroll 1
    for (int c = 0; c < CPC; c++) {
      const int zg = c & 1;
      const uint32_t dvc = __shfl_sync(0xffffffffu, dvl, c);
      const bf162 d2 = u2b(dvc | (dvc << 16));
#pragma unroll
      for (int half = 0; half < 2; half++) {
        bar_sync((half ? 3 : 9) + zg, 256);
        const float* zb = sm.z[zg][0] + half * 1024;
        float4 x[4][2];
#pragma unroll
        for (int ww = 0; ww < 4; ww++) {
          x[ww][0] = *reinterpret_cast<const float4*>(zb + ww * ZPB * 16 + roff0);
          x[ww][1] = *reinterpret_cast<const float4*>(zb + ww * ZPB * 16 + roff1);
        }
        const int sidx = half * 1024 + wtid * 8;
        const uint4 kvv = *reinterpret_cast<const uint4*>(&sm.u[c][UPAD + sidx]);
        if (half == 1 && c + 2 < CPC) bar_arrive(5 + zg, 256);
        uint4 o;
        o.x = pack2((x[0][0].x + x[1][0].x) + (x[2][0].x + x[3][0].x), (x[0][0].y + x[1][0].y) + (x[2][0].y + x[3][0].y));
        o.y = pack2((x[0][0].z + x[1][0].z) + (x[2][0].z + x[3][0].z), (x[0][0].w + x[1][0].w) + (x[2][0].w + x[3][0].w));
        o.z = pack2((x[0][1].x + x[1][1].x) + (x[2][1].x + x[3][1].x), (x[0][1].y + x[1][1].y) + (x[2][1].y + x[3][1].y));
        o.w = pack2((x[0][1].z + x[1][1].z) + (x[2][1].z + x[3][1].z), (x[0][1].w + x[1][1].w) + (x[2][1].w + x[3][1].w));
        o.x = b2u(__hadd2_rn(u2b(o.x), __hmul2_rn(u2b(kvv.x), d2)));
        o.y = b2u(__hadd2_rn(u2b(o.y), __hmul2_rn(u2b(kvv.y), d2)));
        o.z = b2u(__hadd2_rn(u2b(o.z), __hmul2_rn(u2b(kvv.z), d2)));
        o.w = b2u(__hadd2_rn(u2b(o.w), __hmul2_rn(u2b(kvv.w), d2)));
        st_pub4(g_y2 + ((64 * half + rpb) * 640 + c0 + c) * 2 + re2, enc4(o));
      }
    }
    if (wid == 11) bar_sync(8, 128); else bar_arrive(8, 128);
    asm volatile("setmaxnreg.inc.sync.aligned.u32 168;");
  }

  if (tid == 352) {
    asm volatile("red.relaxed.gpu.global.add.u32 [%0], 1;" ::"l"(&g_ctr3) : "memory");
    wait_ctr(&g_ctr3, sm.target3);
    asm volatile("mbarrier.arrive.shared.b64 _, [%0];" ::"r"(smem_u32(&sm.mbary)) : "memory");
  }
  __syncwarp();
  const int g = lane >> 2, tq = lane & 3;
  const int hh = wid & 1, gqi = wid >> 1;
  const int row = hh * 8 + g;
  uint32_t hreg[20], hnreg[20];
  {
    const uint4* src = g_y2 + cta * 1280 + tid;
    uint4 v[4];
    if (wid < 8) {
      mbar_wait(&sm.mbar);
#pragma unroll
      for (int k = 0; k < 5; k++) {
        const uint4 qv4 = *reinterpret_cast<const uint4*>(&sm.q[row][32 * (5 * gqi + k) + 8 * tq]);
        hreg[4 * k] = qv4.x; hreg[4 * k + 1] = qv4.y; hreg[4 * k + 2] = qv4.z; hreg[4 * k + 3] = qv4.w;
      }
      const float2 ps = row_part_stats(hreg);
      if (tq == 0) sm.stq[row][gqi] = ps;
      bar_sync(7, 256);
      row_normalize<false>(reinterpret_cast<const float4*>(sm.stq[row]), hreg, hnreg);
    }
    mbar_wait(&sm.mbary);
#pragma unroll
    for (int i = 0; i < 4; i++) if (i < 3 || tid < 128) v[i] = ld_poll4(src + NTHR * i);
    int it = 0;
    bool all;
    do {
      all = true;
#pragma unroll
      for (int i = 0; i < 4; i++)
        if ((i < 3 || tid < 128) && !ready4(v[i])) { v[i] = ld_poll4(src + NTHR * i); all = false; }
    } while (!all && ++it < SPIN_LIMIT);
#pragma unroll
    for (int i = 0; i < 4; i++) {
      if (i < 3 || tid < 128) {
        const int t = tid + NTHR * i;
        tile[(t & 1) * 640 + tile_perm(t >> 1)] = make_uint4(~v[i].x, ~v[i].y, ~v[i].z, ~v[i].w);
      }
    }
  }
  __syncthreads();

  if (wid < 8) {
#pragma unroll
    for (int k = 0; k < 5; k++) {
      const int base = 32 * (5 * gqi + k);
      const int lch = base + 8 * ((lane & 7) >> 1) + 2 * (lane >> 3) + (lane & 1);
      uint32_t y[4];
      asm volatile("ldmatrix.sync.aligned.m8n8.x4.trans.shared.b16 {%0,%1,%2,%3}, [%4];"
                   : "=r"(y[0]), "=r"(y[1]), "=r"(y[2]), "=r"(y[3]) : "r"(smem_u32(&tile[hh * 640 + tile_perm(lch)])) : "memory");
#pragma unroll
      for (int i = 0; i < 4; i++)
        hreg[4 * k + i] = b2u(__hadd2_rn(u2b(hreg[4 * k + i]), __hmul2_rn(u2b(hnreg[4 * k + i]), u2b(y[i]))));
    }
    const float2 ps = row_part_stats(hreg);
    if (tq == 0) sm.st[row][gqi] = ps;
    bar_sync(7, 256);
    row_normalize<false>(reinterpret_cast<const float4*>(sm.st[row]), hreg, hnreg);
    float cr[5][4];
#pragma unroll
    for (int k = 0; k < 5; k++) {
      cr[k][0] = cr[k][1] = cr[k][2] = cr[k][3] = 0.f;
      const uint4 w4 = sm.wr[4 * (5 * gqi + k) + tq];
      mma_bf16(cr[k], hnreg[4 * k + 0], hnreg[4 * k + 1], w4.x, w4.y);
      mma_bf16(cr[k], hnreg[4 * k + 2], hnreg[4 * k + 3], w4.z, w4.w);
    }
    if (tq == 0) sm.rp[row][gqi] = ((cr[0][0] + cr[1][0]) + (cr[2][0] + cr[3][0])) + cr[4][0];
  }
  __syncthreads();
  uint32_t best;
  {
    const int rr = lane & 15;
    const float4 rp4 = *reinterpret_cast<const float4*>(sm.rp[rr]);
    const float r = (rp4.x + rp4.y) + (rp4.z + rp4.w);
    const uint32_t bits = __bfloat16_as_ushort(__float2bfloat16_rn(r));
    const uint32_t ord = (bits & 0x8000u) ? (bits ^ 0xFFFFu) : (bits ^ 0x8000u);
    const uint32_t key = (ord << 16) | 0x8000u | (uint32_t)(2047 - (cta * 16 + rr));
    best = __reduce_max_sync(0xffffffffu, key);
  }
  if (wid >= 8) asm volatile("st.relaxed.gpu.global.u32 [%0], %1;" ::"l"(&g_keys[tid - 256][cta]), "r"(best) : "memory");
  const int brow = (2047 - (int)(best & 0x7FFu)) - cta * 16;
  if (wid < 8 && row == brow) {
#pragma unroll
    for (int k = 0; k < 5; k++)
      st_pub4(&g_cand[cta][0][4 * (5 * gqi + k) + tq], enc4(make_uint4(hnreg[4 * k], hnreg[4 * k + 1], hnreg[4 * k + 2], hnreg[4 * k + 3])));
#pragma unroll
    for (int k = 0; k < 5; k++)
      st_pub4(&g_cand[cta][1][4 * (5 * gqi + k) + tq], enc4(make_uint4(hreg[4 * k], hreg[4 * k + 1], hreg[4 * k + 2], hreg[4 * k + 3])));
  }
#pragma unroll
  for (int i = 0; i < 20; i++) hreg[i] = b2u(__hadd2_rn(u2b(hreg[i]), u2b(hnreg[i])));
  float wf[10][8];
  const int rs = cta < N1 ? (wid & 1) * 32 + lane : wid * 16 + (lane >> 1);
  if (cta < N1 + N2) {
    mbar_wait(&sm.mbarw);
    const uint4* wp = cta < N1 ? &sm.w[(wid / 6) * 1920 + rs * 3 + ((wid % 6) >> 1)] : &sm.w[rs * 2 + (lane & 1)];
    const int wstep = cta < N1 ? 192 : 384;
#pragma unroll
    for (int it = 0; it < 10; it++) {
      const uint4 wv = wp[(it < 8 || cta < N1) ? it * wstep : 0];
      wf[it][0] = lo_f(wv.x); wf[it][1] = hi_f(wv.x); wf[it][2] = lo_f(wv.y); wf[it][3] = hi_f(wv.y);
      wf[it][4] = lo_f(wv.z); wf[it][5] = hi_f(wv.z); wf[it][6] = lo_f(wv.w); wf[it][7] = hi_f(wv.w);
    }
#pragma unroll
    for (int it = 0; it < 10; it++)
#pragma unroll
      for (int j = 0; j < 8; j++) asm volatile("" : "+f"(wf[it][j]));
  }
  if (wid == 11) {
    const uint4* kp = reinterpret_cast<const uint4*>(&g_keys[cta][0]) + lane;
    uint4 v = ld_poll4(kp);
    int it = 0;
    while (!ready4(v) && ++it < SPIN_LIMIT) v = ld_poll4(kp);
    const uint32_t m = max(max(v.x, v.y), max(v.z, v.w));
    const uint32_t wk = __reduce_max_sync(0xffffffffu, m);
    if (lane == 0) sm.win = wk;
  }
  __syncthreads();
  const uint32_t win = sm.win;
  const int wrow = 2047 - (int)(win & 0x7FFu);
  const int wcta = wrow >> 4;
  const bool st_out = wid < 8 && (cta * 16 + row) != wrow;
  uint4* outp = reinterpret_cast<uint4*>(gout + (size_t)(cta * 16 + row) * D_) + 20 * gqi + tq;
  if (cta >= N1) {
    if (st_out) {
#pragma unroll
      for (int k = 0; k < 5; k++) outp[4 * k] = make_uint4(hreg[4 * k], hreg[4 * k + 1], hreg[4 * k + 2], hreg[4 * k + 3]);
    }
  }
  if (cta >= N1) {
#pragma unroll
    for (int i = 0; i < 4; i++) if (i < 3 || tid < 128) g_y2[cta * 1280 + tid + NTHR * i] = make_uint4(0, 0, 0, 0);
  }
  float* xs = &sm.z[0][0][0];
  float* part = xs + 2048;
  if (cta < N1) {
    if (tid < 80) {
      const uint4 v = poll4(&g_cand[wcta][0][tid]);
      float4* xp = reinterpret_cast<float4*>(xs + tid * 8);
      xp[0] = make_float4(lo_f(v.x), hi_f(v.x), lo_f(v.y), hi_f(v.y));
      xp[1] = make_float4(lo_f(v.z), hi_f(v.z), lo_f(v.w), hi_f(v.w));
    }
    __syncthreads();
    float a[8];
#pragma unroll
    for (int j = 0; j < 8; j++) a[j] = 0.f;
#pragma unroll
    for (int it = 0; it < 10; it++) {
      const float x = xs[rs + 64 * it];
#pragma unroll
      for (int j = 0; j < 8; j++) a[j] = fmaf(x, wf[it][j], a[j]);
    }
    {
      const bool up = lane & 16;
#pragma unroll
      for (int j = 0; j < 4; j++) {
        const float send = up ? a[j] : a[j + 4], keep = up ? a[j + 4] : a[j];
        a[j] = keep + __shfl_xor_sync(0xffffffffu, send, 16);
      }
      const bool up2 = lane & 8;
#pragma unroll
      for (int j = 0; j < 2; j++) {
        const float send = up2 ? a[j] : a[j + 2], keep = up2 ? a[j + 2] : a[j];
        a[j] = keep + __shfl_xor_sync(0xffffffffu, send, 8);
      }
      const bool up3 = lane & 4;
      const float send = up3 ? a[0] : a[1], keep = up3 ? a[1] : a[0];
      a[0] = keep + __shfl_xor_sync(0xffffffffu, send, 4);
      a[0] += __shfl_xor_sync(0xffffffffu, a[0], 2);
      a[0] += __shfl_xor_sync(0xffffffffu, a[0], 1);
      if ((lane & 3) == 0) part[wid * 8 + (lane >> 2)] = a[0];
    }
    __syncthreads();
    if (wid == 0) {
      uint32_t bits = 0;
      if (lane < 24) {
        const int hc2 = lane >> 3, j = lane & 7;
        const float gt = rbf(part[(2 * hc2) * 8 + j] + part[(2 * hc2 + 1) * 8 + j]);
        const float up = rbf(part[(6 + 2 * hc2) * 8 + j] + part[(6 + 2 * hc2 + 1) * 8 + j]);
        const float sg = rbf(gt / (1.f + __expf(-gt)));
        bits = __bfloat16_as_ushort(__float2bfloat16_rn(sg * up));
      }
      const uint32_t nb = __shfl_down_sync(0xffffffffu, bits, 1);
      const uint32_t pw = bits | (nb << 16);
      const uint32_t w1 = __shfl_down_sync(0xffffffffu, pw, 2), w2 = __shfl_down_sync(0xffffffffu, pw, 4), w3 = __shfl_down_sync(0xffffffffu, pw, 6);
      const uint4 mine = enc4(make_uint4(pw, w1, w2, w3));
#pragma unroll
      for (int i = 0; i < 4; i++) {
        const int t = lane + 32 * i;
        const int cons = t / 3, ck = t - 3 * cons;
        uint4 v;
        v.x = __shfl_sync(0xffffffffu, mine.x, 8 * ck); v.y = __shfl_sync(0xffffffffu, mine.y, 8 * ck);
        v.z = __shfl_sync(0xffffffffu, mine.z, 8 * ck); v.w = __shfl_sync(0xffffffffu, mine.w, 8 * ck);
        if (t < 3 * N2) st_pub4(&g_act[cons][cta * 3 + ck], v);
      }
      __syncwarp();
      bar_arrive(7, 384);
    } else {
      bar_sync(7, 384);
    }
#pragma unroll
    for (int i = 0; i < 4; i++) if (i < 3 || tid < 128) g_y2[cta * 1280 + tid + NTHR * i] = make_uint4(0, 0, 0, 0);
    if (st_out) {
#pragma unroll
      for (int k = 0; k < 5; k++) outp[4 * k] = make_uint4(hreg[4 * k], hreg[4 * k + 1], hreg[4 * k + 2], hreg[4 * k + 3]);
    }
  } else if (cta < N1 + N2) {
    const int j2 = cta - N1;
    uint4 rowv = make_uint4(0, 0, 0, 0);
    if (tid < 192) {
      const uint4 v = poll4(&g_act[j2][tid]);
      float4* xp = reinterpret_cast<float4*>(xs + tid * 8);
      xp[0] = make_float4(lo_f(v.x), hi_f(v.x), lo_f(v.y), hi_f(v.y));
      xp[1] = make_float4(lo_f(v.z), hi_f(v.z), lo_f(v.w), hi_f(v.w));
    } else if (tid < 196) {
      const int t = tid - 192;
      rowv = poll4(&g_cand[wcta][t >> 1][j2 * 2 + (t & 1)]);
      reinterpret_cast<uint4*>(part + 256)[t] = rowv;
    }
    __syncthreads();
    const int hc = lane & 1;
    float a[8];
#pragma unroll
    for (int j = 0; j < 8; j++) a[j] = 0.f;
#pragma unroll
    for (int it = 0; it < 8; it++) {
      const float x = xs[rs + 192 * it];
#pragma unroll
      for (int j = 0; j < 8; j++) a[j] = fmaf(x, wf[it][j], a[j]);
    }
    {
      const bool up = lane & 16;
#pragma unroll
      for (int j = 0; j < 4; j++) {
        const float send = up ? a[j] : a[j + 4], keep = up ? a[j + 4] : a[j];
        a[j] = keep + __shfl_xor_sync(0xffffffffu, send, 16);
      }
      const bool up2 = lane & 8;
#pragma unroll
      for (int j = 0; j < 2; j++) {
        const float send = up2 ? a[j] : a[j + 2], keep = up2 ? a[j + 2] : a[j];
        a[j] = keep + __shfl_xor_sync(0xffffffffu, send, 8);
      }
      const bool up3 = lane & 4;
      const float send = up3 ? a[0] : a[1], keep = up3 ? a[1] : a[0];
      a[0] = keep + __shfl_xor_sync(0xffffffffu, send, 4);
      a[0] += __shfl_xor_sync(0xffffffffu, a[0], 2);
      if ((lane & 2) == 0) part[wid * 16 + hc * 8 + (lane >> 2)] = a[0];
    }
    __syncthreads();
    if (tid < 16) {
      float y = 0.f;
#pragma unroll
      for (int i = 0; i < 12; i++) y += part[i * 16 + tid];
      const uint32_t ord = win >> 16;
      const uint32_t rb = (ord & 0x8000u) ? (ord ^ 0x8000u) : (ord ^ 0xFFFFu);
      const float r = __uint_as_float(rb << 16);
      const float sg = rbf(1.f / (1.f + __expf(-r)));
      const float yy = rbf(rbf(y) * sg);
      const unsigned short* rv = reinterpret_cast<const unsigned short*>(part + 256);
      const float hn = __uint_as_float((uint32_t)rv[tid] << 16), h = __uint_as_float((uint32_t)rv[16 + tid] << 16);
      gout[(size_t)wrow * D_ + j2 * 16 + tid] = __float2bfloat16_rn(h + rbf(hn + yy));
    }
  }
}

}

typedef CUresult (*EncodeFn)(CUtensorMap*, CUtensorMapDataType, cuuint32_t, void*, const cuuint64_t*, const cuuint64_t*,
                             const cuuint32_t*, const cuuint32_t*, CUtensorMapInterleave, CUtensorMapSwizzle,
                             CUtensorMapL2promotion, CUtensorMapFloatOOBfill);

extern "C" void kernel_launch(void* const* d_in, const int* in_sizes, int n_in, void* d_out, int out_size) {
  (void)in_sizes; (void)n_in; (void)out_size;
  static EncodeFn encode = nullptr;
  static CUtensorMap tmg, tmu, tmd;
  static void* cached[3] = {nullptr, nullptr, nullptr};
  if (!encode) {
    cudaFuncSetAttribute(fused_kernel, cudaFuncAttributeMaxDynamicSharedMemorySize, (int)sizeof(Smem));
    void* fn = nullptr;
    cudaDriverEntryPointQueryResult qr;
    cudaGetDriverEntryPoint("cuTensorMapEncodeTiled", &fn, cudaEnableDefault, &qr);
    encode = (EncodeFn)fn;
  }
  if (cached[0] != d_in[8] || cached[1] != d_in[9] || cached[2] != d_in[10]) {
    const cuuint32_t es[2] = {1, 1};
    {
      const cuuint64_t dims[2] = {F_, D_}, strides[1] = {F_ * 2};
      const cuuint32_t box[2] = {24, 160};
      encode(&tmg, CU_TENSOR_MAP_DATA_TYPE_BFLOAT16, 2, d_in[8], dims, strides, box, es, CU_TENSOR_MAP_INTERLEAVE_NONE,
             CU_TENSOR_MAP_SWIZZLE_NONE, CU_TENSOR_MAP_L2_PROMOTION_NONE, CU_TENSOR_MAP_FLOAT_OOB_FILL_NONE);
      encode(&tmu, CU_TENSOR_MAP_DATA_TYPE_BFLOAT16, 2, d_in[9], dims, strides, box, es, CU_TENSOR_MAP_INTERLEAVE_NONE,
             CU_TENSOR_MAP_SWIZZLE_NONE, CU_TENSOR_MAP_L2_PROMOTION_NONE, CU_TENSOR_MAP_FLOAT_OOB_FILL_NONE);
    }
    {
      const cuuint64_t dims[2] = {D_, F_}, strides[1] = {D_ * 2};
      const cuuint32_t box[2] = {16, 256};
      encode(&tmd, CU_TENSOR_MAP_DATA_TYPE_BFLOAT16, 2, d_in[10], dims, strides, box, es, CU_TENSOR_MAP_INTERLEAVE_NONE,
             CU_TENSOR_MAP_SWIZZLE_NONE, CU_TENSOR_MAP_L2_PROMOTION_NONE, CU_TENSOR_MAP_FLOAT_OOB_FILL_NONE);
    }
    cached[0] = d_in[8]; cached[1] = d_in[9]; cached[2] = d_in[10];
  }
  fused_kernel<<<NCTA, NTHR, sizeof(Smem), cudaStreamPerThread>>>(
      tmg, tmu, tmd, (const bf16*)d_in[0], (const bf16*)d_in[1], (const bf16*)d_in[2], (const bf16*)d_in[3],
      (const bf16*)d_in[4], (const bf16*)d_in[5], (const bf16*)d_in[7], (bf16*)d_out);
}
```

```cpp
#include <cuda_runtime.h>
#include <cuda_bf16.h>
#include <cuda.h>
#include <stdint.h>

namespace {

typedef __nv_bfloat16 bf16;
typedef __nv_bfloat162 bf162;

constexpr int S_ = 2048, D_ = 640, F_ = 1536;
constexpr int NCTA = 128, CPC = 5, NTHR = 384;
constexpr int UPAD = 136, USTR = 2192;
constexpr int TABW = 1040;
constexpr int ZPB = 132;
constexpr int QSTR = 648;
constexpr int N1 = 64;
constexpr int N2 = 40;
constexpr int SPIN_LIMIT = 1 << 19;
constexpr int POLL_NS = 100;

struct __align__(128) Smem {
  uint32_t tabA[3][2][TABW];
  uint32_t extra[1024];
  uint32_t tabB[2][2][TABW];
  bf16 u[CPC][USTR];
  float z[2][4][ZPB * 16];
  bf16 q[16][QSTR];
  alignas(128) uint4 w[3840];
  uint4 wr[80];
  alignas(16) float2 st[16][4];
  alignas(16) float2 stq[16][4];
  alignas(16) float rp[16][4];
  unsigned long long mbar;
  unsigned long long mbarw;
  unsigned long long mbarc;
  unsigned long long mbary;
  unsigned long long mbarh;
  uint32_t target;
  uint32_t target2;
  uint32_t target3;
  uint32_t best;
  uint32_t win;
};

__device__ uint4 g_kv[D_ * S_ / 8];
__device__ uint4 g_y2[D_ * S_ / 8];
__device__ uint32_t g_keys[NCTA][NCTA];
__device__ uint4 g_cand[NCTA][2][80];
__device__ uint4 g_act[N2][F_ / 8];
__device__ __align__(256) unsigned int g_ctrs[3][64];
#define g_ctr g_ctrs[0][0]
#define g_ctr2 g_ctrs[1][0]
#define g_ctr3 g_ctrs[2][0]

__device__ __forceinline__ uint32_t smem_u32(const void* p) { return (uint32_t)__cvta_generic_to_shared(p); }
__device__ __forceinline__ void wg_fence() { asm volatile("wgmma.fence.sync.aligned;" ::: "memory"); }
__device__ __forceinline__ void wg_commit() { asm volatile("wgmma.commit_group.sync.aligned;" ::: "memory"); }
template <int N> __device__ __forceinline__ void wg_wait() { asm volatile("wgmma.wait_group.sync.aligned %0;" ::"n"(N) : "memory"); }
__device__ __forceinline__ void bar_sync(int id, int n) { asm volatile("bar.sync %0, %1;" ::"r"(id), "r"(n) : "memory"); }
__device__ __forceinline__ void bar_arrive(int id, int n) { asm volatile("bar.arrive %0, %1;" ::"r"(id), "r"(n) : "memory"); }
__device__ __forceinline__ bf162 u2b(uint32_t u) { return *reinterpret_cast<bf162*>(&u); }
__device__ __forceinline__ uint32_t b2u(bf162 b) { return *reinterpret_cast<uint32_t*>(&b); }
__device__ __forceinline__ float lo_f(uint32_t u) { return __uint_as_float(u << 16); }
__device__ __forceinline__ float hi_f(uint32_t u) { return __uint_as_float(u & 0xFFFF0000u); }
__device__ __forceinline__ float rbf(float x) { return __bfloat162float(__float2bfloat16_rn(x)); }
__device__ __forceinline__ uint32_t pack2(float a, float b) { return b2u(__floats2bfloat162_rn(a, b)); }
__device__ __forceinline__ uint32_t enc(uint32_t w) { return max(~w, 1u); }
__device__ __forceinline__ uint4 enc4(uint4 v) { return make_uint4(enc(v.x), enc(v.y), enc(v.z), enc(v.w)); }
__device__ __forceinline__ uint4 ld_poll4(const uint4* p) {
  uint4 v;
  asm volatile("ld.relaxed.gpu.global.v4.u32 {%0,%1,%2,%3}, [%4];" : "=r"(v.x), "=r"(v.y), "=r"(v.z), "=r"(v.w) : "l"(p) : "memory");
  return v;
}
__device__ __forceinline__ bool ready4(uint4 v) { return v.x != 0u && v.y != 0u && v.z != 0u && v.w != 0u; }
__device__ __forceinline__ uint4 poll4(const uint4* p) {
  uint4 v = ld_poll4(p);
  int it = 0;
  while (!ready4(v) && ++it < SPIN_LIMIT) v = ld_poll4(p);
  return make_uint4(~v.x, ~v.y, ~v.z, ~v.w);
}
__device__ __forceinline__ void st_pub4(uint4* p, uint4 v) {
  asm volatile("st.relaxed.gpu.global.v4.u32 [%0], {%1,%2,%3,%4};" ::"l"(p), "r"(v.x), "r"(v.y), "r"(v.z), "r"(v.w) : "memory");
}
__device__ __forceinline__ void st_pub2(uint2* p, uint32_t a, uint32_t b) {
  asm volatile("st.relaxed.gpu.global.v2.u32 [%0], {%1,%2};" ::"l"(p), "r"(a), "r"(b) : "memory");
}
__device__ __forceinline__ void mma_bf16(float (&c)[4], uint32_t a0, uint32_t a2, uint32_t b0, uint32_t b1) {
  asm volatile("mma.sync.aligned.m16n8k16.row.col.f32.bf16.bf16.f32 {%0,%1,%2,%3}, {%4,%5,%6,%5}, {%7,%8}, {%0,%1,%2,%3};"
               : "+f"(c[0]), "+f"(c[1]), "+f"(c[2]), "+f"(c[3]) : "r"(a0), "r"(0u), "r"(a2), "r"(b0), "r"(b1));
}
__device__ __forceinline__ void mbar_wait(const unsigned long long* bar) {
  const uint32_t mb = smem_u32(bar);
  uint32_t ok = 0;
  int it = 0;
  while (!ok && ++it < SPIN_LIMIT)
    asm volatile("{ .reg .pred p; mbarrier.try_wait.parity.shared.b64 p, [%1], 0; selp.u32 %0, 1, 0, p; }" : "=r"(ok) : "r"(mb) : "memory");
}
__device__ __forceinline__ void bulk_g2s(void* dst, const void* src, uint32_t bytes, const unsigned long long* bar) {
  asm volatile("cp.async.bulk.shared::cluster.global.mbarrier::complete_tx::bytes [%0], [%1], %2, [%3];" ::"r"(smem_u32(dst)),
               "l"(src), "r"(bytes), "r"(smem_u32(bar)) : "memory");
}
__device__ __forceinline__ void mbar_expect(const unsigned long long* bar, uint32_t bytes) {
  asm volatile("mbarrier.arrive.expect_tx.shared.b64 _, [%0], %1;" ::"r"(smem_u32(bar)), "r"(bytes) : "memory");
}
__device__ __forceinline__ void mma_bf16x(float (&c)[4], uint32_t a0, uint32_t a1, uint32_t a2, uint32_t a3, uint32_t b0, uint32_t b1) {
  asm volatile("mma.sync.aligned.m16n8k16.row.col.f32.bf16.bf16.f32 {%0,%1,%2,%3}, {%4,%5,%6,%7}, {%8,%9}, {%0,%1,%2,%3};"
               : "+f"(c[0]), "+f"(c[1]), "+f"(c[2]), "+f"(c[3]) : "r"(a0), "r"(a1), "r"(a2), "r"(a3), "r"(b0), "r"(b1));
}
__device__ __forceinline__ float fdivr(float a, float d, float r) {
  float q = a * r;
  float e = fmaf(-q, d, a);
  return fmaf(e, r, q);
}

template <bool FIRST> __device__ __forceinline__ void wgmma32(float (&d)[16], const uint32_t* a, uint64_t desc) {
  if (FIRST) {
    asm volatile("wgmma.mma_async.sync.aligned.m64n32k16.f32.bf16.bf16 {%0,%1,%2,%3,%4,%5,%6,%7,%8,%9,%10,%11,%12,%13,%14,%15}, {%16,%17,%18,%19}, %20, 0, 1, 1, 0;"
                 : "+f"(d[0]), "+f"(d[1]), "+f"(d[2]), "+f"(d[3]), "+f"(d[4]), "+f"(d[5]), "+f"(d[6]), "+f"(d[7]),
                   "+f"(d[8]), "+f"(d[9]), "+f"(d[10]), "+f"(d[11]), "+f"(d[12]), "+f"(d[13]), "+f"(d[14]), "+f"(d[15])
                 : "r"(a[0]), "r"(a[1]), "r"(a[2]), "r"(a[3]), "l"(desc));
  } else {
    asm volatile("wgmma.mma_async.sync.aligned.m64n32k16.f32.bf16.bf16 {%0,%1,%2,%3,%4,%5,%6,%7,%8,%9,%10,%11,%12,%13,%14,%15}, {%16,%17,%18,%19}, %20, 1, 1, 1, 0;"
                 : "+f"(d[0]), "+f"(d[1]), "+f"(d[2]), "+f"(d[3]), "+f"(d[4]), "+f"(d[5]), "+f"(d[6]), "+f"(d[7]),
                   "+f"(d[8]), "+f"(d[9]), "+f"(d[10]), "+f"(d[11]), "+f"(d[12]), "+f"(d[13]), "+f"(d[14]), "+f"(d[15])
                 : "r"(a[0]), "r"(a[1]), "r"(a[2]), "r"(a[3]), "l"(desc));
  }
}

template <int G> __device__ __forceinline__ void load_a(uint32_t (&a)[8], const uint32_t* tp) {
#pragma unroll
  for (int q = 0; q < 2; q++) {
    const int e = 2 * G + q;
    a[4 * q + 0] = tp[-64 * e];
    a[4 * q + 1] = tp[-64 * e - 32];
    a[4 * q + 2] = tp[-64 * e + 4];
    a[4 * q + 3] = tp[-64 * e - 28];
  }
}
__device__ __forceinline__ void load_a_all(uint32_t (&a)[8][8], const uint32_t* tp) {
  load_a<0>(a[0], tp); load_a<1>(a[1], tp); load_a<2>(a[2], tp); load_a<3>(a[3], tp);
  load_a<4>(a[4], tp); load_a<5>(a[5], tp); load_a<6>(a[6], tp); load_a<7>(a[7], tp);
}
template <int G> __device__ __forceinline__ void issue_g(float (&acc)[8][16], uint32_t (&a)[8], uint64_t desc0) {
  wg_fence();
#pragma unroll
  for (int q = 0; q < 2; q++) {
#pragma unroll
    for (int b = G; b < 8; b++) {
      const int delta = 2 * b - (2 * G + q);
      if (G == 0 && q == 0) wgmma32<true>(acc[b], &a[4 * q], desc0 + (uint64_t)(int64_t)(16 * delta));
      else wgmma32<false>(acc[b], &a[4 * q], desc0 + (uint64_t)(int64_t)(16 * delta));
    }
  }
  wg_commit();
}
template <int B> __device__ __forceinline__ void fence_blk(float (&acc)[8][16]) {
#pragma unroll
  for (int i = 0; i < 16; i++) asm volatile("" : "+f"(acc[B][i])::"memory");
}
__device__ __forceinline__ void fence_a(uint32_t (&a)[8]) {
#pragma unroll
  for (int i = 0; i < 8; i++) asm volatile("" : "+r"(a[i])::"memory");
}
template <int B> __device__ __forceinline__ void sts_blk(float (&acc)[8][16], float* zw, int off_even, int off_odd) {
#pragma unroll
  for (int jj = 0; jj < 4; jj++) {
    const int j = 4 * B + jj;
    float p0 = acc[B][4 * jj + 0], p1 = acc[B][4 * jj + 1];
    if (jj > 0) { p0 += acc[B][4 * (jj - 1) + 2]; p1 += acc[B][4 * (jj - 1) + 3]; }
    else if (B > 0) { p0 += acc[B > 0 ? B - 1 : 0][14]; p1 += acc[B > 0 ? B - 1 : 0][15]; }
    zw[64 * j + off_even] = p0;
    zw[64 * j + off_odd] = p1;
  }
}
__device__ __forceinline__ int tab_off(int c) { return c == 4 ? 0 : (c + 1) * 2 * TABW + (c >= 2 ? 1024 : 0); }
__device__ __forceinline__ int tile_perm(int ch) { return ch ^ (((ch >> 3) & 3) << 1); }

__device__ __forceinline__ void wait_ctr(const unsigned int* ctr, uint32_t target) {
  uint32_t v;
  int it = 0;
  do {
    asm volatile("ld.acquire.gpu.global.u32 %0, [%1];" : "=r"(v) : "l"(ctr) : "memory");
  } while ((int)(v - target) < 0 && ++it < SPIN_LIMIT);
}

__device__ __forceinline__ float2 row_part_stats(const uint32_t (&x)[20]) {
  float cs[5][4];
#pragma unroll
  for (int k = 0; k < 5; k++) {
    cs[k][0] = cs[k][1] = cs[k][2] = cs[k][3] = 0.f;
    mma_bf16x(cs[k], x[4 * k + 0], x[4 * k + 2], x[4 * k + 1], x[4 * k + 3], 0x3F803F80u, 0x3F803F80u);
  }
  const float mean = ((((cs[0][0] + cs[0][2]) + (cs[1][0] + cs[1][2])) + ((cs[2][0] + cs[2][2]) + (cs[3][0] + cs[3][2]))) + (cs[4][0] + cs[4][2])) * (1.f / 160.f);
  float m2a = 0.f, m2b = 0.f, m2c = 0.f, m2d = 0.f;
#pragma unroll
  for (int i = 0; i < 20; i += 2) {
    const float a = lo_f(x[i]) - mean, b = hi_f(x[i]) - mean, c = lo_f(x[i + 1]) - mean, d = hi_f(x[i + 1]) - mean;
    m2a = fmaf(a, a, m2a); m2b = fmaf(b, b, m2b); m2c = fmaf(c, c, m2c); m2d = fmaf(d, d, m2d);
  }
  float m2 = (m2a + m2b) + (m2c + m2d);
  m2 += __shfl_xor_sync(0xffffffffu, m2, 1);
  m2 += __shfl_xor_sync(0xffffffffu, m2, 2);
  return make_float2(mean, m2);
}
template <bool EXACT> __device__ __forceinline__ void row_normalize(const float4* st, const uint32_t (&x)[20], uint32_t (&y)[20]) {
  const float4 p = st[0], q = st[1];
  const float mean = ((p.x + p.z) + (q.x + q.z)) * 0.25f;
  const float d0 = p.x - mean, d1 = p.z - mean, d2 = q.x - mean, d3 = q.z - mean;
  const float m2 = ((p.y + p.w) + (q.y + q.w)) + 160.f * ((d0 * d0 + d1 * d1) + (d2 * d2 + d3 * d3));
  const float hd = rbf(sqrtf(rbf(rbf(m2 * (1.f / D_)) + 1e-5f)));
  const float hr = __frcp_rn(hd);
  const bf162 hm2 = __float2bfloat162_rn(mean);
#pragma unroll
  for (int i = 0; i < 20; i++) {
    const uint32_t d = b2u(__hsub2_rn(u2b(x[i]), hm2));
    y[i] = EXACT ? pack2(fdivr(lo_f(d), hd, hr), fdivr(hi_f(d), hd, hr)) : pack2(lo_f(d) * hr, hi_f(d) * hr);
  }
}

__device__ __forceinline__ void gather_kv(Smem& sm, int c0, int tid) {
  mbar_wait(&sm.mbarc);
  uint4 v[4];
  uint4* src = g_kv + c0 * 256 + tid;
#pragma unroll
  for (int i = 0; i < 4; i++) if (i < 3 || tid >= 256) v[i] = ld_poll4(src + NTHR * i - (i == 3 ? 256 : 0));
#pragma unroll
  for (int i = 0; i < 4; i++) {
    if (i < 3 || tid >= 256) {
      const int t = tid + NTHR * i - (i == 3 ? 256 : 0);
      int it = 0;
      while (!ready4(v[i]) && ++it < SPIN_LIMIT) { __nanosleep(POLL_NS); v[i] = ld_poll4(g_kv + c0 * 256 + t); }
      *reinterpret_cast<uint4*>(&sm.u[t >> 8][UPAD + (t & 255) * 8]) = make_uint4(~v[i].x, ~v[i].y, ~v[i].z, ~v[i].w);
    }
  }
  asm volatile("fence.proxy.async.shared::cta;" ::: "memory");
  __syncthreads();
}

__global__ void __launch_bounds__(NTHR, 1)
fused_kernel(const __grid_constant__ CUtensorMap tmg, const __grid_constant__ CUtensorMap tmu,
             const __grid_constant__ CUtensorMap tmd, const bf16* __restrict__ gq, const bf16* __restrict__ gk, const bf16* __restrict__ gv,
             const bf16* __restrict__ gsk, const bf16* __restrict__ gh, const bf16* __restrict__ gD,
             const bf16* __restrict__ gwr, bf16* __restrict__ gout) {
  extern __shared__ __align__(128) unsigned char smraw[];
  Smem& sm = *reinterpret_cast<Smem*>(smraw);
  const int tid = threadIdx.x;
  const int cta = blockIdx.x;
  const int c0 = cta * CPC;
  const int lane = tid & 31;
  const int wid = tid >> 5;

  {
    uint4* hs = reinterpret_cast<uint4*>(&sm.z[0][0][0]);
    const int oc = tid >> 2;
    const int r0 = cta * 16 + (tid & 3) * 4;
    uint4 kk[7], vv[4], sk[4];
    if (tid < 320) {
      const uint4* kp = reinterpret_cast<const uint4*>(gk) + (size_t)r0 * 80 + oc;
      const uint4* vp = reinterpret_cast<const uint4*>(gv) + (size_t)r0 * 80 + oc;
#pragma unroll
      for (int i = 0; i < 7; i++) kk[i] = (i >= 3 || r0 > 0) ? __ldg(kp + (i - 3) * 80) : make_uint4(0, 0, 0, 0);
#pragma unroll
      for (int i = 0; i < 4; i++) vv[i] = __ldg(vp + i * 80);
#pragma unroll
      for (int i = 0; i < 4; i++) sk[i] = __ldg(reinterpret_cast<const uint4*>(gsk) + oc * 4 + i);
    } else if (tid == 320) {
      asm volatile("mbarrier.init.shared.b64 [%0], 1;" ::"r"(smem_u32(&sm.mbarh)) : "memory");
      asm volatile("mbarrier.init.shared.b64 [%0], 1;" ::"r"(smem_u32(&sm.mbar)) : "memory");
      asm volatile("mbarrier.init.shared.b64 [%0], 1;" ::"r"(smem_u32(&sm.mbarw)) : "memory");
      asm volatile("mbarrier.init.shared.b64 [%0], 1;" ::"r"(smem_u32(&sm.mbarc)) : "memory");
      asm volatile("mbarrier.init.shared.b64 [%0], 1;" ::"r"(smem_u32(&sm.mbary)) : "memory");
      asm volatile("fence.proxy.async.shared::cta;" ::: "memory");
    } else if (tid == 352) {
      uint32_t v1, v2, v3;
      asm volatile("ld.relaxed.gpu.global.u32 %0, [%1];" : "=r"(v1) : "l"(&g_ctr) : "memory");
      asm volatile("ld.relaxed.gpu.global.u32 %0, [%1];" : "=r"(v2) : "l"(&g_ctr2) : "memory");
      asm volatile("ld.relaxed.gpu.global.u32 %0, [%1];" : "=r"(v3) : "l"(&g_ctr3) : "memory");
      sm.target = (v1 / NCTA + 1u) * NCTA;
      sm.target2 = (v2 / NCTA + 1u) * NCTA;
      sm.target3 = (v3 / NCTA + 1u) * NCTA;
    }
    if (tid < 320) bar_sync(6, 384); else { bar_arrive(6, 384); bar_sync(5, 64); }
    if (tid < 320) {
      uint32_t o[4][4];
#pragma unroll
      for (int p = 0; p < 4; p++) {
        const bf162 w0 = u2b(__byte_perm(sk[p].x, sk[p].z, 0x5410)), w1 = u2b(__byte_perm(sk[p].x, sk[p].z, 0x7632));
        const bf162 w2 = u2b(__byte_perm(sk[p].y, sk[p].w, 0x5410)), w3 = u2b(__byte_perm(sk[p].y, sk[p].w, 0x7632));
        uint32_t kv[4];
#pragma unroll
        for (int i = 0; i < 4; i++) {
          const uint32_t k0 = p == 0 ? kk[i].x : p == 1 ? kk[i].y : p == 2 ? kk[i].z : kk[i].w;
          const uint32_t k1 = p == 0 ? kk[i + 1].x : p == 1 ? kk[i + 1].y : p == 2 ? kk[i + 1].z : kk[i + 1].w;
          const uint32_t k2 = p == 0 ? kk[i + 2].x : p == 1 ? kk[i + 2].y : p == 2 ? kk[i + 2].z : kk[i + 2].w;
          const uint32_t k3 = p == 0 ? kk[i + 3].x : p == 1 ? kk[i + 3].y : p == 2 ? kk[i + 3].z : kk[i + 3].w;
          const uint32_t vx = p == 0 ? vv[i].x : p == 1 ? vv[i].y : p == 2 ? vv[i].z : vv[i].w;
          bf162 a = __hmul2_rn(u2b(k0), w3);
          a = __hadd2_rn(a, __hmul2_rn(u2b(k1), w2));
          a = __hadd2_rn(a, __hmul2_rn(u2b(k2), w1));
          a = __hadd2_rn(a, __hmul2_rn(u2b(k3), w0));
          kv[i] = b2u(__hmul2_rn(a, u2b(vx)));
        }
        o[p][0] = enc(__byte_perm(kv[0], kv[1], 0x5410)); o[p][1] = enc(__byte_perm(kv[2], kv[3], 0x5410));
        o[p][2] = enc(__byte_perm(kv[0], kv[1], 0x7632)); o[p][3] = enc(__byte_perm(kv[2], kv[3], 0x7632));
      }
      uint2* dst = reinterpret_cast<uint2*>(g_kv) + (size_t)(oc * 8) * 512 + (r0 >> 2);
#pragma unroll
      for (int p = 0; p < 4; p++) {
        st_pub2(dst + (2 * p) * 512, o[p][0], o[p][1]);
        st_pub2(dst + (2 * p + 1) * 512, o[p][2], o[p][3]);
      }
      if (wid == 0) bar_sync(4, 320); else bar_arrive(4, 320);
      if (tid == 0) {
        asm volatile("red.relaxed.gpu.global.add.u32 [%0], 1;" ::"l"(&g_ctr2) : "memory");
      }
      __syncwarp();
    } else {
      const int t0 = tid - 320;
      const uint4 zz = make_uint4(0, 0, 0, 0);
      if (tid == 320) {
        mbar_expect(&sm.mbarh, CPC * S_ * 2);
        bulk_g2s(hs, gh + (size_t)c0 * S_, CPC * S_ * 2, &sm.mbarh);
      }
      __syncwarp();
      for (int t = t0; t < CPC * 17; t += 64) *reinterpret_cast<uint4*>(&sm.u[t / 17][(t % 17) * 8]) = zz;
      if (t0 < 40) *reinterpret_cast<uint4*>(&sm.tabA[0][0][0] + tab_off(t0 >> 3) + ((t0 >> 2) & 1) * TABW + 1024 + 4 * (t0 & 3)) = zz;
      (&g_cand[cta][0][0])[t0] = zz;
      (&g_cand[cta][0][0])[64 + t0] = zz;
      if (t0 < 32) (&g_cand[cta][0][0])[128 + t0] = zz;
      else reinterpret_cast<uint4*>(&g_keys[cta][0])[t0 - 32] = zz;
      if (cta >= N1 && cta < N1 + N2) {
#pragma unroll
        for (int i = 0; i < 3; i++) g_act[cta - N1][t0 + 64 * i] = zz;
      }
    }
    mbar_wait(&sm.mbarh);
#pragma unroll
    for (int i = 0; i < 4; i++) {
      const int t = (NTHR - 1 - tid) + NTHR * i;
      if (t < CPC * 256) {
        uint32_t* tb = &sm.tabA[0][0][0] + tab_off(t >> 8) + (255 - (t & 255)) * 4;
        const uint4 h = hs[t];
        const uint32_t hp = (t & 255) ? reinterpret_cast<const uint32_t*>(hs)[4 * t - 1] : 0u;
        uint4 r1, rr;
        r1.x = __byte_perm(h.w, 0, 0x1032); r1.y = __byte_perm(h.z, 0, 0x1032);
        r1.z = __byte_perm(h.y, 0, 0x1032); r1.w = __byte_perm(h.x, 0, 0x1032);
        rr.x = __byte_perm(h.w, h.z, 0x7610); rr.y = __byte_perm(h.z, h.y, 0x7610);
        rr.z = __byte_perm(h.y, h.x, 0x7610); rr.w = __byte_perm(h.x, hp, 0x7610);
        *reinterpret_cast<uint4*>(tb) = rr;
        *reinterpret_cast<uint4*>(tb + TABW) = r1;
      }
    }
  }
  __syncthreads();

  const int wg = __shfl_sync(0xffffffffu, tid >> 7, 0);
  const int wtid = tid & 127;
  uint4* tile = reinterpret_cast<uint4*>(&sm.tabB[0][0][0]);
  if (wg < 2) {
    asm volatile("setmaxnreg.inc.sync.aligned.u32 224;");
    const int w = (tid >> 5) & 3, g = lane >> 2, tq = lane & 3;
    float* zw = sm.z[wg][w];
    const int sw = 3 * (((tq + w) >> 1) & 1);
    const int off_even = 16 * (tq + w) + 4 * ((0 + (g >> 2)) ^ sw) + (g & 3);
    const int off_odd = 16 * (tq + w) + 4 * ((2 + (g >> 2)) ^ sw) + (g & 3);
    uint32_t a[8][8];
    const uint32_t* tp0 = &sm.tabA[0][g & 1][1019 - 8 * w - (g >> 1) + tq];
    load_a_all(a, tp0 + tab_off(wg));
    float acc[8][16];
#pragma unroll
    for (int b = 0; b < 8; b++)
#pragma unroll
      for (int i = 0; i < 16; i++) acc[b][i] = 0.f;
    gather_kv(sm, c0, tid);
#pragma unroll 1
    for (int c = wg; c < CPC; c += 2) {
      const uint64_t desc = (uint64_t)((smem_u32(&sm.u[c][UPAD - 8]) & 0x3FFFF) >> 4) | ((uint64_t)1 << 16) | ((uint64_t)8 << 32);
      if (c > 0) bar_sync(1 + wg, 256);
      issue_g<0>(acc, a[0], desc);
      issue_g<1>(acc, a[1], desc);
      issue_g<2>(acc, a[2], desc);
      issue_g<3>(acc, a[3], desc);
      issue_g<4>(acc, a[4], desc);
      issue_g<5>(acc, a[5], desc);
      if (c + 1 < CPC) bar_arrive(1 + (wg ^ 1), 256);
      issue_g<6>(acc, a[6], desc);
      issue_g<7>(acc, a[7], desc);
      if (c >= 2) bar_sync(5 + wg, 256);
      wg_wait<4>();
      fence_blk<0>(acc); fence_blk<1>(acc); fence_blk<2>(acc); fence_blk<3>(acc);
      sts_blk<0>(acc, zw, off_even, off_odd);
      sts_blk<1>(acc, zw, off_even, off_odd);
      sts_blk<2>(acc, zw, off_even, off_odd);
      sts_blk<3>(acc, zw, off_even, off_odd);
      bar_arrive(9 + wg, 256);
      wg_wait<0>();
      fence_blk<4>(acc); fence_blk<5>(acc); fence_blk<6>(acc); fence_blk<7>(acc);
#pragma unroll
      for (int i = 0; i < 8; i++) fence_a(a[i]);
      sts_blk<4>(acc, zw, off_even, off_odd);
      sts_blk<5>(acc, zw, off_even, off_odd);
      sts_blk<6>(acc, zw, off_even, off_odd);
      sts_blk<7>(acc, zw, off_even, off_odd);
      bar_arrive(3 + wg, 256);
      if (c + 2 < CPC) load_a_all(a, tp0 + tab_off(c + 2));
    }
    asm volatile("setmaxnreg.dec.sync.aligned.u32 168;");
  } else {
    asm volatile("setmaxnreg.dec.sync.aligned.u32 56;");
    if (((wtid & 15) >> 2) < ((wtid >> 4) & 3))
      *reinterpret_cast<uint4*>(&sm.z[wtid >> 6][(wtid >> 4) & 3][(wtid & 15) * 4]) = make_uint4(0, 0, 0, 0);
    if (wtid == 96) {
      __threadfence();
      asm volatile("red.relaxed.gpu.global.add.u32 [%0], 1;" ::"l"(&g_ctr) : "memory");
    }
    if (wtid == 64) {
      const unsigned target = sm.target2;
      uint32_t v;
      int it = 0;
      do {
        asm volatile("ld.relaxed.gpu.global.u32 %0, [%1];" : "=r"(v) : "l"(&g_ctr2) : "memory");
      } while ((int)(v - target) < 0 && ++it < SPIN_LIMIT);
      asm volatile("mbarrier.arrive.shared.b64 _, [%0];" ::"r"(smem_u32(&sm.mbarc)) : "memory");
    }
    __syncwarp();
    gather_kv(sm, c0, tid);
#pragma unroll
    for (int i = 0; i < 10; i++) g_kv[c0 * 256 + wtid + 128 * i] = make_uint4(0, 0, 0, 0);
    if (wtid == 96) wait_ctr(&g_ctr, sm.target);
    __syncwarp();
    if (wtid == 32) {
      const uint32_t mw = smem_u32(&sm.mbarw);
      mbar_expect(&sm.mbar, 17 * D_ * 2);
#pragma unroll 1
      for (int r = 0; r < 16; r++) bulk_g2s(&sm.q[r][0], gq + (size_t)(cta * 16 + r) * D_, D_ * 2, &sm.mbar);
      bulk_g2s(&sm.wr[0], gwr, D_ * 2, &sm.mbar);
      if (cta < N1) {
        asm volatile("mbarrier.arrive.expect_tx.shared.b64 _, [%0], %1;" ::"r"(mw), "r"(3840 * 16) : "memory");
#pragma unroll 1
        for (int i = 0; i < 4; i++) {
          asm volatile("cp.async.bulk.tensor.2d.shared::cluster.global.mbarrier::complete_tx::bytes [%0], [%1, {%3, %4}], [%2];" ::"r"(smem_u32(&sm.w[i * 480])),
                       "l"(&tmg), "r"(mw), "r"(cta * 24), "r"(i * 160) : "memory");
          asm volatile("cp.async.bulk.tensor.2d.shared::cluster.global.mbarrier::complete_tx::bytes [%0], [%1, {%3, %4}], [%2];" ::"r"(smem_u32(&sm.w[1920 + i * 480])),
                       "l"(&tmu), "r"(mw), "r"(cta * 24), "r"(i * 160) : "memory");
        }
      } else if (cta < N1 + N2) {
        asm volatile("mbarrier.arrive.expect_tx.shared.b64 _, [%0], %1;" ::"r"(mw), "r"(3072 * 16) : "memory");
#pragma unroll 1
        for (int i = 0; i < 6; i++)
          asm volatile("cp.async.bulk.tensor.2d.shared::cluster.global.mbarrier::complete_tx::bytes [%0], [%1, {%3, %4}], [%2];" ::"r"(smem_u32(&sm.w[i * 512])),
                       "l"(&tmd), "r"(mw), "r"((cta - N1) * 16), "r"(i * 256) : "memory");
      }
    }
    const int rpb = wtid >> 1, re2 = wtid & 1;
    const int rsw = 3 * ((rpb >> 1) & 1);
    const int roff0 = 16 * rpb + 4 * ((2 * re2 + 0) ^ rsw);
    const int roff1 = 16 * rpb + 4 * ((2 * re2 + 1) ^ rsw);
    const uint32_t dvl = reinterpret_cast<const unsigned short*>(gD)[c0 + (lane < CPC ? lane : 0)];
#pragma unroll 1
    for (int c = 0; c < CPC; c++) {
      const int zg = c & 1;
      const uint32_t dvc = __shfl_sync(0xffffffffu, dvl, c);
      const bf162 d2 = u2b(dvc | (dvc << 16));
#pragma unroll
      for (int half = 0; half < 2; half++) {
        bar_sync((half ? 3 : 9) + zg, 256);
        const float* zb = sm.z[zg][0] + half * 1024;
        float4 x[4][2];
#pragma unroll
        for (int ww = 0; ww < 4; ww++) {
          x[ww][0] = *reinterpret_cast<const float4*>(zb + ww * ZPB * 16 + roff0);
          x[ww][1] = *reinterpret_cast<const float4*>(zb + ww * ZPB * 16 + roff1);
        }
        const int sidx = half * 1024 + wtid * 8;
        const uint4 kvv = *reinterpret_cast<const uint4*>(&sm.u[c][UPAD + sidx]);
        if (half == 1 && c + 2 < CPC) bar_arrive(5 + zg, 256);
        uint4 o;
        o.x = pack2((x[0][0].x + x[1][0].x) + (x[2][0].x + x[3][0].x), (x[0][0].y + x[1][0].y) + (x[2][0].y + x[3][0].y));
        o.y = pack2((x[0][0].z + x[1][0].z) + (x[2][0].z + x[3][0].z), (x[0][0].w + x[1][0].w) + (x[2][0].w + x[3][0].w));
        o.z = pack2((x[0][1].x + x[1][1].x) + (x[2][1].x + x[3][1].x), (x[0][1].y + x[1][1].y) + (x[2][1].y + x[3][1].y));
        o.w = pack2((x[0][1].z + x[1][1].z) + (x[2][1].z + x[3][1].z), (x[0][1].w + x[1][1].w) + (x[2][1].w + x[3][1].w));
        o.x = b2u(__hadd2_rn(u2b(o.x), __hmul2_rn(u2b(kvv.x), d2)));
        o.y = b2u(__hadd2_rn(u2b(o.y), __hmul2_rn(u2b(kvv.y), d2)));
        o.z = b2u(__hadd2_rn(u2b(o.z), __hmul2_rn(u2b(kvv.z), d2)));
        o.w = b2u(__hadd2_rn(u2b(o.w), __hmul2_rn(u2b(kvv.w), d2)));
        st_pub4(g_y2 + ((64 * half + rpb) * 640 + c0 + c) * 2 + re2, enc4(o));
      }
    }
    if (wid == 11) bar_sync(8, 128); else bar_arrive(8, 128);
    asm volatile("setmaxnreg.inc.sync.aligned.u32 168;");
  }

  if (tid == 352) {
    asm volatile("red.relaxed.gpu.global.add.u32 [%0], 1;" ::"l"(&g_ctr3) : "memory");
    wait_ctr(&g_ctr3, sm.target3);
    asm volatile("mbarrier.arrive.shared.b64 _, [%0];" ::"r"(smem_u32(&sm.mbary)) : "memory");
  }
  __syncwarp();
  const int g = lane >> 2, tq = lane & 3;
  const int hh = wid & 1, gqi = wid >> 1;
  const int row = hh * 8 + g;
  uint32_t hreg[20], hnreg[20];
  uint4 wr4[5];
  {
    const uint4* src = g_y2 + cta * 1280 + tid;
    uint4 v[4];
    if (wid < 8) {
      mbar_wait(&sm.mbar);
#pragma unroll
      for (int k = 0; k < 5; k++) {
        const uint4 qv4 = *reinterpret_cast<const uint4*>(&sm.q[row][32 * (5 * gqi + k) + 8 * tq]);
        hreg[4 * k] = qv4.x; hreg[4 * k + 1] = qv4.y; hreg[4 * k + 2] = qv4.z; hreg[4 * k + 3] = qv4.w;
        wr4[k] = sm.wr[4 * (5 * gqi + k) + tq];
      }
      const float2 ps = row_part_stats(hreg);
      if (tq == 0) sm.stq[row][gqi] = ps;
      bar_sync(7, 256);
      row_normalize<false>(reinterpret_cast<const float4*>(sm.stq[row]), hreg, hnreg);
    }
    mbar_wait(&sm.mbary);
#pragma unroll
    for (int i = 0; i < 4; i++) if (i < 3 || tid < 128) v[i] = ld_poll4(src + NTHR * i);
    int it = 0;
    bool all;
    do {
      all = true;
#pragma unroll
      for (int i = 0; i < 4; i++)
        if ((i < 3 || tid < 128) && !ready4(v[i])) { v[i] = ld_poll4(src + NTHR * i); all = false; }
    } while (!all && ++it < SPIN_LIMIT);
#pragma unroll
    for (int i = 0; i < 4; i++) {
      if (i < 3 || tid < 128) {
        const int t = tid + NTHR * i;
        tile[(t & 1) * 640 + tile_perm(t >> 1)] = make_uint4(~v[i].x, ~v[i].y, ~v[i].z, ~v[i].w);
      }
    }
  }
  __syncthreads();

  if (wid < 8) {
#pragma unroll
    for (int k = 0; k < 5; k++) {
      const int base = 32 * (5 * gqi + k);
      const int lch = base + 8 * ((lane & 7) >> 1) + 2 * (lane >> 3) + (lane & 1);
      uint32_t y[4];
      asm volatile("ldmatrix.sync.aligned.m8n8.x4.trans.shared.b16 {%0,%1,%2,%3}, [%4];"
                   : "=r"(y[0]), "=r"(y[1]), "=r"(y[2]), "=r"(y[3]) : "r"(smem_u32(&tile[hh * 640 + tile_perm(lch)])) : "memory");
#pragma unroll
      for (int i = 0; i < 4; i++)
        hreg[4 * k + i] = b2u(__hadd2_rn(u2b(hreg[4 * k + i]), __hmul2_rn(u2b(hnreg[4 * k + i]), u2b(y[i]))));
    }
    const float2 ps = row_part_stats(hreg);
    if (tq == 0) sm.st[row][gqi] = ps;
    bar_sync(7, 256);
    row_normalize<false>(reinterpret_cast<const float4*>(sm.st[row]), hreg, hnreg);
    float cr[5][4];
#pragma unroll
    for (int k = 0; k < 5; k++) {
      cr[k][0] = cr[k][1] = cr[k][2] = cr[k][3] = 0.f;
      const uint4 w4 = wr4[k];
      mma_bf16(cr[k], hnreg[4 * k + 0], hnreg[4 * k + 1], w4.x, w4.y);
      mma_bf16(cr[k], hnreg[4 * k + 2], hnreg[4 * k + 3], w4.z, w4.w);
    }
    if (tq == 0) sm.rp[row][gqi] = ((cr[0][0] + cr[1][0]) + (cr[2][0] + cr[3][0])) + cr[4][0];
  }
  __syncthreads();
  uint32_t best;
  {
    const int rr = lane & 15;
    const float4 rp4 = *reinterpret_cast<const float4*>(sm.rp[rr]);
    const float r = (rp4.x + rp4.y) + (rp4.z + rp4.w);
    const uint32_t bits = __bfloat16_as_ushort(__float2bfloat16_rn(r));
    const uint32_t ord = (bits & 0x8000u) ? (bits ^ 0xFFFFu) : (bits ^ 0x8000u);
    const uint32_t key = (ord << 16) | 0x8000u | (uint32_t)(2047 - (cta * 16 + rr));
    best = __reduce_max_sync(0xffffffffu, key);
  }
  if (wid >= 8) asm volatile("st.relaxed.gpu.global.u32 [%0], %1;" ::"l"(&g_keys[tid - 256][cta]), "r"(best) : "memory");
  const int brow = (2047 - (int)(best & 0x7FFu)) - cta * 16;
  if (wid < 8 && row == brow) {
#pragma unroll
    for (int k = 0; k < 5; k++)
      st_pub4(&g_cand[cta][0][4 * (5 * gqi + k) + tq], enc4(make_uint4(hnreg[4 * k], hnreg[4 * k + 1], hnreg[4 * k + 2], hnreg[4 * k + 3])));
#pragma unroll
    for (int k = 0; k < 5; k++)
      st_pub4(&g_cand[cta][1][4 * (5 * gqi + k) + tq], enc4(make_uint4(hreg[4 * k], hreg[4 * k + 1], hreg[4 * k + 2], hreg[4 * k + 3])));
  }
#pragma unroll
  for (int i = 0; i < 20; i++) hreg[i] = b2u(__hadd2_rn(u2b(hreg[i]), u2b(hnreg[i])));
  float wf[10][8];
  const int rs = cta < N1 ? (wid & 1) * 32 + lane : wid * 16 + (lane >> 1);
  if (cta < N1 + N2) {
    mbar_wait(&sm.mbarw);
    const uint4* wp = cta < N1 ? &sm.w[(wid / 6) * 1920 + rs * 3 + ((wid % 6) >> 1)] : &sm.w[rs * 2 + (lane & 1)];
    const int wstep = cta < N1 ? 192 : 384;
#pragma unroll
    for (int it = 0; it < 10; it++) {
      const uint4 wv = wp[(it < 8 || cta < N1) ? it * wstep : 0];
      wf[it][0] = lo_f(wv.x); wf[it][1] = hi_f(wv.x); wf[it][2] = lo_f(wv.y); wf[it][3] = hi_f(wv.y);
      wf[it][4] = lo_f(wv.z); wf[it][5] = hi_f(wv.z); wf[it][6] = lo_f(wv.w); wf[it][7] = hi_f(wv.w);
    }
#pragma unroll
    for (int it = 0; it < 10; it++)
#pragma unroll
      for (int j = 0; j < 8; j++) asm volatile("" : "+f"(wf[it][j]));
  }
  if (wid == 11) {
    const uint4* kp = reinterpret_cast<const uint4*>(&g_keys[cta][0]) + lane;
    uint4 v = ld_poll4(kp);
    int it = 0;
    while (!ready4(v) && ++it < SPIN_LIMIT) v = ld_poll4(kp);
    const uint32_t m = max(max(v.x, v.y), max(v.z, v.w));
    const uint32_t wk = __reduce_max_sync(0xffffffffu, m);
    if (lane == 0) sm.win = wk;
  }
  __syncthreads();
  const uint32_t win = sm.win;
  const int wrow = 2047 - (int)(win & 0x7FFu);
  const int wcta = wrow >> 4;
  const bool st_out = wid < 8 && (cta * 16 + row) != wrow;
  uint4* outp = reinterpret_cast<uint4*>(gout + (size_t)(cta * 16 + row) * D_) + 20 * gqi + tq;
  if (cta >= N1) {
    if (st_out) {
#pragma unroll
      for (int k = 0; k < 5; k++) outp[4 * k] = make_uint4(hreg[4 * k], hreg[4 * k + 1], hreg[4 * k + 2], hreg[4 * k + 3]);
    }
  }
  if (cta >= N1) {
#pragma unroll
    for (int i = 0; i < 4; i++) if (i < 3 || tid < 128) g_y2[cta * 1280 + tid + NTHR * i] = make_uint4(0, 0, 0, 0);
  }
  float* xs = &sm.z[0][0][0];
  float* part = xs + 2048;
  if (cta < N1) {
    if (tid < 80) {
      const uint4 v = poll4(&g_cand[wcta][0][tid]);
      float4* xp = reinterpret_cast<float4*>(xs + tid * 8);
      xp[0] = make_float4(lo_f(v.x), hi_f(v.x), lo_f(v.y), hi_f(v.y));
      xp[1] = make_float4(lo_f(v.z), hi_f(v.z), lo_f(v.w), hi_f(v.w));
    }
    __syncthreads();
    float a[8];
#pragma unroll
    for (int j = 0; j < 8; j++) a[j] = 0.f;
#pragma unroll
    for (int it = 0; it < 10; it++) {
      const float x = xs[rs + 64 * it];
#pragma unroll
      for (int j = 0; j < 8; j++) a[j] = fmaf(x, wf[it][j], a[j]);
    }
    {
      const bool up = lane & 16;
#pragma unroll
      for (int j = 0; j < 4; j++) {
        const float send = up ? a[j] : a[j + 4], keep = up ? a[j + 4] : a[j];
        a[j] = keep + __shfl_xor_sync(0xffffffffu, send, 16);
      }
      const bool up2 = lane & 8;
#pragma unroll
      for (int j = 0; j < 2; j++) {
        const float send = up2 ? a[j] : a[j + 2], keep = up2 ? a[j + 2] : a[j];
        a[j] = keep + __shfl_xor_sync(0xffffffffu, send, 8);
      }
      const bool up3 = lane & 4;
      const float send = up3 ? a[0] : a[1], keep = up3 ? a[1] : a[0];
      a[0] = keep + __shfl_xor_sync(0xffffffffu, send, 4);
      a[0] += __shfl_xor_sync(0xffffffffu, a[0], 2);
      a[0] += __shfl_xor_sync(0xffffffffu, a[0], 1);
      if ((lane & 3) == 0) part[wid * 8 + (lane >> 2)] = a[0];
    }
    __syncthreads();
    if (wid == 0) {
      uint32_t bits = 0;
      if (lane < 24) {
        const int hc2 = lane >> 3, j = lane & 7;
        const float gt = rbf(part[(2 * hc2) * 8 + j] + part[(2 * hc2 + 1) * 8 + j]);
        const float up = rbf(part[(6 + 2 * hc2) * 8 + j] + part[(6 + 2 * hc2 + 1) * 8 + j]);
        const float sg = rbf(gt / (1.f + __expf(-gt)));
        bits = __bfloat16_as_ushort(__float2bfloat16_rn(sg * up));
      }
      const uint32_t nb = __shfl_down_sync(0xffffffffu, bits, 1);
      const uint32_t pw = bits | (nb << 16);
      const uint32_t w1 = __shfl_down_sync(0xffffffffu, pw, 2), w2 = __shfl_down_sync(0xffffffffu, pw, 4), w3 = __shfl_down_sync(0xffffffffu, pw, 6);
      const uint4 mine = enc4(make_uint4(pw, w1, w2, w3));
#pragma unroll
      for (int i = 0; i < 4; i++) {
        const int t = lane + 32 * i;
        const int cons = t / 3, ck = t - 3 * cons;
        uint4 v;
        v.x = __shfl_sync(0xffffffffu, mine.x, 8 * ck); v.y = __shfl_sync(0xffffffffu, mine.y, 8 * ck);
        v.z = __shfl_sync(0xffffffffu, mine.z, 8 * ck); v.w = __shfl_sync(0xffffffffu, mine.w, 8 * ck);
        if (t < 3 * N2) st_pub4(&g_act[cons][cta * 3 + ck], v);
      }
      __syncwarp();
      bar_arrive(7, 384);
    } else {
      bar_sync(7, 384);
    }
#pragma unroll
    for (int i = 0; i < 4; i++) if (i < 3 || tid < 128) g_y2[cta * 1280 + tid + NTHR * i] = make_uint4(0, 0, 0, 0);
    if (st_out) {
#pragma unroll
      for (int k = 0; k < 5; k++) outp[4 * k] = make_uint4(hreg[4 * k], hreg[4 * k + 1], hreg[4 * k + 2], hreg[4 * k + 3]);
    }
  } else if (cta < N1 + N2) {
    const int j2 = cta - N1;
    uint4 rowv = make_uint4(0, 0, 0, 0);
    if (tid < 192) {
      const uint4 v = poll4(&g_act[j2][tid]);
      float4* xp = reinterpret_cast<float4*>(xs + tid * 8);
      xp[0] = make_float4(lo_f(v.x), hi_f(v.x), lo_f(v.y), hi_f(v.y));
      xp[1] = make_float4(lo_f(v.z), hi_f(v.z), lo_f(v.w), hi_f(v.w));
    } else if (tid < 196) {
      const int t = tid - 192;
      rowv = poll4(&g_cand[wcta][t >> 1][j2 * 2 + (t & 1)]);
      reinterpret_cast<uint4*>(part + 256)[t] = rowv;
    }
    const uint32_t ord = win >> 16;
    const uint32_t rb = (ord & 0x8000u) ? (ord ^ 0x8000u) : (ord ^ 0xFFFFu);
    float sg = rbf(1.f / (1.f + __expf(-__uint_as_float(rb << 16))));
    asm volatile("" : "+f"(sg));
    __syncthreads();
    const unsigned short* rv = reinterpret_cast<const unsigned short*>(part + 256);
    const float hn = __uint_as_float((uint32_t)rv[tid & 15] << 16), h = __uint_as_float((uint32_t)rv[16 + (tid & 15)] << 16);
    const int hc = lane & 1;
    float a[8];
#pragma unroll
    for (int j = 0; j < 8; j++) a[j] = 0.f;
#pragma unroll
    for (int it = 0; it < 8; it++) {
      const float x = xs[rs + 192 * it];
#pragma unroll
      for (int j = 0; j < 8; j++) a[j] = fmaf(x, wf[it][j], a[j]);
    }
    {
      const bool up = lane & 16;
#pragma unroll
      for (int j = 0; j < 4; j++) {
        const float send = up ? a[j] : a[j + 4], keep = up ? a[j + 4] : a[j];
        a[j] = keep + __shfl_xor_sync(0xffffffffu, send, 16);
      }
      const bool up2 = lane & 8;
#pragma unroll
      for (int j = 0; j < 2; j++) {
        const float send = up2 ? a[j] : a[j + 2], keep = up2 ? a[j + 2] : a[j];
        a[j] = keep + __shfl_xor_sync(0xffffffffu, send, 8);
      }
      const bool up3 = lane & 4;
      const float send = up3 ? a[0] : a[1], keep = up3 ? a[1] : a[0];
      a[0] = keep + __shfl_xor_sync(0xffffffffu, send, 4);
      a[0] += __shfl_xor_sync(0xffffffffu, a[0], 2);
      if ((lane & 2) == 0) part[wid * 16 + hc * 8 + (lane >> 2)] = a[0];
    }
    __syncthreads();
    if (tid < 16) {
      float y0 = 0.f, y1 = 0.f, y2 = 0.f;
#pragma unroll
      for (int i = 0; i < 4; i++) { y0 += part[i * 16 + tid]; y1 += part[(4 + i) * 16 + tid]; y2 += part[(8 + i) * 16 + tid]; }
      const float yy = rbf(rbf((y0 + y1) + y2) * sg);
      gout[(size_t)wrow * D_ + j2 * 16 + tid] = __float2bfloat16_rn(h + rbf(hn + yy));
    }
  }
}

}

typedef CUresult (*EncodeFn)(CUtensorMap*, CUtensorMapDataType, cuuint32_t, void*, const cuuint64_t*, const cuuint64_t*,
                             const cuuint32_t*, const cuuint32_t*, CUtensorMapInterleave, CUtensorMapSwizzle,
                             CUtensorMapL2promotion, CUtensorMapFloatOOBfill);

extern "C" void kernel_launch(void* const* d_in, const int* in_sizes, int n_in, void* d_out, int out_size) {
  (void)in_sizes; (void)n_in; (void)out_size;
  static EncodeFn encode = nullptr;
  static CUtensorMap tmg, tmu, tmd;
  static void* cached[3] = {nullptr, nullptr, nullptr};
  if (!encode) {
    cudaFuncSetAttribute(fused_kernel, cudaFuncAttributeMaxDynamicSharedMemorySize, (int)sizeof(Smem));
    void* fn = nullptr;
    cudaDriverEntryPointQueryResult qr;
    cudaGetDriverEntryPoint("cuTensorMapEncodeTiled", &fn, cudaEnableDefault, &qr);
    encode = (EncodeFn)fn;
  }
  if (cached[0] != d_in[8] || cached[1] != d_in[9] || cached[2] != d_in[10]) {
    const cuuint32_t es[2] = {1, 1};
    {
      const cuuint64_t dims[2] = {F_, D_}, strides[1] = {F_ * 2};
      const cuuint32_t box[2] = {24, 160};
      encode(&tmg, CU_TENSOR_MAP_DATA_TYPE_BFLOAT16, 2, d_in[8], dims, strides, box, es, CU_TENSOR_MAP_INTERLEAVE_NONE,
             CU_TENSOR_MAP_SWIZZLE_NONE, CU_TENSOR_MAP_L2_PROMOTION_NONE, CU_TENSOR_MAP_FLOAT_OOB_FILL_NONE);
      encode(&tmu, CU_TENSOR_MAP_DATA_TYPE_BFLOAT16, 2, d_in[9], dims, strides, box, es, CU_TENSOR_MAP_INTERLEAVE_NONE,
             CU_TENSOR_MAP_SWIZZLE_NONE, CU_TENSOR_MAP_L2_PROMOTION_NONE, CU_TENSOR_MAP_FLOAT_OOB_FILL_NONE);
    }
    {
      const cuuint64_t dims[2] = {D_, F_}, strides[1] = {D_ * 2};
      const cuuint32_t box[2] = {16, 256};
      encode(&tmd, CU_TENSOR_MAP_DATA_TYPE_BFLOAT16, 2, d_in[10], dims, strides, box, es, CU_TENSOR_MAP_INTERLEAVE_NONE,
             CU_TENSOR_MAP_SWIZZLE_NONE, CU_TENSOR_MAP_L2_PROMOTION_NONE, CU_TENSOR_MAP_FLOAT_OOB_FILL_NONE);
    }
    cached[0] = d_in[8]; cached[1] = d_in[9]; cached[2] = d_in[10];
  }
  fused_kernel<<<NCTA, NTHR, sizeof(Smem), cudaStreamPerThread>>>(
      tmg, tmu, tmd, (const bf16*)d_in[0], (const bf16*)d_in[1], (const bf16*)d_in[2], (const bf16*)d_in[3],
      (const bf16*)d_in[4], (const bf16*)d_in[5], (const bf16*)d_in[7], (bf16*)d_out);
}
```

```cpp
#include <cuda_runtime.h>
#include <cuda_bf16.h>
#include <cuda.h>
#include <stdint.h>

namespace {

typedef __nv_bfloat16 bf16;
typedef __nv_bfloat162 bf162;

constexpr int S_ = 2048, D_ = 640, F_ = 1536;
constexpr int NCTA = 128, CPC = 5, NTHR = 384;
constexpr int UPAD = 136, USTR = 2192;
constexpr int TABW = 1040;
constexpr int ZPB = 132;
constexpr int QSTR = 648;
constexpr int N1 = 64;
constexpr int N2 = 40;
constexpr int SPIN_LIMIT = 1 << 19;
constexpr int POLL_NS = 100;

struct __align__(128) Smem {
  uint32_t tabA[3][2][TABW];
  uint32_t extra[1024];
  uint32_t tabB[2][2][TABW];
  bf16 u[CPC][USTR];
  float z[2][4][ZPB * 16];
  bf16 q[16][QSTR];
  alignas(128) uint4 w[3840];
  uint4 wr[80];
  alignas(16) float2 st[16][4];
  alignas(16) float2 stq[16][4];
  alignas(16) float rp[16][4];
  unsigned long long mbar;
  unsigned long long mbarw;
  unsigned long long mbarc;
  unsigned long long mbary;
  unsigned long long mbarh;
  uint32_t target;
  uint32_t target2;
  uint32_t target3;
  uint32_t best;
  uint32_t win;
};

__device__ uint4 g_kv[D_ * S_ / 8];
__device__ uint4 g_y2[D_ * S_ / 8];
__device__ uint32_t g_keys[NCTA][NCTA];
__device__ uint4 g_cand[NCTA][2][80];
__device__ uint4 g_act[N2][F_ / 8];
__device__ __align__(256) unsigned int g_ctrs[3][64];
#define g_ctr g_ctrs[0][0]
#define g_ctr2 g_ctrs[1][0]
#define g_ctr3 g_ctrs[2][0]

__device__ __forceinline__ uint32_t smem_u32(const void* p) { return (uint32_t)__cvta_generic_to_shared(p); }
__device__ __forceinline__ void wg_fence() { asm volatile("wgmma.fence.sync.aligned;" ::: "memory"); }
__device__ __forceinline__ void wg_commit() { asm volatile("wgmma.commit_group.sync.aligned;" ::: "memory"); }
template <int N> __device__ __forceinline__ void wg_wait() { asm volatile("wgmma.wait_group.sync.aligned %0;" ::"n"(N) : "memory"); }
__device__ __forceinline__ void bar_sync(int id, int n) { asm volatile("bar.sync %0, %1;" ::"r"(id), "r"(n) : "memory"); }
__device__ __forceinline__ void bar_arrive(int id, int n) { asm volatile("bar.arrive %0, %1;" ::"r"(id), "r"(n) : "memory"); }
__device__ __forceinline__ bf162 u2b(uint32_t u) { return *reinterpret_cast<bf162*>(&u); }
__device__ __forceinline__ uint32_t b2u(bf162 b) { return *reinterpret_cast<uint32_t*>(&b); }
__device__ __forceinline__ float lo_f(uint32_t u) { return __uint_as_float(u << 16); }
__device__ __forceinline__ float hi_f(uint32_t u) { return __uint_as_float(u & 0xFFFF0000u); }
__device__ __forceinline__ float rbf(float x) { return __bfloat162float(__float2bfloat16_rn(x)); }
__device__ __forceinline__ uint32_t pack2(float a, float b) { return b2u(__floats2bfloat162_rn(a, b)); }
__device__ __forceinline__ uint32_t enc(uint32_t w) { return max(~w, 1u); }
__device__ __forceinline__ uint4 enc4(uint4 v) { return make_uint4(enc(v.x), enc(v.y), enc(v.z), enc(v.w)); }
__device__ __forceinline__ uint4 ld_poll4(const uint4* p) {
  uint4 v;
  asm volatile("ld.relaxed.gpu.global.v4.u32 {%0,%1,%2,%3}, [%4];" : "=r"(v.x), "=r"(v.y), "=r"(v.z), "=r"(v.w) : "l"(p) : "memory");
  return v;
}
__device__ __forceinline__ bool ready4(uint4 v) { return v.x != 0u && v.y != 0u && v.z != 0u && v.w != 0u; }
__device__ __forceinline__ uint4 poll4(const uint4* p) {
  uint4 v = ld_poll4(p);
  int it = 0;
  while (!ready4(v) && ++it < SPIN_LIMIT) v = ld_poll4(p);
  return make_uint4(~v.x, ~v.y, ~v.z, ~v.w);
}
__device__ __forceinline__ void st_pub4(uint4* p, uint4 v) {
  asm volatile("st.relaxed.gpu.global.v4.u32 [%0], {%1,%2,%3,%4};" ::"l"(p), "r"(v.x), "r"(v.y), "r"(v.z), "r"(v.w) : "memory");
}
__device__ __forceinline__ void st_pub2(uint2* p, uint32_t a, uint32_t b) {
  asm volatile("st.relaxed.gpu.global.v2.u32 [%0], {%1,%2};" ::"l"(p), "r"(a), "r"(b) : "memory");
}
__device__ __forceinline__ void mma_bf16(float (&c)[4], uint32_t a0, uint32_t a2, uint32_t b0, uint32_t b1) {
  asm volatile("mma.sync.aligned.m16n8k16.row.col.f32.bf16.bf16.f32 {%0,%1,%2,%3}, {%4,%5,%6,%5}, {%7,%8}, {%0,%1,%2,%3};"
               : "+f"(c[0]), "+f"(c[1]), "+f"(c[2]), "+f"(c[3]) : "r"(a0), "r"(0u), "r"(a2), "r"(b0), "r"(b1));
}
__device__ __forceinline__ void mbar_wait(const unsigned long long* bar) {
  const uint32_t mb = smem_u32(bar);
  uint32_t ok = 0;
  int it = 0;
  while (!ok && ++it < SPIN_LIMIT)
    asm volatile("{ .reg .pred p; mbarrier.try_wait.parity.shared.b64 p, [%1], 0; selp.u32 %0, 1, 0, p; }" : "=r"(ok) : "r"(mb) : "memory");
}
__device__ __forceinline__ void bulk_g2s(void* dst, const void* src, uint32_t bytes, const unsigned long long* bar) {
  asm volatile("cp.async.bulk.shared::cluster.global.mbarrier::complete_tx::bytes [%0], [%1], %2, [%3];" ::"r"(smem_u32(dst)),
               "l"(src), "r"(bytes), "r"(smem_u32(bar)) : "memory");
}
__device__ __forceinline__ void mbar_expect(const unsigned long long* bar, uint32_t bytes) {
  asm volatile("mbarrier.arrive.expect_tx.shared.b64 _, [%0], %1;" ::"r"(smem_u32(bar)), "r"(bytes) : "memory");
}
__device__ __forceinline__ void mma_bf16x(float (&c)[4], uint32_t a0, uint32_t a1, uint32_t a2, uint32_t a3, uint32_t b0, uint32_t b1) {
  asm volatile("mma.sync.aligned.m16n8k16.row.col.f32.bf16.bf16.f32 {%0,%1,%2,%3}, {%4,%5,%6,%7}, {%8,%9}, {%0,%1,%2,%3};"
               : "+f"(c[0]), "+f"(c[1]), "+f"(c[2]), "+f"(c[3]) : "r"(a0), "r"(a1), "r"(a2), "r"(a3), "r"(b0), "r"(b1));
}
__device__ __forceinline__ float fdivr(float a, float d, float r) {
  float q = a * r;
  float e = fmaf(-q, d, a);
  return fmaf(e, r, q);
}

template <bool FIRST> __device__ __forceinline__ void wgmma32(float (&d)[16], const uint32_t* a, uint64_t desc) {
  if (FIRST) {
    asm volatile("wgmma.mma_async.sync.aligned.m64n32k16.f32.bf16.bf16 {%0,%1,%2,%3,%4,%5,%6,%7,%8,%9,%10,%11,%12,%13,%14,%15}, {%16,%17,%18,%19}, %20, 0, 1, 1, 0;"
                 : "+f"(d[0]), "+f"(d[1]), "+f"(d[2]), "+f"(d[3]), "+f"(d[4]), "+f"(d[5]), "+f"(d[6]), "+f"(d[7]),
                   "+f"(d[8]), "+f"(d[9]), "+f"(d[10]), "+f"(d[11]), "+f"(d[12]), "+f"(d[13]), "+f"(d[14]), "+f"(d[15])
                 : "r"(a[0]), "r"(a[1]), "r"(a[2]), "r"(a[3]), "l"(desc));
  } else {
    asm volatile("wgmma.mma_async.sync.aligned.m64n32k16.f32.bf16.bf16 {%0,%1,%2,%3,%4,%5,%6,%7,%8,%9,%10,%11,%12,%13,%14,%15}, {%16,%17,%18,%19}, %20, 1, 1, 1, 0;"
                 : "+f"(d[0]), "+f"(d[1]), "+f"(d[2]), "+f"(d[3]), "+f"(d[4]), "+f"(d[5]), "+f"(d[6]), "+f"(d[7]),
                   "+f"(d[8]), "+f"(d[9]), "+f"(d[10]), "+f"(d[11]), "+f"(d[12]), "+f"(d[13]), "+f"(d[14]), "+f"(d[15])
                 : "r"(a[0]), "r"(a[1]), "r"(a[2]), "r"(a[3]), "l"(desc));
  }
}

template <int G> __device__ __forceinline__ void load_a(uint32_t (&a)[8], const uint32_t* tp) {
#pragma unroll
  for (int q = 0; q < 2; q++) {
    const int e = 2 * G + q;
    a[4 * q + 0] = tp[-64 * e];
    a[4 * q + 1] = tp[-64 * e - 32];
    a[4 * q + 2] = tp[-64 * e + 4];
    a[4 * q + 3] = tp[-64 * e - 28];
  }
}
__device__ __forceinline__ void load_a_all(uint32_t (&a)[8][8], const uint32_t* tp) {
  load_a<0>(a[0], tp); load_a<1>(a[1], tp); load_a<2>(a[2], tp); load_a<3>(a[3], tp);
  load_a<4>(a[4], tp); load_a<5>(a[5], tp); load_a<6>(a[6], tp); load_a<7>(a[7], tp);
}
template <int G> __device__ __forceinline__ void issue_g(float (&acc)[8][16], uint32_t (&a)[8], uint64_t desc0) {
  wg_fence();
#pragma unroll
  for (int q = 0; q < 2; q++) {
#pragma unroll
    for (int b = G; b < 8; b++) {
      const int delta = 2 * b - (2 * G + q);
      if (G == 0 && q == 0) wgmma32<true>(acc[b], &a[4 * q], desc0 + (uint64_t)(int64_t)(16 * delta));
      else wgmma32<false>(acc[b], &a[4 * q], desc0 + (uint64_t)(int64_t)(16 * delta));
    }
  }
  wg_commit();
}
template <int B> __device__ __forceinline__ void fence_blk(float (&acc)[8][16]) {
#pragma unroll
  for (int i = 0; i < 16; i++) asm volatile("" : "+f"(acc[B][i])::"memory");
}
__device__ __forceinline__ void fence_a(uint32_t (&a)[8]) {
#pragma unroll
  for (int i = 0; i < 8; i++) asm volatile("" : "+r"(a[i])::"memory");
}
template <int B> __device__ __forceinline__ void sts_blk(float (&acc)[8][16], float* zw, int off_even, int off_odd) {
#pragma unroll
  for (int jj = 0; jj < 4; jj++) {
    const int j = 4 * B + jj;
    float p0 = acc[B][4 * jj + 0], p1 = acc[B][4 * jj + 1];
    if (jj > 0) { p0 += acc[B][4 * (jj - 1) + 2]; p1 += acc[B][4 * (jj - 1) + 3]; }
    else if (B > 0) { p0 += acc[B > 0 ? B - 1 : 0][14]; p1 += acc[B > 0 ? B - 1 : 0][15]; }
    zw[64 * j + off_even] = p0;
    zw[64 * j + off_odd] = p1;
  }
}
__device__ __forceinline__ int tab_off(int c) { return c == 4 ? 0 : (c + 1) * 2 * TABW + (c >= 2 ? 1024 : 0); }
__device__ __forceinline__ int tile_perm(int ch) { return ch ^ (((ch >> 3) & 3) << 1); }

__device__ __forceinline__ void wait_ctr(const unsigned int* ctr, uint32_t target) {
  uint32_t v;
  int it = 0;
  do {
    asm volatile("ld.acquire.gpu.global.u32 %0, [%1];" : "=r"(v) : "l"(ctr) : "memory");
  } while ((int)(v - target) < 0 && ++it < SPIN_LIMIT);
}

__device__ __forceinline__ float2 row_part_stats(const uint32_t (&x)[20]) {
  float cs[5][4];
#pragma unroll
  for (int k = 0; k < 5; k++) {
    cs[k][0] = cs[k][1] = cs[k][2] = cs[k][3] = 0.f;
    mma_bf16x(cs[k], x[4 * k + 0], x[4 * k + 2], x[4 * k + 1], x[4 * k + 3], 0x3F803F80u, 0x3F803F80u);
  }
  const float mean = ((((cs[0][0] + cs[0][2]) + (cs[1][0] + cs[1][2])) + ((cs[2][0] + cs[2][2]) + (cs[3][0] + cs[3][2]))) + (cs[4][0] + cs[4][2])) * (1.f / 160.f);
  float m2a = 0.f, m2b = 0.f, m2c = 0.f, m2d = 0.f;
#pragma unroll
  for (int i = 0; i < 20; i += 2) {
    const float a = lo_f(x[i]) - mean, b = hi_f(x[i]) - mean, c = lo_f(x[i + 1]) - mean, d = hi_f(x[i + 1]) - mean;
    m2a = fmaf(a, a, m2a); m2b = fmaf(b, b, m2b); m2c = fmaf(c, c, m2c); m2d = fmaf(d, d, m2d);
  }
  float m2 = (m2a + m2b) + (m2c + m2d);
  m2 += __shfl_xor_sync(0xffffffffu, m2, 1);
  m2 += __shfl_xor_sync(0xffffffffu, m2, 2);
  return make_float2(mean, m2);
}
template <bool EXACT> __device__ __forceinline__ void row_normalize(const float4* st, const uint32_t (&x)[20], uint32_t (&y)[20]) {
  const float4 p = st[0], q = st[1];
  const float mean = ((p.x + p.z) + (q.x + q.z)) * 0.25f;
  const float d0 = p.x - mean, d1 = p.z - mean, d2 = q.x - mean, d3 = q.z - mean;
  const float m2 = ((p.y + p.w) + (q.y + q.w)) + 160.f * ((d0 * d0 + d1 * d1) + (d2 * d2 + d3 * d3));
  const float hd = rbf(sqrtf(rbf(rbf(m2 * (1.f / D_)) + 1e-5f)));
  const float hr = __frcp_rn(hd);
  const bf162 hm2 = __float2bfloat162_rn(mean);
#pragma unroll
  for (int i = 0; i < 20; i++) {
    const uint32_t d = b2u(__hsub2_rn(u2b(x[i]), hm2));
    y[i] = EXACT ? pack2(fdivr(lo_f(d), hd, hr), fdivr(hi_f(d), hd, hr)) : pack2(lo_f(d) * hr, hi_f(d) * hr);
  }
}

__device__ __forceinline__ void gather_kv(Smem& sm, int c0, int tid) {
  mbar_wait(&sm.mbarc);
  uint4 v[4];
  uint4* src = g_kv + c0 * 256 + tid;
#pragma unroll
  for (int i = 0; i < 4; i++) if (i < 3 || tid >= 256) v[i] = ld_poll4(src + NTHR * i - (i == 3 ? 256 : 0));
#pragma unroll
  for (int i = 0; i < 4; i++) {
    if (i < 3 || tid >= 256) {
      const int t = tid + NTHR * i - (i == 3 ? 256 : 0);
      int it = 0;
      while (!ready4(v[i]) && ++it < SPIN_LIMIT) { __nanosleep(POLL_NS); v[i] = ld_poll4(g_kv + c0 * 256 + t); }
      *reinterpret_cast<uint4*>(&sm.u[t >> 8][UPAD + (t & 255) * 8]) = make_uint4(~v[i].x, ~v[i].y, ~v[i].z, ~v[i].w);
    }
  }
  asm volatile("fence.proxy.async.shared::cta;" ::: "memory");
  __syncthreads();
}

__global__ void __launch_bounds__(NTHR, 1)
fused_kernel(const __grid_constant__ CUtensorMap tmg, const __grid_constant__ CUtensorMap tmu,
             const __grid_constant__ CUtensorMap tmd, const bf16* __restrict__ gq, const bf16* __restrict__ gk, const bf16* __restrict__ gv,
             const bf16* __restrict__ gsk, const bf16* __restrict__ gh, const bf16* __restrict__ gD,
             const bf16* __restrict__ gwr, bf16* __restrict__ gout) {
  extern __shared__ __align__(128) unsigned char smraw[];
  Smem& sm = *reinterpret_cast<Smem*>(smraw);
  const int tid = threadIdx.x;
  const int cta = blockIdx.x;
  const int c0 = cta * CPC;
  const int lane = tid & 31;
  const int wid = tid >> 5;

  {
    uint4* hs = reinterpret_cast<uint4*>(&sm.z[0][0][0]);
    const int oc = tid >> 2;
    const int r0 = cta * 16 + (tid & 3) * 4;
    uint4 kk[7], vv[4], sk[4];
    if (tid < 320) {
      const uint4* kp = reinterpret_cast<const uint4*>(gk) + (size_t)r0 * 80 + oc;
      const uint4* vp = reinterpret_cast<const uint4*>(gv) + (size_t)r0 * 80 + oc;
#pragma unroll
      for (int i = 0; i < 7; i++) kk[i] = (i >= 3 || r0 > 0) ? __ldg(kp + (i - 3) * 80) : make_uint4(0, 0, 0, 0);
#pragma unroll
      for (int i = 0; i < 4; i++) vv[i] = __ldg(vp + i * 80);
#pragma unroll
      for (int i = 0; i < 4; i++) sk[i] = __ldg(reinterpret_cast<const uint4*>(gsk) + oc * 4 + i);
    } else if (tid == 320) {
      asm volatile("mbarrier.init.shared.b64 [%0], 1;" ::"r"(smem_u32(&sm.mbarh)) : "memory");
      asm volatile("mbarrier.init.shared.b64 [%0], 1;" ::"r"(smem_u32(&sm.mbar)) : "memory");
      asm volatile("mbarrier.init.shared.b64 [%0], 1;" ::"r"(smem_u32(&sm.mbarw)) : "memory");
      asm volatile("mbarrier.init.shared.b64 [%0], 1;" ::"r"(smem_u32(&sm.mbarc)) : "memory");
      asm volatile("mbarrier.init.shared.b64 [%0], 1;" ::"r"(smem_u32(&sm.mbary)) : "memory");
      asm volatile("fence.proxy.async.shared::cta;" ::: "memory");
    } else if (tid == 352) {
      uint32_t v1, v2, v3;
      asm volatile("ld.relaxed.gpu.global.u32 %0, [%1];" : "=r"(v1) : "l"(&g_ctr) : "memory");
      asm volatile("ld.relaxed.gpu.global.u32 %0, [%1];" : "=r"(v2) : "l"(&g_ctr2) : "memory");
      asm volatile("ld.relaxed.gpu.global.u32 %0, [%1];" : "=r"(v3) : "l"(&g_ctr3) : "memory");
      sm.target = (v1 / NCTA + 1u) * NCTA;
      sm.target2 = (v2 / NCTA + 1u) * NCTA;
      sm.target3 = (v3 / NCTA + 1u) * NCTA;
    }
    if (tid < 320) bar_sync(6, 384); else { bar_arrive(6, 384); bar_sync(5, 64); }
    if (tid < 320) {
      uint32_t o[4][4];
#pragma unroll
      for (int p = 0; p < 4; p++) {
        const bf162 w0 = u2b(__byte_perm(sk[p].x, sk[p].z, 0x5410)), w1 = u2b(__byte_perm(sk[p].x, sk[p].z, 0x7632));
        const bf162 w2 = u2b(__byte_perm(sk[p].y, sk[p].w, 0x5410)), w3 = u2b(__byte_perm(sk[p].y, sk[p].w, 0x7632));
        uint32_t kv[4];
#pragma unroll
        for (int i = 0; i < 4; i++) {
          const uint32_t k0 = p == 0 ? kk[i].x : p == 1 ? kk[i].y : p == 2 ? kk[i].z : kk[i].w;
          const uint32_t k1 = p == 0 ? kk[i + 1].x : p == 1 ? kk[i + 1].y : p == 2 ? kk[i + 1].z : kk[i + 1].w;
          const uint32_t k2 = p == 0 ? kk[i + 2].x : p == 1 ? kk[i + 2].y : p == 2 ? kk[i + 2].z : kk[i + 2].w;
          const uint32_t k3 = p == 0 ? kk[i + 3].x : p == 1 ? kk[i + 3].y : p == 2 ? kk[i + 3].z : kk[i + 3].w;
          const uint32_t vx = p == 0 ? vv[i].x : p == 1 ? vv[i].y : p == 2 ? vv[i].z : vv[i].w;
          bf162 a = __hmul2_rn(u2b(k0), w3);
          a = __hadd2_rn(a, __hmul2_rn(u2b(k1), w2));
          a = __hadd2_rn(a, __hmul2_rn(u2b(k2), w1));
          a = __hadd2_rn(a, __hmul2_rn(u2b(k3), w0));
          kv[i] = b2u(__hmul2_rn(a, u2b(vx)));
        }
        o[p][0] = enc(__byte_perm(kv[0], kv[1], 0x5410)); o[p][1] = enc(__byte_perm(kv[2], kv[3], 0x5410));
        o[p][2] = enc(__byte_perm(kv[0], kv[1], 0x7632)); o[p][3] = enc(__byte_perm(kv[2], kv[3], 0x7632));
      }
      uint2* dst = reinterpret_cast<uint2*>(g_kv) + (size_t)(oc * 8) * 512 + (r0 >> 2);
#pragma unroll
      for (int p = 0; p < 4; p++) {
        st_pub2(dst + (2 * p) * 512, o[p][0], o[p][1]);
        st_pub2(dst + (2 * p + 1) * 512, o[p][2], o[p][3]);
      }
      if (wid == 0) bar_sync(4, 320); else bar_arrive(4, 320);
      if (tid == 0) {
        asm volatile("red.relaxed.gpu.global.add.u32 [%0], 1;" ::"l"(&g_ctr2) : "memory");
      }
      __syncwarp();
    } else {
      const int t0 = tid - 320;
      const uint4 zz = make_uint4(0, 0, 0, 0);
      if (tid == 320) {
        mbar_expect(&sm.mbarh, CPC * S_ * 2);
        bulk_g2s(hs, gh + (size_t)c0 * S_, CPC * S_ * 2, &sm.mbarh);
      }
      __syncwarp();
      for (int t = t0; t < CPC * 17; t += 64) *reinterpret_cast<uint4*>(&sm.u[t / 17][(t % 17) * 8]) = zz;
      if (t0 < 40) *reinterpret_cast<uint4*>(&sm.tabA[0][0][0] + tab_off(t0 >> 3) + ((t0 >> 2) & 1) * TABW + 1024 + 4 * (t0 & 3)) = zz;
      (&g_cand[cta][0][0])[t0] = zz;
      (&g_cand[cta][0][0])[64 + t0] = zz;
      if (t0 < 32) (&g_cand[cta][0][0])[128 + t0] = zz;
      else reinterpret_cast<uint4*>(&g_keys[cta][0])[t0 - 32] = zz;
      if (cta >= N1 && cta < N1 + N2) {
#pragma unroll
        for (int i = 0; i < 3; i++) g_act[cta - N1][t0 + 64 * i] = zz;
      }
    }
    mbar_wait(&sm.mbarh);
#pragma unroll
    for (int i = 0; i < 4; i++) {
      const int t = (NTHR - 1 - tid) + NTHR * i;
      if (t < CPC * 256) {
        uint32_t* tb = &sm.tabA[0][0][0] + tab_off(t >> 8) + (255 - (t & 255)) * 4;
        const uint4 h = hs[t];
        const uint32_t hp = (t & 255) ? reinterpret_cast<const uint32_t*>(hs)[4 * t - 1] : 0u;
        uint4 r1, rr;
        r1.x = __byte_perm(h.w, 0, 0x1032); r1.y = __byte_perm(h.z, 0, 0x1032);
        r1.z = __byte_perm(h.y, 0, 0x1032); r1.w = __byte_perm(h.x, 0, 0x1032);
        rr.x = __byte_perm(h.w, h.z, 0x7610); rr.y = __byte_perm(h.z, h.y, 0x7610);
        rr.z = __byte_perm(h.y, h.x, 0x7610); rr.w = __byte_perm(h.x, hp, 0x7610);
        *reinterpret_cast<uint4*>(tb) = rr;
        *reinterpret_cast<uint4*>(tb + TABW) = r1;
      }
    }
  }
  __syncthreads();

  const int wg = __shfl_sync(0xffffffffu, tid >> 7, 0);
  const int wtid = tid & 127;
  uint4* tile = reinterpret_cast<uint4*>(&sm.tabB[0][0][0]);
  if (wg < 2) {
    asm volatile("setmaxnreg.inc.sync.aligned.u32 224;");
    const int w = (tid >> 5) & 3, g = lane >> 2, tq = lane & 3;
    float* zw = sm.z[wg][w];
    const int sw = 3 * (((tq + w) >> 1) & 1);
    const int off_even = 16 * (tq + w) + 4 * ((0 + (g >> 2)) ^ sw) + (g & 3);
    const int off_odd = 16 * (tq + w) + 4 * ((2 + (g >> 2)) ^ sw) + (g & 3);
    uint32_t a[8][8];
    const uint32_t* tp0 = &sm.tabA[0][g & 1][1019 - 8 * w - (g >> 1) + tq];
    load_a_all(a, tp0 + tab_off(wg));
    float acc[8][16];
#pragma unroll
    for (int b = 0; b < 8; b++)
#pragma unroll
      for (int i = 0; i < 16; i++) acc[b][i] = 0.f;
    gather_kv(sm, c0, tid);
#pragma unroll 1
    for (int c = wg; c < CPC; c += 2) {
      const uint64_t desc = (uint64_t)((smem_u32(&sm.u[c][UPAD - 8]) & 0x3FFFF) >> 4) | ((uint64_t)1 << 16) | ((uint64_t)8 << 32);
      if (c > 0) bar_sync(1 + wg, 256);
      issue_g<0>(acc, a[0], desc);
      issue_g<1>(acc, a[1], desc);
      issue_g<2>(acc, a[2], desc);
      issue_g<3>(acc, a[3], desc);
      issue_g<4>(acc, a[4], desc);
      issue_g<5>(acc, a[5], desc);
      if (c + 1 < CPC) bar_arrive(1 + (wg ^ 1), 256);
      issue_g<6>(acc, a[6], desc);
      issue_g<7>(acc, a[7], desc);
      if (c >= 2) bar_sync(5 + wg, 256);
      wg_wait<4>();
      fence_blk<0>(acc); fence_blk<1>(acc); fence_blk<2>(acc); fence_blk<3>(acc);
      sts_blk<0>(acc, zw, off_even, off_odd);
      sts_blk<1>(acc, zw, off_even, off_odd);
      sts_blk<2>(acc, zw, off_even, off_odd);
      sts_blk<3>(acc, zw, off_even, off_odd);
      bar_arrive(9 + wg, 256);
      wg_wait<0>();
      fence_blk<4>(acc); fence_blk<5>(acc); fence_blk<6>(acc); fence_blk<7>(acc);
#pragma unroll
      for (int i = 0; i < 8; i++) fence_a(a[i]);
      sts_blk<4>(acc, zw, off_even, off_odd);
      sts_blk<5>(acc, zw, off_even, off_odd);
      sts_blk<6>(acc, zw, off_even, off_odd);
      sts_blk<7>(acc, zw, off_even, off_odd);
      bar_arrive(3 + wg, 256);
      if (c + 2 < CPC) load_a_all(a, tp0 + tab_off(c + 2));
    }
    asm volatile("setmaxnreg.dec.sync.aligned.u32 168;");
  } else {
    asm volatile("setmaxnreg.dec.sync.aligned.u32 56;");
    if (((wtid & 15) >> 2) < ((wtid >> 4) & 3))
      *reinterpret_cast<uint4*>(&sm.z[wtid >> 6][(wtid >> 4) & 3][(wtid & 15) * 4]) = make_uint4(0, 0, 0, 0);
    if (wtid == 96) {
      __threadfence();
      asm volatile("red.relaxed.gpu.global.add.u32 [%0], 1;" ::"l"(&g_ctr) : "memory");
    }
    if (wtid == 64) {
      const unsigned target = sm.target2;
      uint32_t v;
      int it = 0;
      do {
        asm volatile("ld.relaxed.gpu.global.u32 %0, [%1];" : "=r"(v) : "l"(&g_ctr2) : "memory");
      } while ((int)(v - target) < 0 && ++it < SPIN_LIMIT);
      asm volatile("mbarrier.arrive.shared.b64 _, [%0];" ::"r"(smem_u32(&sm.mbarc)) : "memory");
    }
    __syncwarp();
    gather_kv(sm, c0, tid);
#pragma unroll
    for (int i = 0; i < 10; i++) g_kv[c0 * 256 + wtid + 128 * i] = make_uint4(0, 0, 0, 0);
    if (wtid == 96) wait_ctr(&g_ctr, sm.target);
    __syncwarp();
    if (wtid == 32) {
      const uint32_t mw = smem_u32(&sm.mbarw);
      mbar_expect(&sm.mbar, 17 * D_ * 2);
#pragma unroll 1
      for (int r = 0; r < 16; r++) bulk_g2s(&sm.q[r][0], gq + (size_t)(cta * 16 + r) * D_, D_ * 2, &sm.mbar);
      bulk_g2s(&sm.wr[0], gwr, D_ * 2, &sm.mbar);
      if (cta < N1) {
        asm volatile("mbarrier.arrive.expect_tx.shared.b64 _, [%0], %1;" ::"r"(mw), "r"(3840 * 16) : "memory");
#pragma unroll 1
        for (int i = 0; i < 4; i++) {
          asm volatile("cp.async.bulk.tensor.2d.shared::cluster.global.mbarrier::complete_tx::bytes [%0], [%1, {%3, %4}], [%2];" ::"r"(smem_u32(&sm.w[i * 480])),
                       "l"(&tmg), "r"(mw), "r"(cta * 24), "r"(i * 160) : "memory");
          asm volatile("cp.async.bulk.tensor.2d.shared::cluster.global.mbarrier::complete_tx::bytes [%0], [%1, {%3, %4}], [%2];" ::"r"(smem_u32(&sm.w[1920 + i * 480])),
                       "l"(&tmu), "r"(mw), "r"(cta * 24), "r"(i * 160) : "memory");
        }
      } else if (cta < N1 + N2) {
        asm volatile("mbarrier.arrive.expect_tx.shared.b64 _, [%0], %1;" ::"r"(mw), "r"(3072 * 16) : "memory");
#pragma unroll 1
        for (int i = 0; i < 6; i++)
          asm volatile("cp.async.bulk.tensor.2d.shared::cluster.global.mbarrier::complete_tx::bytes [%0], [%1, {%3, %4}], [%2];" ::"r"(smem_u32(&sm.w[i * 512])),
                       "l"(&tmd), "r"(mw), "r"((cta - N1) * 16), "r"(i * 256) : "memory");
      }
    }
    const int rpb = wtid >> 1, re2 = wtid & 1;
    const int rsw = 3 * ((rpb >> 1) & 1);
    const int roff0 = 16 * rpb + 4 * ((2 * re2 + 0) ^ rsw);
    const int roff1 = 16 * rpb + 4 * ((2 * re2 + 1) ^ rsw);
    const uint32_t dvl = reinterpret_cast<const unsigned short*>(gD)[c0 + (lane < CPC ? lane : 0)];
#pragma unroll 1
    for (int c = 0; c < CPC; c++) {
      const int zg = c & 1;
      const uint32_t dvc = __shfl_sync(0xffffffffu, dvl, c);
      const bf162 d2 = u2b(dvc | (dvc << 16));
#pragma unroll
      for (int half = 0; half < 2; half++) {
        bar_sync((half ? 3 : 9) + zg, 256);
        const float* zb = sm.z[zg][0] + half * 1024;
        float4 x[4][2];
#pragma unroll
        for (int ww = 0; ww < 4; ww++) {
          x[ww][0] = *reinterpret_cast<const float4*>(zb + ww * ZPB * 16 + roff0);
          x[ww][1] = *reinterpret_cast<const float4*>(zb + ww * ZPB * 16 + roff1);
        }
        const int sidx = half * 1024 + wtid * 8;
        const uint4 kvv = *reinterpret_cast<const uint4*>(&sm.u[c][UPAD + sidx]);
        if (half == 1 && c + 2 < CPC) bar_arrive(5 + zg, 256);
        uint4 o;
        o.x = pack2((x[0][0].x + x[1][0].x) + (x[2][0].x + x[3][0].x), (x[0][0].y + x[1][0].y) + (x[2][0].y + x[3][0].y));
        o.y = pack2((x[0][0].z + x[1][0].z) + (x[2][0].z + x[3][0].z), (x[0][0].w + x[1][0].w) + (x[2][0].w + x[3][0].w));
        o.z = pack2((x[0][1].x + x[1][1].x) + (x[2][1].x + x[3][1].x), (x[0][1].y + x[1][1].y) + (x[2][1].y + x[3][1].y));
        o.w = pack2((x[0][1].z + x[1][1].z) + (x[2][1].z + x[3][1].z), (x[0][1].w + x[1][1].w) + (x[2][1].w + x[3][1].w));
        o.x = b2u(__hadd2_rn(u2b(o.x), __hmul2_rn(u2b(kvv.x), d2)));
        o.y = b2u(__hadd2_rn(u2b(o.y), __hmul2_rn(u2b(kvv.y), d2)));
        o.z = b2u(__hadd2_rn(u2b(o.z), __hmul2_rn(u2b(kvv.z), d2)));
        o.w = b2u(__hadd2_rn(u2b(o.w), __hmul2_rn(u2b(kvv.w), d2)));
        st_pub4(g_y2 + ((64 * half + rpb) * 640 + c0 + c) * 2 + re2, enc4(o));
      }
    }
    if (wid == 11) bar_sync(8, 128); else bar_arrive(8, 128);
    asm volatile("setmaxnreg.inc.sync.aligned.u32 168;");
  }

  if (tid == 352) {
    asm volatile("red.relaxed.gpu.global.add.u32 [%0], 1;" ::"l"(&g_ctr3) : "memory");
    wait_ctr(&g_ctr3, sm.target3);
    asm volatile("mbarrier.arrive.shared.b64 _, [%0];" ::"r"(smem_u32(&sm.mbary)) : "memory");
  }
  __syncwarp();
  const int g = lane >> 2, tq = lane & 3;
  const int hh = wid & 1, gqi = wid >> 1;
  const int row = hh * 8 + g;
  uint32_t hreg[20], hnreg[20];
  {
    const uint4* src = g_y2 + cta * 1280 + (160 * gqi + lane) * 2 + hh;
    uint4 v[5];
    if (wid < 8) {
      mbar_wait(&sm.mbar);
#pragma unroll
      for (int k = 0; k < 5; k++) {
        const uint4 qv4 = *reinterpret_cast<const uint4*>(&sm.q[row][32 * (5 * gqi + k) + 8 * tq]);
        hreg[4 * k] = qv4.x; hreg[4 * k + 1] = qv4.y; hreg[4 * k + 2] = qv4.z; hreg[4 * k + 3] = qv4.w;
      }
      const float2 ps = row_part_stats(hreg);
      if (tq == 0) sm.stq[row][gqi] = ps;
      bar_sync(11 + hh, 128);
      row_normalize<false>(reinterpret_cast<const float4*>(sm.stq[row]), hreg, hnreg);
    }
    if (wid < 8) {
      mbar_wait(&sm.mbary);
#pragma unroll
      for (int i = 0; i < 5; i++) v[i] = ld_poll4(src + 64 * i);
      int it = 0;
      bool all;
      do {
        all = true;
#pragma unroll
        for (int i = 0; i < 5; i++)
          if (!ready4(v[i])) { v[i] = ld_poll4(src + 64 * i); all = false; }
      } while (!all && ++it < SPIN_LIMIT);
#pragma unroll
      for (int i = 0; i < 5; i++)
        tile[hh * 640 + tile_perm(160 * gqi + 32 * i + lane)] = make_uint4(~v[i].x, ~v[i].y, ~v[i].z, ~v[i].w);
      __syncwarp();
    }
  }

  if (wid < 8) {
#pragma unroll
    for (int k = 0; k < 5; k++) {
      const int base = 32 * (5 * gqi + k);
      const int lch = base + 8 * ((lane & 7) >> 1) + 2 * (lane >> 3) + (lane & 1);
      uint32_t y[4];
      asm volatile("ldmatrix.sync.aligned.m8n8.x4.trans.shared.b16 {%0,%1,%2,%3}, [%4];"
                   : "=r"(y[0]), "=r"(y[1]), "=r"(y[2]), "=r"(y[3]) : "r"(smem_u32(&tile[hh * 640 + tile_perm(lch)])) : "memory");
#pragma unroll
      for (int i = 0; i < 4; i++)
        hreg[4 * k + i] = b2u(__hadd2_rn(u2b(hreg[4 * k + i]), __hmul2_rn(u2b(hnreg[4 * k + i]), u2b(y[i]))));
    }
    const float2 ps = row_part_stats(hreg);
    if (tq == 0) sm.st[row][gqi] = ps;
    bar_sync(11 + hh, 128);
    row_normalize<false>(reinterpret_cast<const float4*>(sm.st[row]), hreg, hnreg);
    float cr[5][4];
#pragma unroll
    for (int k = 0; k < 5; k++) {
      cr[k][0] = cr[k][1] = cr[k][2] = cr[k][3] = 0.f;
      const uint4 w4 = sm.wr[4 * (5 * gqi + k) + tq];
      mma_bf16(cr[k], hnreg[4 * k + 0], hnreg[4 * k + 1], w4.x, w4.y);
      mma_bf16(cr[k], hnreg[4 * k + 2], hnreg[4 * k + 3], w4.z, w4.w);
    }
    if (tq == 0) sm.rp[row][gqi] = ((cr[0][0] + cr[1][0]) + (cr[2][0] + cr[3][0])) + cr[4][0];
  }
  __syncthreads();
  uint32_t best;
  {
    const int rr = lane & 15;
    const float4 rp4 = *reinterpret_cast<const float4*>(sm.rp[rr]);
    const float r = (rp4.x + rp4.y) + (rp4.z + rp4.w);
    const uint32_t bits = __bfloat16_as_ushort(__float2bfloat16_rn(r));
    const uint32_t ord = (bits & 0x8000u) ? (bits ^ 0xFFFFu) : (bits ^ 0x8000u);
    const uint32_t key = (ord << 16) | 0x8000u | (uint32_t)(2047 - (cta * 16 + rr));
    best = __reduce_max_sync(0xffffffffu, key);
  }
  if (wid >= 8) asm volatile("st.relaxed.gpu.global.u32 [%0], %1;" ::"l"(&g_keys[tid - 256][cta]), "r"(best) : "memory");
  const int brow = (2047 - (int)(best & 0x7FFu)) - cta * 16;
  if (wid < 8 && row == brow) {
#pragma unroll
    for (int k = 0; k < 5; k++)
      st_pub4(&g_cand[cta][0][4 * (5 * gqi + k) + tq], enc4(make_uint4(hnreg[4 * k], hnreg[4 * k + 1], hnreg[4 * k + 2], hnreg[4 * k + 3])));
#pragma unroll
    for (int k = 0; k < 5; k++)
      st_pub4(&g_cand[cta][1][4 * (5 * gqi + k) + tq], enc4(make_uint4(hreg[4 * k], hreg[4 * k + 1], hreg[4 * k + 2], hreg[4 * k + 3])));
  }
#pragma unroll
  for (int i = 0; i < 20; i++) hreg[i] = b2u(__hadd2_rn(u2b(hreg[i]), u2b(hnreg[i])));
  float wf[10][8];
  const int rs = cta < N1 ? (wid & 1) * 32 + lane : wid * 16 + (lane >> 1);
  if (cta < N1 + N2) {
    mbar_wait(&sm.mbarw);
    const uint4* wp = cta < N1 ? &sm.w[(wid / 6) * 1920 + rs * 3 + ((wid % 6) >> 1)] : &sm.w[rs * 2 + (lane & 1)];
    const int wstep = cta < N1 ? 192 : 384;
#pragma unroll
    for (int it = 0; it < 10; it++) {
      const uint4 wv = wp[(it < 8 || cta < N1) ? it * wstep : 0];
      wf[it][0] = lo_f(wv.x); wf[it][1] = hi_f(wv.x); wf[it][2] = lo_f(wv.y); wf[it][3] = hi_f(wv.y);
      wf[it][4] = lo_f(wv.z); wf[it][5] = hi_f(wv.z); wf[it][6] = lo_f(wv.w); wf[it][7] = hi_f(wv.w);
    }
#pragma unroll
    for (int it = 0; it < 10; it++)
#pragma unroll
      for (int j = 0; j < 8; j++) asm volatile("" : "+f"(wf[it][j]));
  }
  if (wid == 11) {
    const uint4* kp = reinterpret_cast<const uint4*>(&g_keys[cta][0]) + lane;
    uint4 v = ld_poll4(kp);
    int it = 0;
    while (!ready4(v) && ++it < SPIN_LIMIT) v = ld_poll4(kp);
    const uint32_t m = max(max(v.x, v.y), max(v.z, v.w));
    const uint32_t wk = __reduce_max_sync(0xffffffffu, m);
    if (lane == 0) sm.win = wk;
  }
  __syncthreads();
  const uint32_t win = sm.win;
  const int wrow = 2047 - (int)(win & 0x7FFu);
  const int wcta = wrow >> 4;
  const bool st_out = wid < 8 && (cta * 16 + row) != wrow;
  uint4* outp = reinterpret_cast<uint4*>(gout + (size_t)(cta * 16 + row) * D_) + 20 * gqi + tq;
  if (cta >= N1) {
    if (st_out) {
#pragma unroll
      for (int k = 0; k < 5; k++) outp[4 * k] = make_uint4(hreg[4 * k], hreg[4 * k + 1], hreg[4 * k + 2], hreg[4 * k + 3]);
    }
  }
  if (cta >= N1) {
#pragma unroll
    for (int i = 0; i < 4; i++) if (i < 3 || tid < 128) g_y2[cta * 1280 + tid + NTHR * i] = make_uint4(0, 0, 0, 0);
  }
  float* xs = &sm.z[0][0][0];
  float* part = xs + 2048;
  if (cta < N1) {
    if (tid < 80) {
      const uint4 v = poll4(&g_cand[wcta][0][tid]);
      float4* xp = reinterpret_cast<float4*>(xs + tid * 8);
      xp[0] = make_float4(lo_f(v.x), hi_f(v.x), lo_f(v.y), hi_f(v.y));
      xp[1] = make_float4(lo_f(v.z), hi_f(v.z), lo_f(v.w), hi_f(v.w));
    }
    __syncthreads();
    float a[8];
#pragma unroll
    for (int j = 0; j < 8; j++) a[j] = 0.f;
#pragma unroll
    for (int it = 0; it < 10; it++) {
      const float x = xs[rs + 64 * it];
#pragma unroll
      for (int j = 0; j < 8; j++) a[j] = fmaf(x, wf[it][j], a[j]);
    }
    {
      const bool up = lane & 16;
#pragma unroll
      for (int j = 0; j < 4; j++) {
        const float send = up ? a[j] : a[j + 4], keep = up ? a[j + 4] : a[j];
        a[j] = keep + __shfl_xor_sync(0xffffffffu, send, 16);
      }
      const bool up2 = lane & 8;
#pragma unroll
      for (int j = 0; j < 2; j++) {
        const float send = up2 ? a[j] : a[j + 2], keep = up2 ? a[j + 2] : a[j];
        a[j] = keep + __shfl_xor_sync(0xffffffffu, send, 8);
      }
      const bool up3 = lane & 4;
      const float send = up3 ? a[0] : a[1], keep = up3 ? a[1] : a[0];
      a[0] = keep + __shfl_xor_sync(0xffffffffu, send, 4);
      a[0] += __shfl_xor_sync(0xffffffffu, a[0], 2);
      a[0] += __shfl_xor_sync(0xffffffffu, a[0], 1);
      if ((lane & 3) == 0) part[wid * 8 + (lane >> 2)] = a[0];
    }
    __syncthreads();
    if (wid == 0) {
      uint32_t bits = 0;
      if (lane < 24) {
        const int hc2 = lane >> 3, j = lane & 7;
        const float gt = rbf(part[(2 * hc2) * 8 + j] + part[(2 * hc2 + 1) * 8 + j]);
        const float up = rbf(part[(6 + 2 * hc2) * 8 + j] + part[(6 + 2 * hc2 + 1) * 8 + j]);
        const float sg = rbf(gt / (1.f + __expf(-gt)));
        bits = __bfloat16_as_ushort(__float2bfloat16_rn(sg * up));
      }
      const uint32_t nb = __shfl_down_sync(0xffffffffu, bits, 1);
      const uint32_t pw = bits | (nb << 16);
      const uint32_t w1 = __shfl_down_sync(0xffffffffu, pw, 2), w2 = __shfl_down_sync(0xffffffffu, pw, 4), w3 = __shfl_down_sync(0xffffffffu, pw, 6);
      const uint4 mine = enc4(make_uint4(pw, w1, w2, w3));
#pragma unroll
      for (int i = 0; i < 4; i++) {
        const int t = lane + 32 * i;
        const int cons = t / 3, ck = t - 3 * cons;
        uint4 v;
        v.x = __shfl_sync(0xffffffffu, mine.x, 8 * ck); v.y = __shfl_sync(0xffffffffu, mine.y, 8 * ck);
        v.z = __shfl_sync(0xffffffffu, mine.z, 8 * ck); v.w = __shfl_sync(0xffffffffu, mine.w, 8 * ck);
        if (t < 3 * N2) st_pub4(&g_act[cons][cta * 3 + ck], v);
      }
      __syncwarp();
      bar_arrive(7, 384);
    } else {
      bar_sync(7, 384);
    }
#pragma unroll
    for (int i = 0; i < 4; i++) if (i < 3 || tid < 128) g_y2[cta * 1280 + tid + NTHR * i] = make_uint4(0, 0, 0, 0);
    if (st_out) {
#pragma unroll
      for (int k = 0; k < 5; k++) outp[4 * k] = make_uint4(hreg[4 * k], hreg[4 * k + 1], hreg[4 * k + 2], hreg[4 * k + 3]);
    }
  } else if (cta < N1 + N2) {
    const int j2 = cta - N1;
    uint4 rowv = make_uint4(0, 0, 0, 0);
    if (tid < 192) {
      const uint4 v = poll4(&g_act[j2][tid]);
      float4* xp = reinterpret_cast<float4*>(xs + tid * 8);
      xp[0] = make_float4(lo_f(v.x), hi_f(v.x), lo_f(v.y), hi_f(v.y));
      xp[1] = make_float4(lo_f(v.z), hi_f(v.z), lo_f(v.w), hi_f(v.w));
    } else if (tid < 196) {
      const int t = tid - 192;
      rowv = poll4(&g_cand[wcta][t >> 1][j2 * 2 + (t & 1)]);
      reinterpret_cast<uint4*>(part + 256)[t] = rowv;
    }
    __syncthreads();
    const int hc = lane & 1;
    float a[8];
#pragma unroll
    for (int j = 0; j < 8; j++) a[j] = 0.f;
#pragma unroll
    for (int it = 0; it < 8; it++) {
      const float x = xs[rs + 192 * it];
#pragma unroll
      for (int j = 0; j < 8; j++) a[j] = fmaf(x, wf[it][j], a[j]);
    }
    {
      const bool up = lane & 16;
#pragma unroll
      for (int j = 0; j < 4; j++) {
        const float send = up ? a[j] : a[j + 4], keep = up ? a[j + 4] : a[j];
        a[j] = keep + __shfl_xor_sync(0xffffffffu, send, 16);
      }
      const bool up2 = lane & 8;
#pragma unroll
      for (int j = 0; j < 2; j++) {
        const float send = up2 ? a[j] : a[j + 2], keep = up2 ? a[j + 2] : a[j];
        a[j] = keep + __shfl_xor_sync(0xffffffffu, send, 8);
      }
      const bool up3 = lane & 4;
      const float send = up3 ? a[0] : a[1], keep = up3 ? a[1] : a[0];
      a[0] = keep + __shfl_xor_sync(0xffffffffu, send, 4);
      a[0] += __shfl_xor_sync(0xffffffffu, a[0], 2);
      if ((lane & 2) == 0) part[wid * 16 + hc * 8 + (lane >> 2)] = a[0];
    }
    __syncthreads();
    if (tid < 16) {
      float y = 0.f;
#pragma unroll
      for (int i = 0; i < 12; i++) y += part[i * 16 + tid];
      const uint32_t ord = win >> 16;
      const uint32_t rb = (ord & 0x8000u) ? (ord ^ 0x8000u) : (ord ^ 0xFFFFu);
      const float r = __uint_as_float(rb << 16);
      const float sg = rbf(1.f / (1.f + __expf(-r)));
      const float yy = rbf(rbf(y) * sg);
      const unsigned short* rv = reinterpret_cast<const unsigned short*>(part + 256);
      const float hn = __uint_as_float((uint32_t)rv[tid] << 16), h = __uint_as_float((uint32_t)rv[16 + tid] << 16);
      gout[(size_t)wrow * D_ + j2 * 16 + tid] = __float2bfloat16_rn(h + rbf(hn + yy));
    }
  }
}

}

typedef CUresult (*EncodeFn)(CUtensorMap*, CUtensorMapDataType, cuuint32_t, void*, const cuuint64_t*, const cuuint64_t*,
                             const cuuint32_t*, const cuuint32_t*, CUtensorMapInterleave, CUtensorMapSwizzle,
                             CUtensorMapL2promotion, CUtensorMapFloatOOBfill);

extern "C" void kernel_launch(void* const* d_in, const int* in_sizes, int n_in, void* d_out, int out_size) {
  (void)in_sizes; (void)n_in; (void)out_size;
  static EncodeFn encode = nullptr;
  static CUtensorMap tmg, tmu, tmd;
  static void* cached[3] = {nullptr, nullptr, nullptr};
  if (!encode) {
    cudaFuncSetAttribute(fused_kernel, cudaFuncAttributeMaxDynamicSharedMemorySize, (int)sizeof(Smem));
    void* fn = nullptr;
    cudaDriverEntryPointQueryResult qr;
    cudaGetDriverEntryPoint("cuTensorMapEncodeTiled", &fn, cudaEnableDefault, &qr);
    encode = (EncodeFn)fn;
  }
  if (cached[0] != d_in[8] || cached[1] != d_in[9] || cached[2] != d_in[10]) {
    const cuuint32_t es[2] = {1, 1};
    {
      const cuuint64_t dims[2] = {F_, D_}, strides[1] = {F_ * 2};
      const cuuint32_t box[2] = {24, 160};
      encode(&tmg, CU_TENSOR_MAP_DATA_TYPE_BFLOAT16, 2, d_in[8], dims, strides, box, es, CU_TENSOR_MAP_INTERLEAVE_NONE,
             CU_TENSOR_MAP_SWIZZLE_NONE, CU_TENSOR_MAP_L2_PROMOTION_NONE, CU_TENSOR_MAP_FLOAT_OOB_FILL_NONE);
      encode(&tmu, CU_TENSOR_MAP_DATA_TYPE_BFLOAT16, 2, d_in[9], dims, strides, box, es, CU_TENSOR_MAP_INTERLEAVE_NONE,
             CU_TENSOR_MAP_SWIZZLE_NONE, CU_TENSOR_MAP_L2_PROMOTION_NONE, CU_TENSOR_MAP_FLOAT_OOB_FILL_NONE);
    }
    {
      const cuuint64_t dims[2] = {D_, F_}, strides[1] = {D_ * 2};
      const cuuint32_t box[2] = {16, 256};
      encode(&tmd, CU_TENSOR_MAP_DATA_TYPE_BFLOAT16, 2, d_in[10], dims, strides, box, es, CU_TENSOR_MAP_INTERLEAVE_NONE,
             CU_TENSOR_MAP_SWIZZLE_NONE, CU_TENSOR_MAP_L2_PROMOTION_NONE, CU_TENSOR_MAP_FLOAT_OOB_FILL_NONE);
    }
    cached[0] = d_in[8]; cached[1] = d_in[9]; cached[2] = d_in[10];
  }
  fused_kernel<<<NCTA, NTHR, sizeof(Smem), cudaStreamPerThread>>>(
      tmg, tmu, tmd, (const bf16*)d_in[0], (const bf16*)d_in[1], (const bf16*)d_in[2], (const bf16*)d_in[3],
      (const bf16*)d_in[4], (const bf16*)d_in[5], (const bf16*)d_in[7], (bf16*)d_out);
}
```

```cpp
#include <cuda_runtime.h>
#include <cuda_bf16.h>
#include <cuda.h>
#include <stdint.h>

namespace {

typedef __nv_bfloat16 bf16;
typedef __nv_bfloat162 bf162;

constexpr int S_ = 2048, D_ = 640, F_ = 1536;
constexpr int NCTA = 128, CPC = 5, NTHR = 384;
constexpr int UPAD = 136, USTR = 2192;
constexpr int TABW = 1040;
constexpr int ZPB = 132;
constexpr int QSTR = 648;
constexpr int N1 = 64;
constexpr int N2 = 40;
constexpr int SPIN_LIMIT = 1 << 19;
constexpr int POLL_NS = 100;

struct __align__(128) Smem {
  uint32_t tabA[3][2][TABW];
  uint32_t extra[1024];
  uint32_t tabB[2][2][TABW];
  bf16 u[CPC][USTR];
  float z[2][4][ZPB * 16];
  bf16 q[16][QSTR];
  alignas(128) uint4 w[3840];
  uint4 wr[80];
  alignas(16) float2 st[16][4];
  alignas(16) float2 stq[16][4];
  alignas(16) float rp[16][4];
  unsigned long long mbar;
  unsigned long long mbarw;
  unsigned long long mbarc;
  unsigned long long mbary;
  unsigned long long mbarh;
  uint32_t target;
  uint32_t target2;
  uint32_t target3;
  uint32_t best;
  uint32_t win;
};

__device__ uint4 g_kv[D_ * S_ / 8];
__device__ uint4 g_y2[D_ * S_ / 8];
__device__ uint32_t g_keys[NCTA][NCTA];
__device__ uint4 g_cand[NCTA][2][80];
__device__ uint4 g_act[N2][F_ / 8];
__device__ __align__(256) unsigned int g_ctrs[3][64];
#define g_ctr g_ctrs[0][0]
#define g_ctr2 g_ctrs[1][0]
#define g_ctr3 g_ctrs[2][0]

__device__ __forceinline__ uint32_t smem_u32(const void* p) { return (uint32_t)__cvta_generic_to_shared(p); }
__device__ __forceinline__ void wg_fence() { asm volatile("wgmma.fence.sync.aligned;" ::: "memory"); }
__device__ __forceinline__ void wg_commit() { asm volatile("wgmma.commit_group.sync.aligned;" ::: "memory"); }
template <int N> __device__ __forceinline__ void wg_wait() { asm volatile("wgmma.wait_group.sync.aligned %0;" ::"n"(N) : "memory"); }
__device__ __forceinline__ void bar_sync(int id, int n) { asm volatile("bar.sync %0, %1;" ::"r"(id), "r"(n) : "memory"); }
__device__ __forceinline__ void bar_arrive(int id, int n) { asm volatile("bar.arrive %0, %1;" ::"r"(id), "r"(n) : "memory"); }
__device__ __forceinline__ bf162 u2b(uint32_t u) { return *reinterpret_cast<bf162*>(&u); }
__device__ __forceinline__ uint32_t b2u(bf162 b) { return *reinterpret_cast<uint32_t*>(&b); }
__device__ __forceinline__ float lo_f(uint32_t u) { return __uint_as_float(u << 16); }
__device__ __forceinline__ float hi_f(uint32_t u) { return __uint_as_float(u & 0xFFFF0000u); }
__device__ __forceinline__ float rbf(float x) { return __bfloat162float(__float2bfloat16_rn(x)); }
__device__ __forceinline__ uint32_t pack2(float a, float b) { return b2u(__floats2bfloat162_rn(a, b)); }
__device__ __forceinline__ uint32_t enc(uint32_t w) { return max(~w, 1u); }
__device__ __forceinline__ uint4 enc4(uint4 v) { return make_uint4(enc(v.x), enc(v.y), enc(v.z), enc(v.w)); }
__device__ __forceinline__ uint4 ld_poll4(const uint4* p) {
  uint4 v;
  asm volatile("ld.relaxed.gpu.global.v4.u32 {%0,%1,%2,%3}, [%4];" : "=r"(v.x), "=r"(v.y), "=r"(v.z), "=r"(v.w) : "l"(p) : "memory");
  return v;
}
__device__ __forceinline__ bool ready4(uint4 v) { return v.x != 0u && v.y != 0u && v.z != 0u && v.w != 0u; }
__device__ __forceinline__ uint4 poll4(const uint4* p) {
  uint4 v = ld_poll4(p);
  int it = 0;
  while (!ready4(v) && ++it < SPIN_LIMIT) v = ld_poll4(p);
  return make_uint4(~v.x, ~v.y, ~v.z, ~v.w);
}
__device__ __forceinline__ void st_pub4(uint4* p, uint4 v) {
  asm volatile("st.relaxed.gpu.global.v4.u32 [%0], {%1,%2,%3,%4};" ::"l"(p), "r"(v.x), "r"(v.y), "r"(v.z), "r"(v.w) : "memory");
}
__device__ __forceinline__ void st_pub2(uint2* p, uint32_t a, uint32_t b) {
  asm volatile("st.relaxed.gpu.global.v2.u32 [%0], {%1,%2};" ::"l"(p), "r"(a), "r"(b) : "memory");
}
__device__ __forceinline__ void mma_bf16(float (&c)[4], uint32_t a0, uint32_t a2, uint32_t b0, uint32_t b1) {
  asm volatile("mma.sync.aligned.m16n8k16.row.col.f32.bf16.bf16.f32 {%0,%1,%2,%3}, {%4,%5,%6,%5}, {%7,%8}, {%0,%1,%2,%3};"
               : "+f"(c[0]), "+f"(c[1]), "+f"(c[2]), "+f"(c[3]) : "r"(a0), "r"(0u), "r"(a2), "r"(b0), "r"(b1));
}
__device__ __forceinline__ void mbar_wait(const unsigned long long* bar) {
  const uint32_t mb = smem_u32(bar);
  uint32_t ok = 0;
  int it = 0;
  while (!ok && ++it < SPIN_LIMIT)
    asm volatile("{ .reg .pred p; mbarrier.try_wait.parity.shared.b64 p, [%1], 0; selp.u32 %0, 1, 0, p; }" : "=r"(ok) : "r"(mb) : "memory");
}
__device__ __forceinline__ void bulk_g2s(void* dst, const void* src, uint32_t bytes, const unsigned long long* bar) {
  asm volatile("cp.async.bulk.shared::cluster.global.mbarrier::complete_tx::bytes [%0], [%1], %2, [%3];" ::"r"(smem_u32(dst)),
               "l"(src), "r"(bytes), "r"(smem_u32(bar)) : "memory");
}
__device__ __forceinline__ void mbar_expect(const unsigned long long* bar, uint32_t bytes) {
  asm volatile("mbarrier.arrive.expect_tx.shared.b64 _, [%0], %1;" ::"r"(smem_u32(bar)), "r"(bytes) : "memory");
}
__device__ __forceinline__ void mma_bf16x(float (&c)[4], uint32_t a0, uint32_t a1, uint32_t a2, uint32_t a3, uint32_t b0, uint32_t b1) {
  asm volatile("mma.sync.aligned.m16n8k16.row.col.f32.bf16.bf16.f32 {%0,%1,%2,%3}, {%4,%5,%6,%7}, {%8,%9}, {%0,%1,%2,%3};"
               : "+f"(c[0]), "+f"(c[1]), "+f"(c[2]), "+f"(c[3]) : "r"(a0), "r"(a1), "r"(a2), "r"(a3), "r"(b0), "r"(b1));
}
__device__ __forceinline__ float fdivr(float a, float d, float r) {
  float q = a * r;
  float e = fmaf(-q, d, a);
  return fmaf(e, r, q);
}

template <bool FIRST> __device__ __forceinline__ void wgmma32(float (&d)[16], const uint32_t* a, uint64_t desc) {
  if (FIRST) {
    asm volatile("wgmma.mma_async.sync.aligned.m64n32k16.f32.bf16.bf16 {%0,%1,%2,%3,%4,%5,%6,%7,%8,%9,%10,%11,%12,%13,%14,%15}, {%16,%17,%18,%19}, %20, 0, 1, 1, 0;"
                 : "+f"(d[0]), "+f"(d[1]), "+f"(d[2]), "+f"(d[3]), "+f"(d[4]), "+f"(d[5]), "+f"(d[6]), "+f"(d[7]),
                   "+f"(d[8]), "+f"(d[9]), "+f"(d[10]), "+f"(d[11]), "+f"(d[12]), "+f"(d[13]), "+f"(d[14]), "+f"(d[15])
                 : "r"(a[0]), "r"(a[1]), "r"(a[2]), "r"(a[3]), "l"(desc));
  } else {
    asm volatile("wgmma.mma_async.sync.aligned.m64n32k16.f32.bf16.bf16 {%0,%1,%2,%3,%4,%5,%6,%7,%8,%9,%10,%11,%12,%13,%14,%15}, {%16,%17,%18,%19}, %20, 1, 1, 1, 0;"
                 : "+f"(d[0]), "+f"(d[1]), "+f"(d[2]), "+f"(d[3]), "+f"(d[4]), "+f"(d[5]), "+f"(d[6]), "+f"(d[7]),
                   "+f"(d[8]), "+f"(d[9]), "+f"(d[10]), "+f"(d[11]), "+f"(d[12]), "+f"(d[13]), "+f"(d[14]), "+f"(d[15])
                 : "r"(a[0]), "r"(a[1]), "r"(a[2]), "r"(a[3]), "l"(desc));
  }
}

template <int G> __device__ __forceinline__ void load_a(uint32_t (&a)[8], const uint32_t* tp) {
#pragma unroll
  for (int q = 0; q < 2; q++) {
    const int e = 2 * G + q;
    a[4 * q + 0] = tp[-64 * e];
    a[4 * q + 1] = tp[-64 * e - 32];
    a[4 * q + 2] = tp[-64 * e + 4];
    a[4 * q + 3] = tp[-64 * e - 28];
  }
}
__device__ __forceinline__ void load_a_all(uint32_t (&a)[8][8], const uint32_t* tp) {
  load_a<0>(a[0], tp); load_a<1>(a[1], tp); load_a<2>(a[2], tp); load_a<3>(a[3], tp);
  load_a<4>(a[4], tp); load_a<5>(a[5], tp); load_a<6>(a[6], tp); load_a<7>(a[7], tp);
}
template <int G> __device__ __forceinline__ void issue_g(float (&acc)[8][16], uint32_t (&a)[8], uint64_t desc0) {
  wg_fence();
#pragma unroll
  for (int q = 0; q < 2; q++) {
#pragma unroll
    for (int b = G; b < 8; b++) {
      const int delta = 2 * b - (2 * G + q);
      if (G == 0 && q == 0) wgmma32<true>(acc[b], &a[4 * q], desc0 + (uint64_t)(int64_t)(16 * delta));
      else wgmma32<false>(acc[b], &a[4 * q], desc0 + (uint64_t)(int64_t)(16 * delta));
    }
  }
  wg_commit();
}
template <int B> __device__ __forceinline__ void fence_blk(float (&acc)[8][16]) {
#pragma unroll
  for (int i = 0; i < 16; i++) asm volatile("" : "+f"(acc[B][i])::"memory");
}
__device__ __forceinline__ void fence_a(uint32_t (&a)[8]) {
#pragma unroll
  for (int i = 0; i < 8; i++) asm volatile("" : "+r"(a[i])::"memory");
}
template <int B> __device__ __forceinline__ void sts_blk(float (&acc)[8][16], float* zw, int off_even, int off_odd) {
#pragma unroll
  for (int jj = 0; jj < 4; jj++) {
    const int j = 4 * B + jj;
    float p0 = acc[B][4 * jj + 0], p1 = acc[B][4 * jj + 1];
    if (jj > 0) { p0 += acc[B][4 * (jj - 1) + 2]; p1 += acc[B][4 * (jj - 1) + 3]; }
    else if (B > 0) { p0 += acc[B > 0 ? B - 1 : 0][14]; p1 += acc[B > 0 ? B - 1 : 0][15]; }
    zw[64 * j + off_even] = p0;
    zw[64 * j + off_odd] = p1;
  }
}
__device__ __forceinline__ int tab_off(int c) { return c == 4 ? 0 : (c + 1) * 2 * TABW + (c >= 2 ? 1024 : 0); }
__device__ __forceinline__ int tile_perm(int ch) { return ch ^ (((ch >> 3) & 3) << 1); }

__device__ __forceinline__ void wait_ctr(const unsigned int* ctr, uint32_t target) {
  uint32_t v;
  int it = 0;
  do {
    asm volatile("ld.acquire.gpu.global.u32 %0, [%1];" : "=r"(v) : "l"(ctr) : "memory");
  } while ((int)(v - target) < 0 && ++it < SPIN_LIMIT);
}

__device__ __forceinline__ float2 row_part_stats(const uint32_t (&x)[20]) {
  float cs[5][4];
#pragma unroll
  for (int k = 0; k < 5; k++) {
    cs[k][0] = cs[k][1] = cs[k][2] = cs[k][3] = 0.f;
    mma_bf16x(cs[k], x[4 * k + 0], x[4 * k + 2], x[4 * k + 1], x[4 * k + 3], 0x3F803F80u, 0x3F803F80u);
  }
  const float mean = ((((cs[0][0] + cs[0][2]) + (cs[1][0] + cs[1][2])) + ((cs[2][0] + cs[2][2]) + (cs[3][0] + cs[3][2]))) + (cs[4][0] + cs[4][2])) * (1.f / 160.f);
  float m2a = 0.f, m2b = 0.f, m2c = 0.f, m2d = 0.f;
#pragma unroll
  for (int i = 0; i < 20; i += 2) {
    const float a = lo_f(x[i]) - mean, b = hi_f(x[i]) - mean, c = lo_f(x[i + 1]) - mean, d = hi_f(x[i + 1]) - mean;
    m2a = fmaf(a, a, m2a); m2b = fmaf(b, b, m2b); m2c = fmaf(c, c, m2c); m2d = fmaf(d, d, m2d);
  }
  float m2 = (m2a + m2b) + (m2c + m2d);
  m2 += __shfl_xor_sync(0xffffffffu, m2, 1);
  m2 += __shfl_xor_sync(0xffffffffu, m2, 2);
  return make_float2(mean, m2);
}
template <bool EXACT> __device__ __forceinline__ void row_normalize(const float4* st, const uint32_t (&x)[20], uint32_t (&y)[20]) {
  const float4 p = st[0], q = st[1];
  const float mean = ((p.x + p.z) + (q.x + q.z)) * 0.25f;
  const float d0 = p.x - mean, d1 = p.z - mean, d2 = q.x - mean, d3 = q.z - mean;
  const float m2 = ((p.y + p.w) + (q.y + q.w)) + 160.f * ((d0 * d0 + d1 * d1) + (d2 * d2 + d3 * d3));
  const float hd = rbf(sqrtf(rbf(rbf(m2 * (1.f / D_)) + 1e-5f)));
  const float hr = __frcp_rn(hd);
  const bf162 hm2 = __float2bfloat162_rn(mean);
#pragma unroll
  for (int i = 0; i < 20; i++) {
    const uint32_t d = b2u(__hsub2_rn(u2b(x[i]), hm2));
    y[i] = EXACT ? pack2(fdivr(lo_f(d), hd, hr), fdivr(hi_f(d), hd, hr)) : pack2(lo_f(d) * hr, hi_f(d) * hr);
  }
}

__device__ __forceinline__ void gather_kv(Smem& sm, int c0, int tid) {
  mbar_wait(&sm.mbarc);
  uint4 v[4];
  uint4* src = g_kv + c0 * 256 + tid;
#pragma unroll
  for (int i = 0; i < 4; i++) if (i < 3 || tid >= 256) v[i] = ld_poll4(src + NTHR * i - (i == 3 ? 256 : 0));
#pragma unroll
  for (int i = 0; i < 4; i++) {
    if (i < 3 || tid >= 256) {
      const int t = tid + NTHR * i - (i == 3 ? 256 : 0);
      int it = 0;
      while (!ready4(v[i]) && ++it < SPIN_LIMIT) { __nanosleep(POLL_NS); v[i] = ld_poll4(g_kv + c0 * 256 + t); }
      *reinterpret_cast<uint4*>(&sm.u[t >> 8][UPAD + (t & 255) * 8]) = make_uint4(~v[i].x, ~v[i].y, ~v[i].z, ~v[i].w);
    }
  }
  asm volatile("fence.proxy.async.shared::cta;" ::: "memory");
  __syncthreads();
}

__global__ void __launch_bounds__(NTHR, 1)
fused_kernel(const __grid_constant__ CUtensorMap tmg, const __grid_constant__ CUtensorMap tmu,
             const __grid_constant__ CUtensorMap tmd, const bf16* __restrict__ gq, const bf16* __restrict__ gk, const bf16* __restrict__ gv,
             const bf16* __restrict__ gsk, const bf16* __restrict__ gh, const bf16* __restrict__ gD,
             const bf16* __restrict__ gwr, bf16* __restrict__ gout) {
  extern __shared__ __align__(128) unsigned char smraw[];
  Smem& sm = *reinterpret_cast<Smem*>(smraw);
  const int tid = threadIdx.x;
  const int cta = blockIdx.x;
  const int c0 = cta * CPC;
  const int lane = tid & 31;
  const int wid = tid >> 5;

  {
    uint4* hs = reinterpret_cast<uint4*>(&sm.z[0][0][0]);
    const int oc = tid >> 2;
    const int r0 = cta * 16 + (tid & 3) * 4;
    uint4 kk[7], vv[4], sk[4];
    if (tid < 320) {
      const uint4* kp = reinterpret_cast<const uint4*>(gk) + (size_t)r0 * 80 + oc;
      const uint4* vp = reinterpret_cast<const uint4*>(gv) + (size_t)r0 * 80 + oc;
#pragma unroll
      for (int i = 0; i < 4; i++) sk[i] = __ldg(reinterpret_cast<const uint4*>(gsk) + oc * 4 + i);
#pragma unroll
      for (int i = 0; i < 7; i++) kk[i] = (i >= 3 || r0 > 0) ? __ldg(kp + (i - 3) * 80) : make_uint4(0, 0, 0, 0);
#pragma unroll
      for (int i = 0; i < 4; i++) vv[i] = __ldg(vp + i * 80);
    } else if (tid == 320) {
      asm volatile("mbarrier.init.shared.b64 [%0], 1;" ::"r"(smem_u32(&sm.mbarh)) : "memory");
      asm volatile("mbarrier.init.shared.b64 [%0], 1;" ::"r"(smem_u32(&sm.mbar)) : "memory");
      asm volatile("mbarrier.init.shared.b64 [%0], 1;" ::"r"(smem_u32(&sm.mbarw)) : "memory");
      asm volatile("mbarrier.init.shared.b64 [%0], 1;" ::"r"(smem_u32(&sm.mbarc)) : "memory");
      asm volatile("mbarrier.init.shared.b64 [%0], 1;" ::"r"(smem_u32(&sm.mbary)) : "memory");
      asm volatile("fence.proxy.async.shared::cta;" ::: "memory");
    } else if (tid == 352) {
      uint32_t v1, v2, v3;
      asm volatile("ld.relaxed.gpu.global.u32 %0, [%1];" : "=r"(v1) : "l"(&g_ctr) : "memory");
      asm volatile("ld.relaxed.gpu.global.u32 %0, [%1];" : "=r"(v2) : "l"(&g_ctr2) : "memory");
      asm volatile("ld.relaxed.gpu.global.u32 %0, [%1];" : "=r"(v3) : "l"(&g_ctr3) : "memory");
      sm.target = (v1 / NCTA + 1u) * NCTA;
      sm.target2 = (v2 / NCTA + 1u) * NCTA;
      sm.target3 = (v3 / NCTA + 1u) * NCTA;
    }
    if (tid < 320) bar_sync(6, 384); else { bar_arrive(6, 384); bar_sync(5, 64); }
    if (tid < 320) {
      uint32_t o[4][4];
#pragma unroll
      for (int p = 0; p < 4; p++) {
        const bf162 w0 = u2b(__byte_perm(sk[p].x, sk[p].z, 0x5410)), w1 = u2b(__byte_perm(sk[p].x, sk[p].z, 0x7632));
        const bf162 w2 = u2b(__byte_perm(sk[p].y, sk[p].w, 0x5410)), w3 = u2b(__byte_perm(sk[p].y, sk[p].w, 0x7632));
        uint32_t kv[4];
#pragma unroll
        for (int i = 0; i < 4; i++) {
          const uint32_t k0 = p == 0 ? kk[i].x : p == 1 ? kk[i].y : p == 2 ? kk[i].z : kk[i].w;
          const uint32_t k1 = p == 0 ? kk[i + 1].x : p == 1 ? kk[i + 1].y : p == 2 ? kk[i + 1].z : kk[i + 1].w;
          const uint32_t k2 = p == 0 ? kk[i + 2].x : p == 1 ? kk[i + 2].y : p == 2 ? kk[i + 2].z : kk[i + 2].w;
          const uint32_t k3 = p == 0 ? kk[i + 3].x : p == 1 ? kk[i + 3].y : p == 2 ? kk[i + 3].z : kk[i + 3].w;
          const uint32_t vx = p == 0 ? vv[i].x : p == 1 ? vv[i].y : p == 2 ? vv[i].z : vv[i].w;
          bf162 a = __hmul2_rn(u2b(k0), w3);
          a = __hadd2_rn(a, __hmul2_rn(u2b(k1), w2));
          a = __hadd2_rn(a, __hmul2_rn(u2b(k2), w1));
          a = __hadd2_rn(a, __hmul2_rn(u2b(k3), w0));
          kv[i] = b2u(__hmul2_rn(a, u2b(vx)));
        }
        o[p][0] = enc(__byte_perm(kv[0], kv[1], 0x5410)); o[p][1] = enc(__byte_perm(kv[2], kv[3], 0x5410));
        o[p][2] = enc(__byte_perm(kv[0], kv[1], 0x7632)); o[p][3] = enc(__byte_perm(kv[2], kv[3], 0x7632));
      }
      uint2* dst = reinterpret_cast<uint2*>(g_kv) + (size_t)(oc * 8) * 512 + (r0 >> 2);
#pragma unroll
      for (int p = 0; p < 4; p++) {
        st_pub2(dst + (2 * p) * 512, o[p][0], o[p][1]);
        st_pub2(dst + (2 * p + 1) * 512, o[p][2], o[p][3]);
      }
      if (wid == 0) bar_sync(4, 320); else bar_arrive(4, 320);
      if (tid == 0) {
        asm volatile("red.relaxed.gpu.global.add.u32 [%0], 1;" ::"l"(&g_ctr2) : "memory");
      }
      __syncwarp();
    } else {
      const int t0 = tid - 320;
      const uint4 zz = make_uint4(0, 0, 0, 0);
      if (tid == 320) {
        mbar_expect(&sm.mbarh, CPC * S_ * 2);
        bulk_g2s(hs, gh + (size_t)c0 * S_, CPC * S_ * 2, &sm.mbarh);
      }
      __syncwarp();
      for (int t = t0; t < CPC * 17; t += 64) *reinterpret_cast<uint4*>(&sm.u[t / 17][(t % 17) * 8]) = zz;
      if (t0 < 40) *reinterpret_cast<uint4*>(&sm.tabA[0][0][0] + tab_off(t0 >> 3) + ((t0 >> 2) & 1) * TABW + 1024 + 4 * (t0 & 3)) = zz;
      (&g_cand[cta][0][0])[t0] = zz;
      (&g_cand[cta][0][0])[64 + t0] = zz;
      if (t0 < 32) (&g_cand[cta][0][0])[128 + t0] = zz;
      else reinterpret_cast<uint4*>(&g_keys[cta][0])[t0 - 32] = zz;
      if (cta >= N1 && cta < N1 + N2) {
#pragma unroll
        for (int i = 0; i < 3; i++) g_act[cta - N1][t0 + 64 * i] = zz;
      }
    }
    mbar_wait(&sm.mbarh);
#pragma unroll
    for (int i = 0; i < 4; i++) {
      const int t = (NTHR - 1 - tid) + NTHR * i;
      if (t < CPC * 256) {
        uint32_t* tb = &sm.tabA[0][0][0] + tab_off(t >> 8) + (255 - (t & 255)) * 4;
        const uint4 h = hs[t];
        const uint32_t hp = (t & 255) ? reinterpret_cast<const uint32_t*>(hs)[4 * t - 1] : 0u;
        uint4 r1, rr;
        r1.x = __byte_perm(h.w, 0, 0x1032); r1.y = __byte_perm(h.z, 0, 0x1032);
        r1.z = __byte_perm(h.y, 0, 0x1032); r1.w = __byte_perm(h.x, 0, 0x1032);
        rr.x = __byte_perm(h.w, h.z, 0x7610); rr.y = __byte_perm(h.z, h.y, 0x7610);
        rr.z = __byte_perm(h.y, h.x, 0x7610); rr.w = __byte_perm(h.x, hp, 0x7610);
        *reinterpret_cast<uint4*>(tb) = rr;
        *reinterpret_cast<uint4*>(tb + TABW) = r1;
      }
    }
  }
  __syncthreads();

  const int wg = __shfl_sync(0xffffffffu, tid >> 7, 0);
  const int wtid = tid & 127;
  uint4* tile = reinterpret_cast<uint4*>(&sm.tabB[0][0][0]);
  if (wg < 2) {
    asm volatile("setmaxnreg.inc.sync.aligned.u32 224;");
    const int w = (tid >> 5) & 3, g = lane >> 2, tq = lane & 3;
    float* zw = sm.z[wg][w];
    const int sw = 3 * (((tq + w) >> 1) & 1);
    const int off_even = 16 * (tq + w) + 4 * ((0 + (g >> 2)) ^ sw) + (g & 3);
    const int off_odd = 16 * (tq + w) + 4 * ((2 + (g >> 2)) ^ sw) + (g & 3);
    uint32_t a[8][8];
    const uint32_t* tp0 = &sm.tabA[0][g & 1][1019 - 8 * w - (g >> 1) + tq];
    load_a_all(a, tp0 + tab_off(wg));
    float acc[8][16];
#pragma unroll
    for (int b = 0; b < 8; b++)
#pragma unroll
      for (int i = 0; i < 16; i++) acc[b][i] = 0.f;
    gather_kv(sm, c0, tid);
#pragma unroll 1
    for (int c = wg; c < CPC; c += 2) {
      const uint64_t desc = (uint64_t)((smem_u32(&sm.u[c][UPAD - 8]) & 0x3FFFF) >> 4) | ((uint64_t)1 << 16) | ((uint64_t)8 << 32);
      if (c > 0) bar_sync(1 + wg, 256);
      issue_g<0>(acc, a[0], desc);
      issue_g<1>(acc, a[1], desc);
      issue_g<2>(acc, a[2], desc);
      issue_g<3>(acc, a[3], desc);
      issue_g<4>(acc, a[4], desc);
      issue_g<5>(acc, a[5], desc);
      if (c + 1 < CPC) bar_arrive(1 + (wg ^ 1), 256);
      issue_g<6>(acc, a[6], desc);
      issue_g<7>(acc, a[7], desc);
      if (c >= 2) bar_sync(5 + wg, 256);
      const uint32_t* tn = tp0 + tab_off(c + 2 < CPC ? c + 2 : c);
      wg_wait<4>();
      fence_blk<0>(acc); fence_blk<1>(acc); fence_blk<2>(acc); fence_blk<3>(acc);
      fence_a(a[0]); fence_a(a[1]); fence_a(a[2]); fence_a(a[3]);
      sts_blk<0>(acc, zw, off_even, off_odd); load_a<0>(a[0], tn);
      sts_blk<1>(acc, zw, off_even, off_odd); load_a<1>(a[1], tn);
      sts_blk<2>(acc, zw, off_even, off_odd); load_a<2>(a[2], tn);
      sts_blk<3>(acc, zw, off_even, off_odd); load_a<3>(a[3], tn);
      bar_arrive(9 + wg, 256);
      wg_wait<0>();
      fence_blk<4>(acc); fence_blk<5>(acc); fence_blk<6>(acc); fence_blk<7>(acc);
      fence_a(a[4]); fence_a(a[5]); fence_a(a[6]); fence_a(a[7]);
      sts_blk<4>(acc, zw, off_even, off_odd); load_a<4>(a[4], tn);
      sts_blk<5>(acc, zw, off_even, off_odd); load_a<5>(a[5], tn);
      sts_blk<6>(acc, zw, off_even, off_odd); load_a<6>(a[6], tn);
      sts_blk<7>(acc, zw, off_even, off_odd); load_a<7>(a[7], tn);
      bar_arrive(3 + wg, 256);
    }
    asm volatile("setmaxnreg.dec.sync.aligned.u32 168;");
  } else {
    asm volatile("setmaxnreg.dec.sync.aligned.u32 56;");
    if (((wtid & 15) >> 2) < ((wtid >> 4) & 3))
      *reinterpret_cast<uint4*>(&sm.z[wtid >> 6][(wtid >> 4) & 3][(wtid & 15) * 4]) = make_uint4(0, 0, 0, 0);
    if (wtid == 96) {
      __threadfence();
      asm volatile("red.relaxed.gpu.global.add.u32 [%0], 1;" ::"l"(&g_ctr) : "memory");
    }
    if (wtid == 64) {
      const unsigned target = sm.target2;
      uint32_t v;
      int it = 0;
      do {
        asm volatile("ld.relaxed.gpu.global.u32 %0, [%1];" : "=r"(v) : "l"(&g_ctr2) : "memory");
      } while ((int)(v - target) < 0 && ++it < SPIN_LIMIT);
      asm volatile("mbarrier.arrive.shared.b64 _, [%0];" ::"r"(smem_u32(&sm.mbarc)) : "memory");
    }
    __syncwarp();
    gather_kv(sm, c0, tid);
#pragma unroll
    for (int i = 0; i < 10; i++) g_kv[c0 * 256 + wtid + 128 * i] = make_uint4(0, 0, 0, 0);
    if (wtid == 96) wait_ctr(&g_ctr, sm.target);
    __syncwarp();
    if (wtid == 32) {
      const uint32_t mw = smem_u32(&sm.mbarw);
      mbar_expect(&sm.mbar, 17 * D_ * 2);
#pragma unroll 1
      for (int r = 0; r < 16; r++) bulk_g2s(&sm.q[r][0], gq + (size_t)(cta * 16 + r) * D_, D_ * 2, &sm.mbar);
      bulk_g2s(&sm.wr[0], gwr, D_ * 2, &sm.mbar);
      if (cta < N1) {
        asm volatile("mbarrier.arrive.expect_tx.shared.b64 _, [%0], %1;" ::"r"(mw), "r"(3840 * 16) : "memory");
#pragma unroll 1
        for (int i = 0; i < 4; i++) {
          asm volatile("cp.async.bulk.tensor.2d.shared::cluster.global.mbarrier::complete_tx::bytes [%0], [%1, {%3, %4}], [%2];" ::"r"(smem_u32(&sm.w[i * 480])),
                       "l"(&tmg), "r"(mw), "r"(cta * 24), "r"(i * 160) : "memory");
          asm volatile("cp.async.bulk.tensor.2d.shared::cluster.global.mbarrier::complete_tx::bytes [%0], [%1, {%3, %4}], [%2];" ::"r"(smem_u32(&sm.w[1920 + i * 480])),
                       "l"(&tmu), "r"(mw), "r"(cta * 24), "r"(i * 160) : "memory");
        }
      } else if (cta < N1 + N2) {
        asm volatile("mbarrier.arrive.expect_tx.shared.b64 _, [%0], %1;" ::"r"(mw), "r"(3072 * 16) : "memory");
#pragma unroll 1
        for (int i = 0; i < 6; i++)
          asm volatile("cp.async.bulk.tensor.2d.shared::cluster.global.mbarrier::complete_tx::bytes [%0], [%1, {%3, %4}], [%2];" ::"r"(smem_u32(&sm.w[i * 512])),
                       "l"(&tmd), "r"(mw), "r"((cta - N1) * 16), "r"(i * 256) : "memory");
      }
    }
    const int rpb = wtid >> 1, re2 = wtid & 1;
    const int rsw = 3 * ((rpb >> 1) & 1);
    const int roff0 = 16 * rpb + 4 * ((2 * re2 + 0) ^ rsw);
    const int roff1 = 16 * rpb + 4 * ((2 * re2 + 1) ^ rsw);
    const uint32_t dvl = reinterpret_cast<const unsigned short*>(gD)[c0 + (lane < CPC ? lane : 0)];
#pragma unroll 1
    for (int c = 0; c < CPC; c++) {
      const int zg = c & 1;
      const uint32_t dvc = __shfl_sync(0xffffffffu, dvl, c);
      const bf162 d2 = u2b(dvc | (dvc << 16));
#pragma unroll
      for (int half = 0; half < 2; half++) {
        bar_sync((half ? 3 : 9) + zg, 256);
        const float* zb = sm.z[zg][0] + half * 1024;
        float4 x[4][2];
#pragma unroll
        for (int ww = 0; ww < 4; ww++) {
          x[ww][0] = *reinterpret_cast<const float4*>(zb + ww * ZPB * 16 + roff0);
          x[ww][1] = *reinterpret_cast<const float4*>(zb + ww * ZPB * 16 + roff1);
        }
        const int sidx = half * 1024 + wtid * 8;
        const uint4 kvv = *reinterpret_cast<const uint4*>(&sm.u[c][UPAD + sidx]);
        if (half == 1 && c + 2 < CPC) bar_arrive(5 + zg, 256);
        uint4 o;
        o.x = pack2((x[0][0].x + x[1][0].x) + (x[2][0].x + x[3][0].x), (x[0][0].y + x[1][0].y) + (x[2][0].y + x[3][0].y));
        o.y = pack2((x[0][0].z + x[1][0].z) + (x[2][0].z + x[3][0].z), (x[0][0].w + x[1][0].w) + (x[2][0].w + x[3][0].w));
        o.z = pack2((x[0][1].x + x[1][1].x) + (x[2][1].x + x[3][1].x), (x[0][1].y + x[1][1].y) + (x[2][1].y + x[3][1].y));
        o.w = pack2((x[0][1].z + x[1][1].z) + (x[2][1].z + x[3][1].z), (x[0][1].w + x[1][1].w) + (x[2][1].w + x[3][1].w));
        o.x = b2u(__hadd2_rn(u2b(o.x), __hmul2_rn(u2b(kvv.x), d2)));
        o.y = b2u(__hadd2_rn(u2b(o.y), __hmul2_rn(u2b(kvv.y), d2)));
        o.z = b2u(__hadd2_rn(u2b(o.z), __hmul2_rn(u2b(kvv.z), d2)));
        o.w = b2u(__hadd2_rn(u2b(o.w), __hmul2_rn(u2b(kvv.w), d2)));
        st_pub4(g_y2 + ((64 * half + rpb) * 640 + c0 + c) * 2 + re2, enc4(o));
      }
    }
    if (wid == 11) bar_sync(8, 128); else bar_arrive(8, 128);
    asm volatile("setmaxnreg.inc.sync.aligned.u32 168;");
  }

  if (tid == 352) {
    asm volatile("red.relaxed.gpu.global.add.u32 [%0], 1;" ::"l"(&g_ctr3) : "memory");
    wait_ctr(&g_ctr3, sm.target3);
    asm volatile("mbarrier.arrive.shared.b64 _, [%0];" ::"r"(smem_u32(&sm.mbary)) : "memory");
  }
  __syncwarp();
  const int g = lane >> 2, tq = lane & 3;
  const int hh = wid & 1, gqi = wid >> 1;
  const int row = hh * 8 + g;
  uint32_t hreg[20], hnreg[20];
  {
    const uint4* src = g_y2 + cta * 1280 + tid;
    uint4 v[4];
    if (wid < 8) {
      mbar_wait(&sm.mbar);
#pragma unroll
      for (int k = 0; k < 5; k++) {
        const uint4 qv4 = *reinterpret_cast<const uint4*>(&sm.q[row][32 * (5 * gqi + k) + 8 * tq]);
        hreg[4 * k] = qv4.x; hreg[4 * k + 1] = qv4.y; hreg[4 * k + 2] = qv4.z; hreg[4 * k + 3] = qv4.w;
      }
      const float2 ps = row_part_stats(hreg);
      if (tq == 0) sm.stq[row][gqi] = ps;
      bar_sync(7, 256);
      row_normalize<false>(reinterpret_cast<const float4*>(sm.stq[row]), hreg, hnreg);
    }
    mbar_wait(&sm.mbary);
#pragma unroll
    for (int i = 0; i < 4; i++) if (i < 3 || tid < 128) v[i] = ld_poll4(src + NTHR * i);
    int it = 0;
    bool all;
    do {
      all = true;
#pragma unroll
      for (int i = 0; i < 4; i++)
        if ((i < 3 || tid < 128) && !ready4(v[i])) { v[i] = ld_poll4(src + NTHR * i); all = false; }
    } while (!all && ++it < SPIN_LIMIT);
#pragma unroll
    for (int i = 0; i < 4; i++) {
      if (i < 3 || tid < 128) {
        const int t = tid + NTHR * i;
        tile[(t & 1) * 640 + tile_perm(t >> 1)] = make_uint4(~v[i].x, ~v[i].y, ~v[i].z, ~v[i].w);
      }
    }
  }
  __syncthreads();

  if (wid < 8) {
#pragma unroll
    for (int k = 0; k < 5; k++) {
      const int base = 32 * (5 * gqi + k);
      const int lch = base + 8 * ((lane & 7) >> 1) + 2 * (lane >> 3) + (lane & 1);
      uint32_t y[4];
      asm volatile("ldmatrix.sync.aligned.m8n8.x4.trans.shared.b16 {%0,%1,%2,%3}, [%4];"
                   : "=r"(y[0]), "=r"(y[1]), "=r"(y[2]), "=r"(y[3]) : "r"(smem_u32(&tile[hh * 640 + tile_perm(lch)])) : "memory");
#pragma unroll
      for (int i = 0; i < 4; i++)
        hreg[4 * k + i] = b2u(__hadd2_rn(u2b(hreg[4 * k + i]), __hmul2_rn(u2b(hnreg[4 * k + i]), u2b(y[i]))));
    }
    const float2 ps = row_part_stats(hreg);
    if (tq == 0) sm.st[row][gqi] = ps;
    bar_sync(7, 256);
    row_normalize<false>(reinterpret_cast<const float4*>(sm.st[row]), hreg, hnreg);
    float cr[5][4];
#pragma unroll
    for (int k = 0; k < 5; k++) {
      cr[k][0] = cr[k][1] = cr[k][2] = cr[k][3] = 0.f;
      const uint4 w4 = sm.wr[4 * (5 * gqi + k) + tq];
      mma_bf16(cr[k], hnreg[4 * k + 0], hnreg[4 * k + 1], w4.x, w4.y);
      mma_bf16(cr[k], hnreg[4 * k + 2], hnreg[4 * k + 3], w4.z, w4.w);
    }
    if (tq == 0) sm.rp[row][gqi] = ((cr[0][0] + cr[1][0]) + (cr[2][0] + cr[3][0])) + cr[4][0];
  }
  __syncthreads();
  uint32_t best;
  {
    const int rr = lane & 15;
    const float4 rp4 = *reinterpret_cast<const float4*>(sm.rp[rr]);
    const float r = (rp4.x + rp4.y) + (rp4.z + rp4.w);
    const uint32_t bits = __bfloat16_as_ushort(__float2bfloat16_rn(r));
    const uint32_t ord = (bits & 0x8000u) ? (bits ^ 0xFFFFu) : (bits ^ 0x8000u);
    const uint32_t key = (ord << 16) | 0x8000u | (uint32_t)(2047 - (cta * 16 + rr));
    best = __reduce_max_sync(0xffffffffu, key);
  }
  if (wid >= 8) asm volatile("st.relaxed.gpu.global.u32 [%0], %1;" ::"l"(&g_keys[tid - 256][cta]), "r"(best) : "memory");
  const int brow = (2047 - (int)(best & 0x7FFu)) - cta * 16;
  if (wid < 8 && row == brow) {
#pragma unroll
    for (int k = 0; k < 5; k++)
      st_pub4(&g_cand[cta][0][4 * (5 * gqi + k) + tq], enc4(make_uint4(hnreg[4 * k], hnreg[4 * k + 1], hnreg[4 * k + 2], hnreg[4 * k + 3])));
#pragma unroll
    for (int k = 0; k < 5; k++)
      st_pub4(&g_cand[cta][1][4 * (5 * gqi + k) + tq], enc4(make_uint4(hreg[4 * k], hreg[4 * k + 1], hreg[4 * k + 2], hreg[4 * k + 3])));
  }
#pragma unroll
  for (int i = 0; i < 20; i++) hreg[i] = b2u(__hadd2_rn(u2b(hreg[i]), u2b(hnreg[i])));
  float wf[10][8];
  const int rs = cta < N1 ? (wid & 1) * 32 + lane : wid * 16 + (lane >> 1);
  if (cta < N1 + N2) {
    mbar_wait(&sm.mbarw);
    const uint4* wp = cta < N1 ? &sm.w[(wid / 6) * 1920 + rs * 3 + ((wid % 6) >> 1)] : &sm.w[rs * 2 + (lane & 1)];
    const int wstep = cta < N1 ? 192 : 384;
#pragma unroll
    for (int it = 0; it < 10; it++) {
      const uint4 wv = wp[(it < 8 || cta < N1) ? it * wstep : 0];
      wf[it][0] = lo_f(wv.x); wf[it][1] = hi_f(wv.x); wf[it][2] = lo_f(wv.y); wf[it][3] = hi_f(wv.y);
      wf[it][4] = lo_f(wv.z); wf[it][5] = hi_f(wv.z); wf[it][6] = lo_f(wv.w); wf[it][7] = hi_f(wv.w);
    }
#pragma unroll
    for (int it = 0; it < 10; it++)
#pragma unroll
      for (int j = 0; j < 8; j++) asm volatile("" : "+f"(wf[it][j]));
  }
  if (wid == 11) {
    const uint4* kp = reinterpret_cast<const uint4*>(&g_keys[cta][0]) + lane;
    uint4 v = ld_poll4(kp);
    int it = 0;
    while (!ready4(v) && ++it < SPIN_LIMIT) v = ld_poll4(kp);
    const uint32_t m = max(max(v.x, v.y), max(v.z, v.w));
    const uint32_t wk = __reduce_max_sync(0xffffffffu, m);
    if (lane == 0) sm.win = wk;
  }
  __syncthreads();
  const uint32_t win = sm.win;
  const int wrow = 2047 - (int)(win & 0x7FFu);
  const int wcta = wrow >> 4;
  const bool st_out = wid < 8 && (cta * 16 + row) != wrow;
  uint4* outp = reinterpret_cast<uint4*>(gout + (size_t)(cta * 16 + row) * D_) + 20 * gqi + tq;
  if (cta >= N1) {
    if (st_out) {
#pragma unroll
      for (int k = 0; k < 5; k++) outp[4 * k] = make_uint4(hreg[4 * k], hreg[4 * k + 1], hreg[4 * k + 2], hreg[4 * k + 3]);
    }
  }
  if (cta >= N1) {
#pragma unroll
    for (int i = 0; i < 4; i++) if (i < 3 || tid < 128) g_y2[cta * 1280 + tid + NTHR * i] = make_uint4(0, 0, 0, 0);
  }
  float* xs = &sm.z[0][0][0];
  float* part = xs + 2048;
  if (cta < N1) {
    if (tid < 80) {
      const uint4 v = poll4(&g_cand[wcta][0][tid]);
      float4* xp = reinterpret_cast<float4*>(xs + tid * 8);
      xp[0] = make_float4(lo_f(v.x), hi_f(v.x), lo_f(v.y), hi_f(v.y));
      xp[1] = make_float4(lo_f(v.z), hi_f(v.z), lo_f(v.w), hi_f(v.w));
    }
    __syncthreads();
    float a[8];
#pragma unroll
    for (int j = 0; j < 8; j++) a[j] = 0.f;
#pragma unroll
    for (int it = 0; it < 10; it++) {
      const float x = xs[rs + 64 * it];
#pragma unroll
      for (int j = 0; j < 8; j++) a[j] = fmaf(x, wf[it][j], a[j]);
    }
    {
      const bool up = lane & 16;
#pragma unroll
      for (int j = 0; j < 4; j++) {
        const float send = up ? a[j] : a[j + 4], keep = up ? a[j + 4] : a[j];
        a[j] = keep + __shfl_xor_sync(0xffffffffu, send, 16);
      }
      const bool up2 = lane & 8;
#pragma unroll
      for (int j = 0; j < 2; j++) {
        const float send = up2 ? a[j] : a[j + 2], keep = up2 ? a[j + 2] : a[j];
        a[j] = keep + __shfl_xor_sync(0xffffffffu, send, 8);
      }
      const bool up3 = lane & 4;
      const float send = up3 ? a[0] : a[1], keep = up3 ? a[1] : a[0];
      a[0] = keep + __shfl_xor_sync(0xffffffffu, send, 4);
      a[0] += __shfl_xor_sync(0xffffffffu, a[0], 2);
      a[0] += __shfl_xor_sync(0xffffffffu, a[0], 1);
      if ((lane & 3) == 0) part[wid * 8 + (lane >> 2)] = a[0];
    }
    __syncthreads();
    if (wid == 0) {
      uint32_t bits = 0;
      if (lane < 24) {
        const int hc2 = lane >> 3, j = lane & 7;
        const float gt = rbf(part[(2 * hc2) * 8 + j] + part[(2 * hc2 + 1) * 8 + j]);
        const float up = rbf(part[(6 + 2 * hc2) * 8 + j] + part[(6 + 2 * hc2 + 1) * 8 + j]);
        const float sg = rbf(gt / (1.f + __expf(-gt)));
        bits = __bfloat16_as_ushort(__float2bfloat16_rn(sg * up));
      }
      const uint32_t nb = __shfl_down_sync(0xffffffffu, bits, 1);
      const uint32_t pw = bits | (nb << 16);
      const uint32_t w1 = __shfl_down_sync(0xffffffffu, pw, 2), w2 = __shfl_down_sync(0xffffffffu, pw, 4), w3 = __shfl_down_sync(0xffffffffu, pw, 6);
      const uint4 mine = enc4(make_uint4(pw, w1, w2, w3));
#pragma unroll
      for (int i = 0; i < 4; i++) {
        const int t = lane + 32 * i;
        const int cons = t / 3, ck = t - 3 * cons;
        uint4 v;
        v.x = __shfl_sync(0xffffffffu, mine.x, 8 * ck); v.y = __shfl_sync(0xffffffffu, mine.y, 8 * ck);
        v.z = __shfl_sync(0xffffffffu, mine.z, 8 * ck); v.w = __shfl_sync(0xffffffffu, mine.w, 8 * ck);
        if (t < 3 * N2) st_pub4(&g_act[cons][cta * 3 + ck], v);
      }
      __syncwarp();
      bar_arrive(7, 384);
    } else {
      bar_sync(7, 384);
    }
#pragma unroll
    for (int i = 0; i < 4; i++) if (i < 3 || tid < 128) g_y2[cta * 1280 + tid + NTHR * i] = make_uint4(0, 0, 0, 0);
    if (st_out) {
#pragma unroll
      for (int k = 0; k < 5; k++) outp[4 * k] = make_uint4(hreg[4 * k], hreg[4 * k + 1], hreg[4 * k + 2], hreg[4 * k + 3]);
    }
  } else if (cta < N1 + N2) {
    const int j2 = cta - N1;
    uint4 rowv = make_uint4(0, 0, 0, 0);
    if (tid < 192) {
      const uint4 v = poll4(&g_act[j2][tid]);
      float4* xp = reinterpret_cast<float4*>(xs + tid * 8);
      xp[0] = make_float4(lo_f(v.x), hi_f(v.x), lo_f(v.y), hi_f(v.y));
      xp[1] = make_float4(lo_f(v.z), hi_f(v.z), lo_f(v.w), hi_f(v.w));
    } else if (tid < 196) {
      const int t = tid - 192;
      rowv = poll4(&g_cand[wcta][t >> 1][j2 * 2 + (t & 1)]);
      reinterpret_cast<uint4*>(part + 256)[t] = rowv;
    }
    __syncthreads();
    const int hc = lane & 1;
    float a[8];
#pragma unroll
    for (int j = 0; j < 8; j++) a[j] = 0.f;
#pragma unroll
    for (int it = 0; it < 8; it++) {
      const float x = xs[rs + 192 * it];
#pragma unroll
      for (int j = 0; j < 8; j++) a[j] = fmaf(x, wf[it][j], a[j]);
    }
    {
      const bool up = lane & 16;
#pragma unroll
      for (int j = 0; j < 4; j++) {
        const float send = up ? a[j] : a[j + 4], keep = up ? a[j + 4] : a[j];
        a[j] = keep + __shfl_xor_sync(0xffffffffu, send, 16);
      }
      const bool up2 = lane & 8;
#pragma unroll
      for (int j = 0; j < 2; j++) {
        const float send = up2 ? a[j] : a[j + 2], keep = up2 ? a[j + 2] : a[j];
        a[j] = keep + __shfl_xor_sync(0xffffffffu, send, 8);
      }
      const bool up3 = lane & 4;
      const float send = up3 ? a[0] : a[1], keep = up3 ? a[1] : a[0];
      a[0] = keep + __shfl_xor_sync(0xffffffffu, send, 4);
      a[0] += __shfl_xor_sync(0xffffffffu, a[0], 2);
      if ((lane & 2) == 0) part[wid * 16 + hc * 8 + (lane >> 2)] = a[0];
    }
    __syncthreads();
    if (tid < 16) {
      float y = 0.f;
#pragma unroll
      for (int i = 0; i < 12; i++) y += part[i * 16 + tid];
      const uint32_t ord = win >> 16;
      const uint32_t rb = (ord & 0x8000u) ? (ord ^ 0x8000u) : (ord ^ 0xFFFFu);
      const float r = __uint_as_float(rb << 16);
      const float sg = rbf(1.f / (1.f + __expf(-r)));
      const float yy = rbf(rbf(y) * sg);
      const unsigned short* rv = reinterpret_cast<const unsigned short*>(part + 256);
      const float hn = __uint_as_float((uint32_t)rv[tid] << 16), h = __uint_as_float((uint32_t)rv[16 + tid] << 16);
      gout[(size_t)wrow * D_ + j2 * 16 + tid] = __float2bfloat16_rn(h + rbf(hn + yy));
    }
  }
}

}

typedef CUresult (*EncodeFn)(CUtensorMap*, CUtensorMapDataType, cuuint32_t, void*, const cuuint64_t*, const cuuint64_t*,
                             const cuuint32_t*, const cuuint32_t*, CUtensorMapInterleave, CUtensorMapSwizzle,
                             CUtensorMapL2promotion, CUtensorMapFloatOOBfill);

extern "C" void kernel_launch(void* const* d_in, const int* in_sizes, int n_in, void* d_out, int out_size) {
  (void)in_sizes; (void)n_in; (void)out_size;
  static EncodeFn encode = nullptr;
  static CUtensorMap tmg, tmu, tmd;
  static void* cached[3] = {nullptr, nullptr, nullptr};
  if (!encode) {
    cudaFuncSetAttribute(fused_kernel, cudaFuncAttributeMaxDynamicSharedMemorySize, (int)sizeof(Smem));
    void* fn = nullptr;
    cudaDriverEntryPointQueryResult qr;
    cudaGetDriverEntryPoint("cuTensorMapEncodeTiled", &fn, cudaEnableDefault, &qr);
    encode = (EncodeFn)fn;
  }
  if (cached[0] != d_in[8] || cached[1] != d_in[9] || cached[2] != d_in[10]) {
    const cuuint32_t es[2] = {1, 1};
    {
      const cuuint64_t dims[2] = {F_, D_}, strides[1] = {F_ * 2};
      const cuuint32_t box[2] = {24, 160};
      encode(&tmg, CU_TENSOR_MAP_DATA_TYPE_BFLOAT16, 2, d_in[8], dims, strides, box, es, CU_TENSOR_MAP_INTERLEAVE_NONE,
             CU_TENSOR_MAP_SWIZZLE_NONE, CU_TENSOR_MAP_L2_PROMOTION_NONE, CU_TENSOR_MAP_FLOAT_OOB_FILL_NONE);
      encode(&tmu, CU_TENSOR_MAP_DATA_TYPE_BFLOAT16, 2, d_in[9], dims, strides, box, es, CU_TENSOR_MAP_INTERLEAVE_NONE,
             CU_TENSOR_MAP_SWIZZLE_NONE, CU_TENSOR_MAP_L2_PROMOTION_NONE, CU_TENSOR_MAP_FLOAT_OOB_FILL_NONE);
    }
    {
      const cuuint64_t dims[2] = {D_, F_}, strides[1] = {D_ * 2};
      const cuuint32_t box[2] = {16, 256};
      encode(&tmd, CU_TENSOR_MAP_DATA_TYPE_BFLOAT16, 2, d_in[10], dims, strides, box, es, CU_TENSOR_MAP_INTERLEAVE_NONE,
             CU_TENSOR_MAP_SWIZZLE_NONE, CU_TENSOR_MAP_L2_PROMOTION_NONE, CU_TENSOR_MAP_FLOAT_OOB_FILL_NONE);
    }
    cached[0] = d_in[8]; cached[1] = d_in[9]; cached[2] = d_in[10];
  }
  fused_kernel<<<NCTA, NTHR, sizeof(Smem), cudaStreamPerThread>>>(
      tmg, tmu, tmd, (const bf16*)d_in[0], (const bf16*)d_in[1], (const bf16*)d_in[2], (const bf16*)d_in[3],
      (const bf16*)d_in[4], (const bf16*)d_in[5], (const bf16*)d_in[7], (bf16*)d_out);
}
```

```cpp
#include <cuda_runtime.h>
#include <cuda_bf16.h>
#include <cuda.h>
#include <stdint.h>

namespace {

typedef __nv_bfloat16 bf16;
typedef __nv_bfloat162 bf162;

constexpr int S_ = 2048, D_ = 640, F_ = 1536;
constexpr int NCTA = 128, CPC = 5, NTHR = 384;
constexpr int UPAD = 136, USTR = 2192;
constexpr int TABW = 1040;
constexpr int ZPB = 132;
constexpr int QSTR = 648;
constexpr int N1 = 64;
constexpr int N2 = 40;
constexpr int SPIN_LIMIT = 1 << 19;
constexpr int POLL_NS = 100;

struct __align__(128) Smem {
  uint32_t tabA[3][2][TABW];
  uint32_t extra[1024];
  uint32_t tabB[2][2][TABW];
  bf16 u[CPC][USTR];
  float z[2][4][ZPB * 16];
  bf16 q[16][QSTR];
  alignas(128) uint4 w[3840];
  uint4 wr[80];
  alignas(16) float2 st[16][4];
  alignas(16) float2 stq[16][4];
  alignas(16) float rp[16][4];
  unsigned long long mbar;
  unsigned long long mbarw;
  unsigned long long mbarc;
  unsigned long long mbary;
  unsigned long long mbarh;
  uint32_t target;
  uint32_t target2;
  uint32_t target3;
  uint32_t best;
  uint32_t win;
};

__device__ uint4 g_kv[D_ * S_ / 8];
__device__ uint4 g_y2[D_ * S_ / 8];
__device__ uint32_t g_keys[NCTA][NCTA];
__device__ uint4 g_cand[NCTA][2][80];
__device__ uint4 g_act[N2][F_ / 8];
__device__ __align__(256) unsigned int g_ctrs[3][64];
#define g_ctr g_ctrs[0][0]
#define g_ctr2 g_ctrs[1][0]
#define g_ctr3 g_ctrs[2][0]

__device__ __forceinline__ uint32_t smem_u32(const void* p) { return (uint32_t)__cvta_generic_to_shared(p); }
__device__ __forceinline__ void wg_fence() { asm volatile("wgmma.fence.sync.aligned;" ::: "memory"); }
__device__ __forceinline__ void wg_commit() { asm volatile("wgmma.commit_group.sync.aligned;" ::: "memory"); }
template <int N> __device__ __forceinline__ void wg_wait() { asm volatile("wgmma.wait_group.sync.aligned %0;" ::"n"(N) : "memory"); }
__device__ __forceinline__ void bar_sync(int id, int n) { asm volatile("bar.sync %0, %1;" ::"r"(id), "r"(n) : "memory"); }
__device__ __forceinline__ void bar_arrive(int id, int n) { asm volatile("bar.arrive %0, %1;" ::"r"(id), "r"(n) : "memory"); }
__device__ __forceinline__ bf162 u2b(uint32_t u) { return *reinterpret_cast<bf162*>(&u); }
__device__ __forceinline__ uint32_t b2u(bf162 b) { return *reinterpret_cast<uint32_t*>(&b); }
__device__ __forceinline__ float lo_f(uint32_t u) { return __uint_as_float(u << 16); }
__device__ __forceinline__ float hi_f(uint32_t u) { return __uint_as_float(u & 0xFFFF0000u); }
__device__ __forceinline__ float rbf(float x) { return __bfloat162float(__float2bfloat16_rn(x)); }
__device__ __forceinline__ uint32_t pack2(float a, float b) { return b2u(__floats2bfloat162_rn(a, b)); }
__device__ __forceinline__ uint32_t enc(uint32_t w) { return max(~w, 1u); }
__device__ __forceinline__ uint4 enc4(uint4 v) { return make_uint4(enc(v.x), enc(v.y), enc(v.z), enc(v.w)); }
__device__ __forceinline__ uint4 ld_poll4(const uint4* p) {
  uint4 v;
  asm volatile("ld.relaxed.gpu.global.v4.u32 {%0,%1,%2,%3}, [%4];" : "=r"(v.x), "=r"(v.y), "=r"(v.z), "=r"(v.w) : "l"(p) : "memory");
  return v;
}
__device__ __forceinline__ bool ready4(uint4 v) { return v.x != 0u && v.y != 0u && v.z != 0u && v.w != 0u; }
__device__ __forceinline__ uint4 poll4(const uint4* p) {
  uint4 v = ld_poll4(p);
  int it = 0;
  while (!ready4(v) && ++it < SPIN_LIMIT) v = ld_poll4(p);
  return make_uint4(~v.x, ~v.y, ~v.z, ~v.w);
}
__device__ __forceinline__ void st_pub4(uint4* p, uint4 v) {
  asm volatile("st.relaxed.gpu.global.v4.u32 [%0], {%1,%2,%3,%4};" ::"l"(p), "r"(v.x), "r"(v.y), "r"(v.z), "r"(v.w) : "memory");
}
__device__ __forceinline__ void st_pub2(uint2* p, uint32_t a, uint32_t b) {
  asm volatile("st.relaxed.gpu.global.v2.u32 [%0], {%1,%2};" ::"l"(p), "r"(a), "r"(b) : "memory");
}
__device__ __forceinline__ void mma_bf16(float (&c)[4], uint32_t a0, uint32_t a2, uint32_t b0, uint32_t b1) {
  asm volatile("mma.sync.aligned.m16n8k16.row.col.f32.bf16.bf16.f32 {%0,%1,%2,%3}, {%4,%5,%6,%5}, {%7,%8}, {%0,%1,%2,%3};"
               : "+f"(c[0]), "+f"(c[1]), "+f"(c[2]), "+f"(c[3]) : "r"(a0), "r"(0u), "r"(a2), "r"(b0), "r"(b1));
}
__device__ __forceinline__ void mbar_wait(const unsigned long long* bar) {
  const uint32_t mb = smem_u32(bar);
  uint32_t ok = 0;
  int it = 0;
  while (!ok && ++it < SPIN_LIMIT)
    asm volatile("{ .reg .pred p; mbarrier.try_wait.parity.shared.b64 p, [%1], 0; selp.u32 %0, 1, 0, p; }" : "=r"(ok) : "r"(mb) : "memory");
}
__device__ __forceinline__ void bulk_g2s(void* dst, const void* src, uint32_t bytes, const unsigned long long* bar) {
  asm volatile("cp.async.bulk.shared::cluster.global.mbarrier::complete_tx::bytes [%0], [%1], %2, [%3];" ::"r"(smem_u32(dst)),
               "l"(src), "r"(bytes), "r"(smem_u32(bar)) : "memory");
}
__device__ __forceinline__ void mbar_expect(const unsigned long long* bar, uint32_t bytes) {
  asm volatile("mbarrier.arrive.expect_tx.shared.b64 _, [%0], %1;" ::"r"(smem_u32(bar)), "r"(bytes) : "memory");
}
__device__ __forceinline__ void mma_bf16x(float (&c)[4], uint32_t a0, uint32_t a1, uint32_t a2, uint32_t a3, uint32_t b0, uint32_t b1) {
  asm volatile("mma.sync.aligned.m16n8k16.row.col.f32.bf16.bf16.f32 {%0,%1,%2,%3}, {%4,%5,%6,%7}, {%8,%9}, {%0,%1,%2,%3};"
               : "+f"(c[0]), "+f"(c[1]), "+f"(c[2]), "+f"(c[3]) : "r"(a0), "r"(a1), "r"(a2), "r"(a3), "r"(b0), "r"(b1));
}
__device__ __forceinline__ float fdivr(float a, float d, float r) {
  float q = a * r;
  float e = fmaf(-q, d, a);
  return fmaf(e, r, q);
}

template <bool FIRST> __device__ __forceinline__ void wgmma32(float (&d)[16], const uint32_t* a, uint64_t desc) {
  if (FIRST) {
    asm volatile("wgmma.mma_async.sync.aligned.m64n32k16.f32.bf16.bf16 {%0,%1,%2,%3,%4,%5,%6,%7,%8,%9,%10,%11,%12,%13,%14,%15}, {%16,%17,%18,%19}, %20, 0, 1, 1, 0;"
                 : "+f"(d[0]), "+f"(d[1]), "+f"(d[2]), "+f"(d[3]), "+f"(d[4]), "+f"(d[5]), "+f"(d[6]), "+f"(d[7]),
                   "+f"(d[8]), "+f"(d[9]), "+f"(d[10]), "+f"(d[11]), "+f"(d[12]), "+f"(d[13]), "+f"(d[14]), "+f"(d[15])
                 : "r"(a[0]), "r"(a[1]), "r"(a[2]), "r"(a[3]), "l"(desc));
  } else {
    asm volatile("wgmma.mma_async.sync.aligned.m64n32k16.f32.bf16.bf16 {%0,%1,%2,%3,%4,%5,%6,%7,%8,%9,%10,%11,%12,%13,%14,%15}, {%16,%17,%18,%19}, %20, 1, 1, 1, 0;"
                 : "+f"(d[0]), "+f"(d[1]), "+f"(d[2]), "+f"(d[3]), "+f"(d[4]), "+f"(d[5]), "+f"(d[6]), "+f"(d[7]),
                   "+f"(d[8]), "+f"(d[9]), "+f"(d[10]), "+f"(d[11]), "+f"(d[12]), "+f"(d[13]), "+f"(d[14]), "+f"(d[15])
                 : "r"(a[0]), "r"(a[1]), "r"(a[2]), "r"(a[3]), "l"(desc));
  }
}

template <int G> __device__ __forceinline__ void load_a(uint32_t (&a)[8], const uint32_t* tp) {
#pragma unroll
  for (int q = 0; q < 2; q++) {
    const int e = 2 * G + q;
    a[4 * q + 0] = tp[-64 * e];
    a[4 * q + 1] = tp[-64 * e - 32];
    a[4 * q + 2] = tp[-64 * e + 4];
    a[4 * q + 3] = tp[-64 * e - 28];
  }
}
__device__ __forceinline__ void load_a_all(uint32_t (&a)[8][8], const uint32_t* tp) {
  load_a<0>(a[0], tp); load_a<1>(a[1], tp); load_a<2>(a[2], tp); load_a<3>(a[3], tp);
  load_a<4>(a[4], tp); load_a<5>(a[5], tp); load_a<6>(a[6], tp); load_a<7>(a[7], tp);
}
template <int G> __device__ __forceinline__ void issue_g(float (&acc)[8][16], uint32_t (&a)[8], uint64_t desc0) {
  wg_fence();
#pragma unroll
  for (int q = 0; q < 2; q++) {
#pragma unroll
    for (int b = G; b < 8; b++) {
      const int delta = 2 * b - (2 * G + q);
      if (G == 0 && q == 0) wgmma32<true>(acc[b], &a[4 * q], desc0 + (uint64_t)(int64_t)(16 * delta));
      else wgmma32<false>(acc[b], &a[4 * q], desc0 + (uint64_t)(int64_t)(16 * delta));
    }
  }
  wg_commit();
}
template <int B> __device__ __forceinline__ void fence_blk(float (&acc)[8][16]) {
#pragma unroll
  for (int i = 0; i < 16; i++) asm volatile("" : "+f"(acc[B][i])::"memory");
}
__device__ __forceinline__ void fence_a(uint32_t (&a)[8]) {
#pragma unroll
  for (int i = 0; i < 8; i++) asm volatile("" : "+r"(a[i])::"memory");
}
template <int B> __device__ __forceinline__ void sts_blk(float (&acc)[8][16], float* zw, int off_even, int off_odd) {
#pragma unroll
  for (int jj = 0; jj < 4; jj++) {
    const int j = 4 * B + jj;
    float p0 = acc[B][4 * jj + 0], p1 = acc[B][4 * jj + 1];
    if (jj > 0) { p0 += acc[B][4 * (jj - 1) + 2]; p1 += acc[B][4 * (jj - 1) + 3]; }
    else if (B > 0) { p0 += acc[B > 0 ? B - 1 : 0][14]; p1 += acc[B > 0 ? B - 1 : 0][15]; }
    zw[64 * j + off_even] = p0;
    zw[64 * j + off_odd] = p1;
  }
}
__device__ __forceinline__ int tab_off(int c) { return c == 4 ? 0 : (c + 1) * 2 * TABW + (c >= 2 ? 1024 : 0); }
__device__ __forceinline__ int tile_perm(int ch) { return ch ^ (((ch >> 3) & 3) << 1); }

__device__ __forceinline__ void wait_ctr(const unsigned int* ctr, uint32_t target) {
  uint32_t v;
  int it = 0;
  do {
    asm volatile("ld.acquire.gpu.global.u32 %0, [%1];" : "=r"(v) : "l"(ctr) : "memory");
  } while ((int)(v - target) < 0 && ++it < SPIN_LIMIT);
}

__device__ __forceinline__ float2 row_part_stats(const uint32_t (&x)[20]) {
  float cs[5][4];
#pragma unroll
  for (int k = 0; k < 5; k++) {
    cs[k][0] = cs[k][1] = cs[k][2] = cs[k][3] = 0.f;
    mma_bf16x(cs[k], x[4 * k + 0], x[4 * k + 2], x[4 * k + 1], x[4 * k + 3], 0x3F803F80u, 0x3F803F80u);
  }
  const float mean = ((((cs[0][0] + cs[0][2]) + (cs[1][0] + cs[1][2])) + ((cs[2][0] + cs[2][2]) + (cs[3][0] + cs[3][2]))) + (cs[4][0] + cs[4][2])) * (1.f / 160.f);
  float m2a = 0.f, m2b = 0.f, m2c = 0.f, m2d = 0.f;
#pragma unroll
  for (int i = 0; i < 20; i += 2) {
    const float a = lo_f(x[i]) - mean, b = hi_f(x[i]) - mean, c = lo_f(x[i + 1]) - mean, d = hi_f(x[i + 1]) - mean;
    m2a = fmaf(a, a, m2a); m2b = fmaf(b, b, m2b); m2c = fmaf(c, c, m2c); m2d = fmaf(d, d, m2d);
  }
  float m2 = (m2a + m2b) + (m2c + m2d);
  m2 += __shfl_xor_sync(0xffffffffu, m2, 1);
  m2 += __shfl_xor_sync(0xffffffffu, m2, 2);
  return make_float2(mean, m2);
}
template <bool EXACT> __device__ __forceinline__ void row_normalize(const float4* st, const uint32_t (&x)[20], uint32_t (&y)[20]) {
  const float4 p = st[0], q = st[1];
  const float mean = ((p.x + p.z) + (q.x + q.z)) * 0.25f;
  const float d0 = p.x - mean, d1 = p.z - mean, d2 = q.x - mean, d3 = q.z - mean;
  const float m2 = ((p.y + p.w) + (q.y + q.w)) + 160.f * ((d0 * d0 + d1 * d1) + (d2 * d2 + d3 * d3));
  const float hd = rbf(sqrtf(rbf(rbf(m2 * (1.f / D_)) + 1e-5f)));
  const float hr = __frcp_rn(hd);
  const bf162 hm2 = __float2bfloat162_rn(mean);
#pragma unroll
  for (int i = 0; i < 20; i++) {
    const uint32_t d = b2u(__hsub2_rn(u2b(x[i]), hm2));
    y[i] = EXACT ? pack2(fdivr(lo_f(d), hd, hr), fdivr(hi_f(d), hd, hr)) : pack2(lo_f(d) * hr, hi_f(d) * hr);
  }
}

__device__ __forceinline__ void gather_kv(Smem& sm, int c0, int tid) {
  mbar_wait(&sm.mbarc);
  uint4 v[4];
  uint4* src = g_kv + c0 * 256 + tid;
#pragma unroll
  for (int i = 0; i < 4; i++) if (i < 3 || tid >= 256) v[i] = ld_poll4(src + NTHR * i - (i == 3 ? 256 : 0));
#pragma unroll
  for (int i = 0; i < 4; i++) {
    if (i < 3 || tid >= 256) {
      const int t = tid + NTHR * i - (i == 3 ? 256 : 0);
      int it = 0;
      while (!ready4(v[i]) && ++it < SPIN_LIMIT) { __nanosleep(POLL_NS); v[i] = ld_poll4(g_kv + c0 * 256 + t); }
      *reinterpret_cast<uint4*>(&sm.u[t >> 8][UPAD + (t & 255) * 8]) = make_uint4(~v[i].x, ~v[i].y, ~v[i].z, ~v[i].w);
    }
  }
  asm volatile("fence.proxy.async.shared::cta;" ::: "memory");
  __syncthreads();
}

__global__ void __launch_bounds__(NTHR, 1)
fused_kernel(const __grid_constant__ CUtensorMap tmg, const __grid_constant__ CUtensorMap tmu,
             const __grid_constant__ CUtensorMap tmd, const bf16* __restrict__ gq, const bf16* __restrict__ gk, const bf16* __restrict__ gv,
             const bf16* __restrict__ gsk, const bf16* __restrict__ gh, const bf16* __restrict__ gD,
             const bf16* __restrict__ gwr, bf16* __restrict__ gout) {
  extern __shared__ __align__(128) unsigned char smraw[];
  Smem& sm = *reinterpret_cast<Smem*>(smraw);
  const int tid = threadIdx.x;
  const int cta = blockIdx.x;
  const int c0 = cta * CPC;
  const int lane = tid & 31;
  const int wid = tid >> 5;

  {
    uint4* hs = reinterpret_cast<uint4*>(&sm.z[0][0][0]);
    const int oc = tid >> 2;
    const int r0 = cta * 16 + (tid & 3) * 4;
    uint4 kk[7], vv[4], sk[4];
    if (tid < 320) {
      const uint4* kp = reinterpret_cast<const uint4*>(gk) + (size_t)r0 * 80 + oc;
      const uint4* vp = reinterpret_cast<const uint4*>(gv) + (size_t)r0 * 80 + oc;
#pragma unroll
      for (int i = 0; i < 4; i++) sk[i] = __ldg(reinterpret_cast<const uint4*>(gsk) + oc * 4 + i);
#pragma unroll
      for (int i = 0; i < 7; i++) kk[i] = (i >= 3 || r0 > 0) ? __ldg(kp + (i - 3) * 80) : make_uint4(0, 0, 0, 0);
#pragma unroll
      for (int i = 0; i < 4; i++) vv[i] = __ldg(vp + i * 80);
    } else if (tid == 320) {
      asm volatile("mbarrier.init.shared.b64 [%0], 1;" ::"r"(smem_u32(&sm.mbarh)) : "memory");
      asm volatile("mbarrier.init.shared.b64 [%0], 1;" ::"r"(smem_u32(&sm.mbar)) : "memory");
      asm volatile("mbarrier.init.shared.b64 [%0], 1;" ::"r"(smem_u32(&sm.mbarw)) : "memory");
      asm volatile("mbarrier.init.shared.b64 [%0], 1;" ::"r"(smem_u32(&sm.mbarc)) : "memory");
      asm volatile("mbarrier.init.shared.b64 [%0], 1;" ::"r"(smem_u32(&sm.mbary)) : "memory");
      asm volatile("fence.proxy.async.shared::cta;" ::: "memory");
    } else if (tid == 352) {
      uint32_t v1, v2, v3;
      asm volatile("ld.relaxed.gpu.global.u32 %0, [%1];" : "=r"(v1) : "l"(&g_ctr) : "memory");
      asm volatile("ld.relaxed.gpu.global.u32 %0, [%1];" : "=r"(v2) : "l"(&g_ctr2) : "memory");
      asm volatile("ld.relaxed.gpu.global.u32 %0, [%1];" : "=r"(v3) : "l"(&g_ctr3) : "memory");
      sm.target = (v1 / NCTA + 1u) * NCTA;
      sm.target2 = (v2 / NCTA + 1u) * NCTA;
      sm.target3 = (v3 / NCTA + 1u) * NCTA;
    }
    if (tid < 320) bar_sync(6, 384); else { bar_arrive(6, 384); bar_sync(5, 64); }
    if (tid < 320) {
      uint32_t o[4][4];
#pragma unroll
      for (int p = 0; p < 4; p++) {
        const bf162 w0 = u2b(__byte_perm(sk[p].x, sk[p].z, 0x5410)), w1 = u2b(__byte_perm(sk[p].x, sk[p].z, 0x7632));
        const bf162 w2 = u2b(__byte_perm(sk[p].y, sk[p].w, 0x5410)), w3 = u2b(__byte_perm(sk[p].y, sk[p].w, 0x7632));
        uint32_t kv[4];
#pragma unroll
        for (int i = 0; i < 4; i++) {
          const uint32_t k0 = p == 0 ? kk[i].x : p == 1 ? kk[i].y : p == 2 ? kk[i].z : kk[i].w;
          const uint32_t k1 = p == 0 ? kk[i + 1].x : p == 1 ? kk[i + 1].y : p == 2 ? kk[i + 1].z : kk[i + 1].w;
          const uint32_t k2 = p == 0 ? kk[i + 2].x : p == 1 ? kk[i + 2].y : p == 2 ? kk[i + 2].z : kk[i + 2].w;
          const uint32_t k3 = p == 0 ? kk[i + 3].x : p == 1 ? kk[i + 3].y : p == 2 ? kk[i + 3].z : kk[i + 3].w;
          const uint32_t vx = p == 0 ? vv[i].x : p == 1 ? vv[i].y : p == 2 ? vv[i].z : vv[i].w;
          bf162 a = __hmul2_rn(u2b(k0), w3);
          a = __hadd2_rn(a, __hmul2_rn(u2b(k1), w2));
          a = __hadd2_rn(a, __hmul2_rn(u2b(k2), w1));
          a = __hadd2_rn(a, __hmul2_rn(u2b(k3), w0));
          kv[i] = b2u(__hmul2_rn(a, u2b(vx)));
        }
        o[p][0] = enc(__byte_perm(kv[0], kv[1], 0x5410)); o[p][1] = enc(__byte_perm(kv[2], kv[3], 0x5410));
        o[p][2] = enc(__byte_perm(kv[0], kv[1], 0x7632)); o[p][3] = enc(__byte_perm(kv[2], kv[3], 0x7632));
      }
      uint2* dst = reinterpret_cast<uint2*>(g_kv) + (size_t)(oc * 8) * 512 + (r0 >> 2);
#pragma unroll
      for (int p = 0; p < 4; p++) {
        st_pub2(dst + (2 * p) * 512, o[p][0], o[p][1]);
        st_pub2(dst + (2 * p + 1) * 512, o[p][2], o[p][3]);
      }
      if (wid == 0) bar_sync(4, 320); else bar_arrive(4, 320);
      if (tid == 0) {
        asm volatile("red.relaxed.gpu.global.add.u32 [%0], 1;" ::"l"(&g_ctr2) : "memory");
      }
      __syncwarp();
    } else {
      const int t0 = tid - 320;
      const uint4 zz = make_uint4(0, 0, 0, 0);
      if (tid == 320) {
        mbar_expect(&sm.mbarh, CPC * S_ * 2);
        bulk_g2s(hs, gh + (size_t)c0 * S_, CPC * S_ * 2, &sm.mbarh);
      }
      __syncwarp();
      for (int t = t0; t < CPC * 17; t += 64) *reinterpret_cast<uint4*>(&sm.u[t / 17][(t % 17) * 8]) = zz;
      if (t0 < 40) *reinterpret_cast<uint4*>(&sm.tabA[0][0][0] + tab_off(t0 >> 3) + ((t0 >> 2) & 1) * TABW + 1024 + 4 * (t0 & 3)) = zz;
      (&g_cand[cta][0][0])[t0] = zz;
      (&g_cand[cta][0][0])[64 + t0] = zz;
      if (t0 < 32) (&g_cand[cta][0][0])[128 + t0] = zz;
      else reinterpret_cast<uint4*>(&g_keys[cta][0])[t0 - 32] = zz;
      if (cta >= N1 && cta < N1 + N2) {
#pragma unroll
        for (int i = 0; i < 3; i++) g_act[cta - N1][t0 + 64 * i] = zz;
      }
    }
    mbar_wait(&sm.mbarh);
#pragma unroll
    for (int i = 0; i < 4; i++) {
      const int t = (NTHR - 1 - tid) + NTHR * i;
      if (t < CPC * 256) {
        uint32_t* tb = &sm.tabA[0][0][0] + tab_off(t >> 8) + (255 - (t & 255)) * 4;
        const uint4 h = hs[t];
        const uint32_t hp = (t & 255) ? reinterpret_cast<const uint32_t*>(hs)[4 * t - 1] : 0u;
        uint4 r1, rr;
        r1.x = __byte_perm(h.w, 0, 0x1032); r1.y = __byte_perm(h.z, 0, 0x1032);
        r1.z = __byte_perm(h.y, 0, 0x1032); r1.w = __byte_perm(h.x, 0, 0x1032);
        rr.x = __byte_perm(h.w, h.z, 0x7610); rr.y = __byte_perm(h.z, h.y, 0x7610);
        rr.z = __byte_perm(h.y, h.x, 0x7610); rr.w = __byte_perm(h.x, hp, 0x7610);
        *reinterpret_cast<uint4*>(tb) = rr;
        *reinterpret_cast<uint4*>(tb + TABW) = r1;
      }
    }
  }
  __syncthreads();

  const int wg = __shfl_sync(0xffffffffu, tid >> 7, 0);
  const int wtid = tid & 127;
  uint4* tile = reinterpret_cast<uint4*>(&sm.tabB[0][0][0]);
  if (wg < 2) {
    asm volatile("setmaxnreg.inc.sync.aligned.u32 224;");
    const int w = (tid >> 5) & 3, g = lane >> 2, tq = lane & 3;
    float* zw = sm.z[wg][w];
    const int sw = 3 * (((tq + w) >> 1) & 1);
    const int off_even = 16 * (tq + w) + 4 * ((0 + (g >> 2)) ^ sw) + (g & 3);
    const int off_odd = 16 * (tq + w) + 4 * ((2 + (g >> 2)) ^ sw) + (g & 3);
    uint32_t a[8][8];
    const uint32_t* tp0 = &sm.tabA[0][g & 1][1019 - 8 * w - (g >> 1) + tq];
    load_a_all(a, tp0 + tab_off(wg));
    float acc[8][16];
#pragma unroll
    for (int b = 0; b < 8; b++)
#pragma unroll
      for (int i = 0; i < 16; i++) acc[b][i] = 0.f;
    gather_kv(sm, c0, tid);
#pragma unroll 1
    for (int c = wg; c < CPC; c += 2) {
      const uint64_t desc = (uint64_t)((smem_u32(&sm.u[c][UPAD - 8]) & 0x3FFFF) >> 4) | ((uint64_t)1 << 16) | ((uint64_t)8 << 32);
      if (c > 0) bar_sync(1 + wg, 256);
      issue_g<0>(acc, a[0], desc);
      issue_g<1>(acc, a[1], desc);
      issue_g<2>(acc, a[2], desc);
      issue_g<3>(acc, a[3], desc);
      issue_g<4>(acc, a[4], desc);
      issue_g<5>(acc, a[5], desc);
      if (c + 1 < CPC) bar_arrive(1 + (wg ^ 1), 256);
      issue_g<6>(acc, a[6], desc);
      issue_g<7>(acc, a[7], desc);
      if (c >= 2) bar_sync(5 + wg, 256);
      wg_wait<4>();
      fence_blk<0>(acc); fence_blk<1>(acc); fence_blk<2>(acc); fence_blk<3>(acc);
      sts_blk<0>(acc, zw, off_even, off_odd);
      sts_blk<1>(acc, zw, off_even, off_odd);
      sts_blk<2>(acc, zw, off_even, off_odd);
      sts_blk<3>(acc, zw, off_even, off_odd);
      bar_arrive(9 + wg, 256);
      wg_wait<0>();
      fence_blk<4>(acc); fence_blk<5>(acc); fence_blk<6>(acc); fence_blk<7>(acc);
#pragma unroll
      for (int i = 0; i < 8; i++) fence_a(a[i]);
      sts_blk<4>(acc, zw, off_even, off_odd);
      sts_blk<5>(acc, zw, off_even, off_odd);
      sts_blk<6>(acc, zw, off_even, off_odd);
      sts_blk<7>(acc, zw, off_even, off_odd);
      bar_arrive(3 + wg, 256);
      if (c + 2 < CPC) load_a_all(a, tp0 + tab_off(c + 2));
    }
    asm volatile("setmaxnreg.dec.sync.aligned.u32 168;");
  } else {
    asm volatile("setmaxnreg.dec.sync.aligned.u32 56;");
    if (((wtid & 15) >> 2) < ((wtid >> 4) & 3))
      *reinterpret_cast<uint4*>(&sm.z[wtid >> 6][(wtid >> 4) & 3][(wtid & 15) * 4]) = make_uint4(0, 0, 0, 0);
    if (wtid == 96) {
      __threadfence();
      asm volatile("red.relaxed.gpu.global.add.u32 [%0], 1;" ::"l"(&g_ctr) : "memory");
    }
    if (wtid == 64) {
      const unsigned target = sm.target2;
      uint32_t v;
      int it = 0;
      do {
        asm volatile("ld.relaxed.gpu.global.u32 %0, [%1];" : "=r"(v) : "l"(&g_ctr2) : "memory");
      } while ((int)(v - target) < 0 && ++it < SPIN_LIMIT);
      asm volatile("mbarrier.arrive.shared.b64 _, [%0];" ::"r"(smem_u32(&sm.mbarc)) : "memory");
    }
    __syncwarp();
    gather_kv(sm, c0, tid);
#pragma unroll
    for (int i = 0; i < 10; i++) g_kv[c0 * 256 + wtid + 128 * i] = make_uint4(0, 0, 0, 0);
    if (wtid == 96) wait_ctr(&g_ctr, sm.target);
    __syncwarp();
    if (wtid == 32) {
      const uint32_t mw = smem_u32(&sm.mbarw);
      mbar_expect(&sm.mbar, 17 * D_ * 2);
#pragma unroll 1
      for (int r = 0; r < 16; r++) bulk_g2s(&sm.q[r][0], gq + (size_t)(cta * 16 + r) * D_, D_ * 2, &sm.mbar);
      bulk_g2s(&sm.wr[0], gwr, D_ * 2, &sm.mbar);
      if (cta < N1) {
        asm volatile("mbarrier.arrive.expect_tx.shared.b64 _, [%0], %1;" ::"r"(mw), "r"(3840 * 16) : "memory");
#pragma unroll 1
        for (int i = 0; i < 4; i++) {
          asm volatile("cp.async.bulk.tensor.2d.shared::cluster.global.mbarrier::complete_tx::bytes [%0], [%1, {%3, %4}], [%2];" ::"r"(smem_u32(&sm.w[i * 480])),
                       "l"(&tmg), "r"(mw), "r"(cta * 24), "r"(i * 160) : "memory");
          asm volatile("cp.async.bulk.tensor.2d.shared::cluster.global.mbarrier::complete_tx::bytes [%0], [%1, {%3, %4}], [%2];" ::"r"(smem_u32(&sm.w[1920 + i * 480])),
                       "l"(&tmu), "r"(mw), "r"(cta * 24), "r"(i * 160) : "memory");
        }
      } else if (cta < N1 + N2) {
        asm volatile("mbarrier.arrive.expect_tx.shared.b64 _, [%0], %1;" ::"r"(mw), "r"(3072 * 16) : "memory");
#pragma unroll 1
        for (int i = 0; i < 6; i++)
          asm volatile("cp.async.bulk.tensor.2d.shared::cluster.global.mbarrier::complete_tx::bytes [%0], [%1, {%3, %4}], [%2];" ::"r"(smem_u32(&sm.w[i * 512])),
                       "l"(&tmd), "r"(mw), "r"((cta - N1) * 16), "r"(i * 256) : "memory");
      }
    }
    const int rpb = wtid >> 1, re2 = wtid & 1;
    const int rsw = 3 * ((rpb >> 1) & 1);
    const int roff0 = 16 * rpb + 4 * ((2 * re2 + 0) ^ rsw);
    const int roff1 = 16 * rpb + 4 * ((2 * re2 + 1) ^ rsw);
    const uint32_t dvl = reinterpret_cast<const unsigned short*>(gD)[c0 + (lane < CPC ? lane : 0)];
#pragma unroll 1
    for (int c = 0; c < CPC; c++) {
      const int zg = c & 1;
      const uint32_t dvc = __shfl_sync(0xffffffffu, dvl, c);
      const bf162 d2 = u2b(dvc | (dvc << 16));
#pragma unroll
      for (int half = 0; half < 2; half++) {
        bar_sync((half ? 3 : 9) + zg, 256);
        const float* zb = sm.z[zg][0] + half * 1024;
        float4 x[4][2];
#pragma unroll
        for (int ww = 0; ww < 4; ww++) {
          x[ww][0] = *reinterpret_cast<const float4*>(zb + ww * ZPB * 16 + roff0);
          x[ww][1] = *reinterpret_cast<const float4*>(zb + ww * ZPB * 16 + roff1);
        }
        const int sidx = half * 1024 + wtid * 8;
        const uint4 kvv = *reinterpret_cast<const uint4*>(&sm.u[c][UPAD + sidx]);
        if (half == 1 && c + 2 < CPC) bar_arrive(5 + zg, 256);
        uint4 o;
        o.x = pack2((x[0][0].x + x[1][0].x) + (x[2][0].x + x[3][0].x), (x[0][0].y + x[1][0].y) + (x[2][0].y + x[3][0].y));
        o.y = pack2((x[0][0].z + x[1][0].z) + (x[2][0].z + x[3][0].z), (x[0][0].w + x[1][0].w) + (x[2][0].w + x[3][0].w));
        o.z = pack2((x[0][1].x + x[1][1].x) + (x[2][1].x + x[3][1].x), (x[0][1].y + x[1][1].y) + (x[2][1].y + x[3][1].y));
        o.w = pack2((x[0][1].z + x[1][1].z) + (x[2][1].z + x[3][1].z), (x[0][1].w + x[1][1].w) + (x[2][1].w + x[3][1].w));
        o.x = b2u(__hadd2_rn(u2b(o.x), __hmul2_rn(u2b(kvv.x), d2)));
        o.y = b2u(__hadd2_rn(u2b(o.y), __hmul2_rn(u2b(kvv.y), d2)));
        o.z = b2u(__hadd2_rn(u2b(o.z), __hmul2_rn(u2b(kvv.z), d2)));
        o.w = b2u(__hadd2_rn(u2b(o.w), __hmul2_rn(u2b(kvv.w), d2)));
        st_pub4(g_y2 + ((64 * half + rpb) * 640 + c0 + c) * 2 + re2, enc4(o));
      }
    }
    if (wid == 11) bar_sync(8, 128); else bar_arrive(8, 128);
    asm volatile("setmaxnreg.inc.sync.aligned.u32 168;");
  }

  if (tid == 352) {
    asm volatile("red.relaxed.gpu.global.add.u32 [%0], 1;" ::"l"(&g_ctr3) : "memory");
    wait_ctr(&g_ctr3, sm.target3);
    asm volatile("mbarrier.arrive.shared.b64 _, [%0];" ::"r"(smem_u32(&sm.mbary)) : "memory");
  }
  __syncwarp();
  const int g = lane >> 2, tq = lane & 3;
  const int hh = wid & 1, gqi = wid >> 1;
  const int row = hh * 8 + g;
  uint32_t hreg[20], hnreg[20];
  {
    const uint4* src = g_y2 + cta * 1280 + tid;
    uint4 v[4];
    if (wid < 8) {
      mbar_wait(&sm.mbar);
#pragma unroll
      for (int k = 0; k < 5; k++) {
        const uint4 qv4 = *reinterpret_cast<const uint4*>(&sm.q[row][32 * (5 * gqi + k) + 8 * tq]);
        hreg[4 * k] = qv4.x; hreg[4 * k + 1] = qv4.y; hreg[4 * k + 2] = qv4.z; hreg[4 * k + 3] = qv4.w;
      }
      const float2 ps = row_part_stats(hreg);
      if (tq == 0) sm.stq[row][gqi] = ps;
      bar_sync(7, 256);
      row_normalize<false>(reinterpret_cast<const float4*>(sm.stq[row]), hreg, hnreg);
    }
    mbar_wait(&sm.mbary);
#pragma unroll
    for (int i = 0; i < 4; i++) if (i < 3 || tid < 128) v[i] = ld_poll4(src + NTHR * i);
    int it = 0;
    bool all;
    do {
      all = true;
#pragma unroll
      for (int i = 0; i < 4; i++)
        if ((i < 3 || tid < 128) && !ready4(v[i])) { v[i] = ld_poll4(src + NTHR * i); all = false; }
    } while (!all && ++it < SPIN_LIMIT);
#pragma unroll
    for (int i = 0; i < 4; i++) {
      if (i < 3 || tid < 128) {
        const int t = tid + NTHR * i;
        tile[(t & 1) * 640 + tile_perm(t >> 1)] = make_uint4(~v[i].x, ~v[i].y, ~v[i].z, ~v[i].w);
      }
    }
  }
  __syncthreads();

  if (wid < 8) {
#pragma unroll
    for (int k = 0; k < 5; k++) {
      const int base = 32 * (5 * gqi + k);
      const int lch = base + 8 * ((lane & 7) >> 1) + 2 * (lane >> 3) + (lane & 1);
      uint32_t y[4];
      asm volatile("ldmatrix.sync.aligned.m8n8.x4.trans.shared.b16 {%0,%1,%2,%3}, [%4];"
                   : "=r"(y[0]), "=r"(y[1]), "=r"(y[2]), "=r"(y[3]) : "r"(smem_u32(&tile[hh * 640 + tile_perm(lch)])) : "memory");
#pragma unroll
      for (int i = 0; i < 4; i++)
        hreg[4 * k + i] = b2u(__hadd2_rn(u2b(hreg[4 * k + i]), __hmul2_rn(u2b(hnreg[4 * k + i]), u2b(y[i]))));
    }
    const float2 ps = row_part_stats(hreg);
    if (tq == 0) sm.st[row][gqi] = ps;
    bar_sync(7, 256);
    row_normalize<false>(reinterpret_cast<const float4*>(sm.st[row]), hreg, hnreg);
    float cr[5][4];
#pragma unroll
    for (int k = 0; k < 5; k++) {
      cr[k][0] = cr[k][1] = cr[k][2] = cr[k][3] = 0.f;
      const uint4 w4 = sm.wr[4 * (5 * gqi + k) + tq];
      mma_bf16(cr[k], hnreg[4 * k + 0], hnreg[4 * k + 1], w4.x, w4.y);
      mma_bf16(cr[k], hnreg[4 * k + 2], hnreg[4 * k + 3], w4.z, w4.w);
    }
    if (tq == 0) sm.rp[row][gqi] = ((cr[0][0] + cr[1][0]) + (cr[2][0] + cr[3][0])) + cr[4][0];
  }
  __syncthreads();
  uint32_t best;
  {
    const int rr = lane & 15;
    const float4 rp4 = *reinterpret_cast<const float4*>(sm.rp[rr]);
    const float r = (rp4.x + rp4.y) + (rp4.z + rp4.w);
    const uint32_t bits = __bfloat16_as_ushort(__float2bfloat16_rn(r));
    const uint32_t ord = (bits & 0x8000u) ? (bits ^ 0xFFFFu) : (bits ^ 0x8000u);
    const uint32_t key = (ord << 16) | 0x8000u | (uint32_t)(2047 - (cta * 16 + rr));
    best = __reduce_max_sync(0xffffffffu, key);
  }
  if (wid >= 8) asm volatile("st.relaxed.gpu.global.u32 [%0], %1;" ::"l"(&g_keys[tid - 256][cta]), "r"(best) : "memory");
  const int brow = (2047 - (int)(best & 0x7FFu)) - cta * 16;
  if (wid < 8 && row == brow) {
#pragma unroll
    for (int k = 0; k < 5; k++)
      st_pub4(&g_cand[cta][0][4 * (5 * gqi + k) + tq], enc4(make_uint4(hnreg[4 * k], hnreg[4 * k + 1], hnreg[4 * k + 2], hnreg[4 * k + 3])));
#pragma unroll
    for (int k = 0; k < 5; k++)
      st_pub4(&g_cand[cta][1][4 * (5 * gqi + k) + tq], enc4(make_uint4(hreg[4 * k], hreg[4 * k + 1], hreg[4 * k + 2], hreg[4 * k + 3])));
  }
#pragma unroll
  for (int i = 0; i < 20; i++) hreg[i] = b2u(__hadd2_rn(u2b(hreg[i]), u2b(hnreg[i])));
  float wf[10][8];
  const int rs = cta < N1 ? (wid & 1) * 32 + lane : wid * 16 + (lane >> 1);
  if (cta < N1 + N2) {
    mbar_wait(&sm.mbarw);
    const uint4* wp = cta < N1 ? &sm.w[(wid / 6) * 1920 + rs * 3 + ((wid % 6) >> 1)] : &sm.w[rs * 2 + (lane & 1)];
    const int wstep = cta < N1 ? 192 : 384;
#pragma unroll
    for (int it = 0; it < 10; it++) {
      const uint4 wv = wp[(it < 8 || cta < N1) ? it * wstep : 0];
      wf[it][0] = lo_f(wv.x); wf[it][1] = hi_f(wv.x); wf[it][2] = lo_f(wv.y); wf[it][3] = hi_f(wv.y);
      wf[it][4] = lo_f(wv.z); wf[it][5] = hi_f(wv.z); wf[it][6] = lo_f(wv.w); wf[it][7] = hi_f(wv.w);
    }
#pragma unroll
    for (int it = 0; it < 10; it++)
#pragma unroll
      for (int j = 0; j < 8; j++) asm volatile("" : "+f"(wf[it][j]));
  }
  if (wid == 11) {
    const uint4* kp = reinterpret_cast<const uint4*>(&g_keys[cta][0]) + lane;
    uint4 v = ld_poll4(kp);
    int it = 0;
    while (!ready4(v) && ++it < SPIN_LIMIT) v = ld_poll4(kp);
    const uint32_t m = max(max(v.x, v.y), max(v.z, v.w));
    const uint32_t wk = __reduce_max_sync(0xffffffffu, m);
    if (lane == 0) sm.win = wk;
  }
  __syncthreads();
  const uint32_t win = sm.win;
  const int wrow = 2047 - (int)(win & 0x7FFu);
  const int wcta = wrow >> 4;
  const bool st_out = wid < 8 && (cta * 16 + row) != wrow;
  uint4* outp = reinterpret_cast<uint4*>(gout + (size_t)(cta * 16 + row) * D_) + 20 * gqi + tq;
  if (cta >= N1) {
    if (st_out) {
#pragma unroll
      for (int k = 0; k < 5; k++) outp[4 * k] = make_uint4(hreg[4 * k], hreg[4 * k + 1], hreg[4 * k + 2], hreg[4 * k + 3]);
    }
  }
  if (cta >= N1) {
#pragma unroll
    for (int i = 0; i < 4; i++) if (i < 3 || tid < 128) g_y2[cta * 1280 + tid + NTHR * i] = make_uint4(0, 0, 0, 0);
  }
  float* xs = &sm.z[0][0][0];
  float* part = xs + 2048;
  if (cta < N1) {
    if (tid < 80) {
      const uint4 v = poll4(&g_cand[wcta][0][tid]);
      float4* xp = reinterpret_cast<float4*>(xs + tid * 8);
      xp[0] = make_float4(lo_f(v.x), hi_f(v.x), lo_f(v.y), hi_f(v.y));
      xp[1] = make_float4(lo_f(v.z), hi_f(v.z), lo_f(v.w), hi_f(v.w));
    }
    __syncthreads();
    float a[8];
#pragma unroll
    for (int j = 0; j < 8; j++) a[j] = 0.f;
#pragma unroll
    for (int it = 0; it < 10; it++) {
      const float x = xs[rs + 64 * it];
#pragma unroll
      for (int j = 0; j < 8; j++) a[j] = fmaf(x, wf[it][j], a[j]);
    }
    {
      const bool up = lane & 16;
#pragma unroll
      for (int j = 0; j < 4; j++) {
        const float send = up ? a[j] : a[j + 4], keep = up ? a[j + 4] : a[j];
        a[j] = keep + __shfl_xor_sync(0xffffffffu, send, 16);
      }
      const bool up2 = lane & 8;
#pragma unroll
      for (int j = 0; j < 2; j++) {
        const float send = up2 ? a[j] : a[j + 2], keep = up2 ? a[j + 2] : a[j];
        a[j] = keep + __shfl_xor_sync(0xffffffffu, send, 8);
      }
      const bool up3 = lane & 4;
      const float send = up3 ? a[0] : a[1], keep = up3 ? a[1] : a[0];
      a[0] = keep + __shfl_xor_sync(0xffffffffu, send, 4);
      a[0] += __shfl_xor_sync(0xffffffffu, a[0], 2);
      a[0] += __shfl_xor_sync(0xffffffffu, a[0], 1);
      if ((lane & 3) == 0) part[wid * 8 + (lane >> 2)] = a[0];
    }
    __syncthreads();
    if (wid == 0) {
      uint32_t bits = 0;
      if (lane < 24) {
        const int hc2 = lane >> 3, j = lane & 7;
        const float gt = rbf(part[(2 * hc2) * 8 + j] + part[(2 * hc2 + 1) * 8 + j]);
        const float up = rbf(part[(6 + 2 * hc2) * 8 + j] + part[(6 + 2 * hc2 + 1) * 8 + j]);
        const float sg = rbf(gt / (1.f + __expf(-gt)));
        bits = __bfloat16_as_ushort(__float2bfloat16_rn(sg * up));
      }
      const uint32_t nb = __shfl_down_sync(0xffffffffu, bits, 1);
      const uint32_t pw = bits | (nb << 16);
      const uint32_t w1 = __shfl_down_sync(0xffffffffu, pw, 2), w2 = __shfl_down_sync(0xffffffffu, pw, 4), w3 = __shfl_down_sync(0xffffffffu, pw, 6);
      const uint4 mine = enc4(make_uint4(pw, w1, w2, w3));
#pragma unroll
      for (int i = 0; i < 4; i++) {
        const int t = lane + 32 * i;
        const int cons = t / 3, ck = t - 3 * cons;
        uint4 v;
        v.x = __shfl_sync(0xffffffffu, mine.x, 8 * ck); v.y = __shfl_sync(0xffffffffu, mine.y, 8 * ck);
        v.z = __shfl_sync(0xffffffffu, mine.z, 8 * ck); v.w = __shfl_sync(0xffffffffu, mine.w, 8 * ck);
        if (t < 3 * N2) st_pub4(&g_act[cons][cta * 3 + ck], v);
      }
      __syncwarp();
      bar_arrive(7, 384);
    } else {
      bar_sync(7, 384);
    }
#pragma unroll
    for (int i = 0; i < 4; i++) if (i < 3 || tid < 128) g_y2[cta * 1280 + tid + NTHR * i] = make_uint4(0, 0, 0, 0);
    if (st_out) {
#pragma unroll
      for (int k = 0; k < 5; k++) outp[4 * k] = make_uint4(hreg[4 * k], hreg[4 * k + 1], hreg[4 * k + 2], hreg[4 * k + 3]);
    }
  } else if (cta < N1 + N2) {
    const int j2 = cta - N1;
    uint4 rowv = make_uint4(0, 0, 0, 0);
    if (tid < 192) {
      const uint4 v = poll4(&g_act[j2][tid]);
      float4* xp = reinterpret_cast<float4*>(xs + tid * 8);
      xp[0] = make_float4(lo_f(v.x), hi_f(v.x), lo_f(v.y), hi_f(v.y));
      xp[1] = make_float4(lo_f(v.z), hi_f(v.z), lo_f(v.w), hi_f(v.w));
    } else if (tid < 196) {
      const int t = tid - 192;
      rowv = poll4(&g_cand[wcta][t >> 1][j2 * 2 + (t & 1)]);
      reinterpret_cast<uint4*>(part + 256)[t] = rowv;
    }
    __syncthreads();
    const int hc = lane & 1;
    float a[8];
#pragma unroll
    for (int j = 0; j < 8; j++) a[j] = 0.f;
#pragma unroll
    for (int it = 0; it < 8; it++) {
      const float x = xs[rs + 192 * it];
#pragma unroll
      for (int j = 0; j < 8; j++) a[j] = fmaf(x, wf[it][j], a[j]);
    }
    {
      const bool up = lane & 16;
#pragma unroll
      for (int j = 0; j < 4; j++) {
        const float send = up ? a[j] : a[j + 4], keep = up ? a[j + 4] : a[j];
        a[j] = keep + __shfl_xor_sync(0xffffffffu, send, 16);
      }
      const bool up2 = lane & 8;
#pragma unroll
      for (int j = 0; j < 2; j++) {
        const float send = up2 ? a[j] : a[j + 2], keep = up2 ? a[j + 2] : a[j];
        a[j] = keep + __shfl_xor_sync(0xffffffffu, send, 8);
      }
      const bool up3 = lane & 4;
      const float send = up3 ? a[0] : a[1], keep = up3 ? a[1] : a[0];
      a[0] = keep + __shfl_xor_sync(0xffffffffu, send, 4);
      a[0] += __shfl_xor_sync(0xffffffffu, a[0], 2);
      if ((lane & 2) == 0) part[wid * 16 + hc * 8 + (lane >> 2)] = a[0];
    }
    __syncthreads();
    if (tid < 16) {
      float y = 0.f;
#pragma unroll
      for (int i = 0; i < 12; i++) y += part[i * 16 + tid];
      const uint32_t ord = win >> 16;
      const uint32_t rb = (ord & 0x8000u) ? (ord ^ 0x8000u) : (ord ^ 0xFFFFu);
      const float r = __uint_as_float(rb << 16);
      const float sg = rbf(1.f / (1.f + __expf(-r)));
      const float yy = rbf(rbf(y) * sg);
      const unsigned short* rv = reinterpret_cast<const unsigned short*>(part + 256);
      const float hn = __uint_as_float((uint32_t)rv[tid] << 16), h = __uint_as_float((uint32_t)rv[16 + tid] << 16);
      gout[(size_t)wrow * D_ + j2 * 16 + tid] = __float2bfloat16_rn(h + rbf(hn + yy));
    }
  }
}

}

typedef CUresult (*EncodeFn)(CUtensorMap*, CUtensorMapDataType, cuuint32_t, void*, const cuuint64_t*, const cuuint64_t*,
                             const cuuint32_t*, const cuuint32_t*, CUtensorMapInterleave, CUtensorMapSwizzle,
                             CUtensorMapL2promotion, CUtensorMapFloatOOBfill);

extern "C" void kernel_launch(void* const* d_in, const int* in_sizes, int n_in, void* d_out, int out_size) {
  (void)in_sizes; (void)n_in; (void)out_size;
  static EncodeFn encode = nullptr;
  static CUtensorMap tmg, tmu, tmd;
  static void* cached[3] = {nullptr, nullptr, nullptr};
  if (!encode) {
    cudaFuncSetAttribute(fused_kernel, cudaFuncAttributeMaxDynamicSharedMemorySize, (int)sizeof(Smem));
    void* fn = nullptr;
    cudaDriverEntryPointQueryResult qr;
    cudaGetDriverEntryPoint("cuTensorMapEncodeTiled", &fn, cudaEnableDefault, &qr);
    encode = (EncodeFn)fn;
  }
  if (cached[0] != d_in[8] || cached[1] != d_in[9] || cached[2] != d_in[10]) {
    const cuuint32_t es[2] = {1, 1};
    {
      const cuuint64_t dims[2] = {F_, D_}, strides[1] = {F_ * 2};
      const cuuint32_t box[2] = {24, 160};
      encode(&tmg, CU_TENSOR_MAP_DATA_TYPE_BFLOAT16, 2, d_in[8], dims, strides, box, es, CU_TENSOR_MAP_INTERLEAVE_NONE,
             CU_TENSOR_MAP_SWIZZLE_NONE, CU_TENSOR_MAP_L2_PROMOTION_NONE, CU_TENSOR_MAP_FLOAT_OOB_FILL_NONE);
      encode(&tmu, CU_TENSOR_MAP_DATA_TYPE_BFLOAT16, 2, d_in[9], dims, strides, box, es, CU_TENSOR_MAP_INTERLEAVE_NONE,
             CU_TENSOR_MAP_SWIZZLE_NONE, CU_TENSOR_MAP_L2_PROMOTION_NONE, CU_TENSOR_MAP_FLOAT_OOB_FILL_NONE);
    }
    {
      const cuuint64_t dims[2] = {D_, F_}, strides[1] = {D_ * 2};
      const cuuint32_t box[2] = {16, 256};
      encode(&tmd, CU_TENSOR_MAP_DATA_TYPE_BFLOAT16, 2, d_in[10], dims, strides, box, es, CU_TENSOR_MAP_INTERLEAVE_NONE,
             CU_TENSOR_MAP_SWIZZLE_NONE, CU_TENSOR_MAP_L2_PROMOTION_NONE, CU_TENSOR_MAP_FLOAT_OOB_FILL_NONE);
    }
    cached[0] = d_in[8]; cached[1] = d_in[9]; cached[2] = d_in[10];
  }
  fused_kernel<<<NCTA, NTHR, sizeof(Smem), cudaStreamPerThread>>>(
      tmg, tmu, tmd, (const bf16*)d_in[0], (const bf16*)d_in[1], (const bf16*)d_in[2], (const bf16*)d_in[3],
      (const bf16*)d_in[4], (const bf16*)d_in[5], (const bf16*)d_in[7], (bf16*)d_out);
}
```
